```python
import torch

def _softmax(x, axis=-1):
    return torch.softmax(x, dim=axis)
def _gelu(x):
    return torch.nn.functional.gelu(x, approximate="tanh")
def _silu(x):
    return torch.nn.functional.silu(x)
def _sigmoid(x):
    return torch.sigmoid(x)
def _layernorm(x, axis=-1, eps=1e-5):
    m = x.mean(dim=axis, keepdim=True)
    v = x.var(dim=axis, keepdim=True, unbiased=False)
    return (x - m) / torch.sqrt(v + eps)
def _scatter_add(tgt, idx, src, axis=0):
    return tgt.clone().index_add_(axis, idx, src)
def _segment_sum(src, seg, n):
    out = torch.zeros((n,) + src.shape[1:], dtype=src.dtype)
    return out.index_add_(0, seg, src)
def _pad(x, pw):
    flat = tuple(v for pair in reversed(pw) for v in pair)
    return torch.nn.functional.pad(x, flat)

kernel_name = 'interleave_layers__softmax_full_mha__moe_arch_mod__prompt'

def setup_inputs():

    _w = (lambda a: (lambda t: t.to(torch.bfloat16) if t.is_floating_point() else t)(torch.as_tensor(a)))
    def _A_setup():
        B, S, D = 1, 2048, 1024
        return {
            "x": _w((lambda *s: torch.randn(*s, dtype=torch.bfloat16) * 0.05)(B, S, D)),
            "wqkv": _w((lambda *s: torch.randn(*s, dtype=torch.bfloat16) * 0.05)(D, 3 * D)),
            "wo": _w((lambda *s: torch.randn(*s, dtype=torch.bfloat16) * 0.05)(D, D)),
        }
    _A_in = _A_setup()

    def _B_setup():
        B, S, D, F, C = 1, 2048, 1024, 3584, 1
        return {
            "x": _w((lambda *s: torch.randn(*s, dtype=torch.bfloat16) * 0.05)(B, S, D)),
            "w_r": _w((lambda *s: torch.randn(*s, dtype=torch.bfloat16) * 0.05)(D)),
            "w_gate": _w((lambda *s: torch.randn(*s, dtype=torch.bfloat16) * 0.05)(D, F)),
            "w_up": _w((lambda *s: torch.randn(*s, dtype=torch.bfloat16) * 0.05)(D, F)),
            "w_down": _w((lambda *s: torch.randn(*s, dtype=torch.bfloat16) * 0.05)(F, D)),
        }
    _B_in = _B_setup()

    return {
        "A_x": _A_in["x"],
        "A_wqkv": _A_in["wqkv"],
        "A_wo": _A_in["wo"],
        "B_x": _B_in["x"],
        "B_w_r": _B_in["w_r"],
        "B_w_gate": _B_in["w_gate"],
        "B_w_up": _B_in["w_up"],
        "B_w_down": _B_in["w_down"],
    }

def reference(A_x, A_wqkv, A_wo, B_x, B_w_r, B_w_gate, B_w_up, B_w_down):
    def _A_ref(x, wqkv, wo):
        B, S, D = x.shape
        H = 32; Dh = D // H
        qkv = (lambda x, *d: x.permute(*d))((x @ wqkv).reshape(B, S, 3, H, Dh), 2, 0, 3, 1, 4)
        q, k, v = qkv[0], qkv[1], qkv[2]
        scale = Dh ** -0.5
        scores = torch.einsum("bhqd,bhkd->bhqk", q, k) * scale
        p = _softmax(scores, axis=-1)
        o = torch.einsum("bhqk,bhkd->bhqd", p, v)
        return (lambda x, *d: x.permute(*d))(o, 0, 2, 1, 3).reshape(B, S, D) @ wo

    def _B_ref(x, w_r, w_gate, w_up, w_down):
        B, S, D = x.shape
        C = 1
        r = x @ w_r
        idx = torch.argsort(-r, axis=-1)[:, :C]
        idx_e = (lambda x, n, axis: torch.repeat_interleave(x, n, dim=axis))(idx.reshape(B, C, 1), D, axis=2)
        x_sel = (lambda x, i, axis: torch.take_along_dim(x, i, dim=axis))(x, idx_e, axis=1)
        g = _silu(x_sel @ w_gate)
        u = x_sel @ w_up
        y = (g * u) @ w_down
        r_sel = _sigmoid((lambda x, i, axis: torch.take_along_dim(x, i, dim=axis))(r, idx, axis=1))
        y = y * r_sel.reshape(B, C, 1)
        b_off = (torch.arange(B) * S).reshape(B, 1)
        flat_idx = (idx + b_off).reshape(B * C)
        zero = (x * 0.0).reshape(B * S, D)
        upd = _scatter_add(zero, flat_idx, y.reshape(B * C, D), axis=0)
        return x + upd.reshape(B, S, D)

    x = A_x
    x = x + _A_ref(_layernorm(x, axis=-1), A_wqkv, A_wo)
    x = x + _B_ref(_layernorm(x, axis=-1), B_w_r, B_w_gate, B_w_up, B_w_down)
    x = x + _A_ref(_layernorm(x, axis=-1), A_wqkv, A_wo)
    x = x + _B_ref(_layernorm(x, axis=-1), B_w_r, B_w_gate, B_w_up, B_w_down)
    return x
```

```cpp
#include <cuda_runtime.h>
#include <cuda_bf16.h>
#include <cuda_fp16.h>
#include <cuda.h>
#include <cudaTypedefs.h>
#include <stdint.h>

namespace {

typedef __nv_bfloat16 bf16;

constexpr int S_ = 2048, D_ = 1024, NH = 32, FF = 3584, NFC = FF / 32;
constexpr float LN_EPS = 1e-5f;
constexpr float QSCALE = 0.17677669529663687f * 1.4426950408889634f;
constexpr uint32_t SENT = 0xFFFFFFFFu;

constexpr int KV_TILE = 16384;
__device__ __align__(1024) char g_kv[NH * 16 * KV_TILE];
__device__ __align__(1024) char g_o[32 * 2 * 16 * 4096];
__device__ __align__(1024) bf16 g_x[S_ * D_];
__device__ float g_csum[8 * 3 * D_];
__device__ float g_wsq[8 * 96];
__device__ float2 g_rs0[S_];
__device__ __align__(16) float4 g_sums[2][S_];
__device__ __align__(16) uint32_t g_ypart[2][NFC][D_];
__device__ __align__(16) uint32_t g_x2row[D_];
__device__ __align__(16) uint32_t g_fix[3 * D_];
__device__ uint32_t g_c0;
__device__ uint32_t g_kvc[2][NH][8];
__device__ uint32_t g_oc[2][16][2];
__device__ __align__(32) uint32_t g_xc[2][8];
struct RouteOut { int idx; float r; float mean; float rstd; };

constexpr uint32_t SB = 1024;

__device__ __forceinline__ uint32_t smem_u32(const void* p) { return (uint32_t)__cvta_generic_to_shared(p); }
__device__ __forceinline__ void mbar_init(uint32_t bar, int cnt) { asm volatile("mbarrier.init.shared::cta.b64 [%0], %1;" :: "r"(bar), "r"(cnt) : "memory"); }
__device__ __forceinline__ void mbar_expect_tx(uint32_t bar, uint32_t bytes) { asm volatile("mbarrier.arrive.expect_tx.shared::cta.b64 _, [%0], %1;" :: "r"(bar), "r"(bytes) : "memory"); }
__device__ __forceinline__ void mbar_arrive(uint32_t bar) { asm volatile("mbarrier.arrive.shared::cta.b64 _, [%0];" :: "r"(bar) : "memory"); }
__device__ __forceinline__ void mbar_wait(uint32_t bar, uint32_t parity) {
    asm volatile("{\n.reg .pred p;\n.reg .u32 n;\nmov.u32 n, 0;\n"
                 "LAB_WAIT:\nmbarrier.try_wait.parity.shared::cta.b64 p, [%0], %1, 0x989680;\n@p bra LAB_DONE;\n"
                 "add.u32 n, n, 1;\nsetp.lt.u32 p, n, 400;\n@p bra LAB_WAIT;\ntrap;\nLAB_DONE:\n}" :: "r"(bar), "r"(parity) : "memory");
}
__device__ __forceinline__ void mbar_arrive_elect(uint32_t bar) {
    asm volatile("{\n.reg .pred p;\nelect.sync _|p, 0xffffffff;\n@p mbarrier.arrive.shared::cta.b64 _, [%0];\n}" :: "r"(bar) : "memory");
}
__device__ __forceinline__ int tid_now() { int v; asm volatile("mov.u32 %0, %%tid.x;" : "=r"(v)); return v; }
__device__ __forceinline__ int cta_now() { int v; asm volatile("mov.u32 %0, %%ctaid.x;" : "=r"(v)); return v; }
__device__ __forceinline__ int warp_uniform(int v) { return __shfl_sync(0xffffffffu, v, 0); }
__device__ __forceinline__ void fence_mbar_init() { asm volatile("fence.mbarrier_init.release.cluster;" ::: "memory"); }
__device__ __forceinline__ void fence_async_smem() { asm volatile("fence.proxy.async.shared::cta;" ::: "memory"); }
__device__ __forceinline__ void fence_async_global() { asm volatile("fence.proxy.async.global;" ::: "memory"); }
__device__ __forceinline__ void named_sync(int id, int n) { asm volatile("bar.sync %0, %1;" :: "r"(id), "r"(n) : "memory"); }
__device__ __forceinline__ bool named_any(bool p, int id) {
    uint32_t r;
    asm volatile("{\n.reg .pred a, b;\nsetp.ne.u32 a, %1, 0;\nbarrier.cta.red.or.pred b, %2, 128, a;\nselp.u32 %0, 1, 0, b;\n}" : "=r"(r) : "r"((uint32_t)p), "r"(id) : "memory");
    return r != 0;
}
__device__ __forceinline__ void bulk_load(uint32_t dst, const void* src, uint32_t bytes, uint32_t bar) {
    asm volatile("cp.async.bulk.shared::cluster.global.mbarrier::complete_tx::bytes [%0], [%1], %2, [%3];" :: "r"(dst), "l"(src), "r"(bytes), "r"(bar) : "memory");
}
__device__ __forceinline__ void bulk_store(void* dst, uint32_t src, uint32_t bytes) {
    asm volatile("cp.async.bulk.global.shared::cta.bulk_group [%0], [%1], %2;" :: "l"(dst), "r"(src), "r"(bytes) : "memory");
}
__device__ __forceinline__ void bulk_commit() { asm volatile("cp.async.bulk.commit_group;" ::: "memory"); }
__device__ __forceinline__ void bulk_wait() { asm volatile("cp.async.bulk.wait_group 0;" ::: "memory"); }
__device__ __forceinline__ void bulk_wait_read() { asm volatile("cp.async.bulk.wait_group.read 0;" ::: "memory"); }
__device__ __forceinline__ void l2_prefetch(const void* src, uint32_t bytes) {
    asm volatile("cp.async.bulk.prefetch.L2.global [%0], %1;" :: "l"(src), "r"(bytes) : "memory");
}
__device__ __forceinline__ void tma_load(uint32_t dst, const CUtensorMap* tm, int c0, int c1, uint32_t bar) {
    asm volatile("cp.async.bulk.tensor.2d.shared::cluster.global.mbarrier::complete_tx::bytes [%0], [%1, {%3, %4}], [%2];"
                 :: "r"(dst), "l"(tm), "r"(bar), "r"(c0), "r"(c1) : "memory");
}
__device__ __forceinline__ void tma_load3(uint32_t dst, const CUtensorMap* tm, int c0, int c1, int c2, uint32_t bar) {
    asm volatile("cp.async.bulk.tensor.3d.shared::cluster.global.mbarrier::complete_tx::bytes [%0], [%1, {%3, %4, %5}], [%2];"
                 :: "r"(dst), "l"(tm), "r"(bar), "r"(c0), "r"(c1), "r"(c2) : "memory");
}
__device__ __forceinline__ void tma_load4(uint32_t dst, const CUtensorMap* tm, int c0, int c1, int c2, int c3, uint32_t bar) {
    asm volatile("cp.async.bulk.tensor.4d.shared::cluster.global.mbarrier::complete_tx::bytes [%0], [%1, {%3, %4, %5, %6}], [%2];"
                 :: "r"(dst), "l"(tm), "r"(bar), "r"(c0), "r"(c1), "r"(c2), "r"(c3) : "memory");
}
__device__ __forceinline__ void tma_store(const CUtensorMap* tm, uint32_t src, int c0, int c1) {
    asm volatile("cp.async.bulk.tensor.2d.global.shared::cta.bulk_group [%0, {%2, %3}], [%1];" :: "l"(tm), "r"(src), "r"(c0), "r"(c1) : "memory");
}
__device__ __forceinline__ void tma_prefetch(const CUtensorMap* tm, int c0, int c1) {
    asm volatile("cp.async.bulk.prefetch.tensor.2d.L2.global [%0, {%1, %2}];" :: "l"(tm), "r"(c0), "r"(c1) : "memory");
}
__device__ __forceinline__ void tm_prefetch(const CUtensorMap* tm) { asm volatile("prefetch.tensormap [%0];" :: "l"(tm) : "memory"); }
__device__ __forceinline__ uint32_t lds32(uint32_t a) { uint32_t v; asm volatile("ld.shared.b32 %0, [%1];" : "=r"(v) : "r"(a) : "memory"); return v; }
__device__ __forceinline__ float ldsf(uint32_t a) { return __uint_as_float(lds32(a)); }
__device__ __forceinline__ float2 lds64f(uint32_t a) { float2 v; asm volatile("ld.shared.v2.f32 {%0, %1}, [%2];" : "=f"(v.x), "=f"(v.y) : "r"(a) : "memory"); return v; }
__device__ __forceinline__ uint4 lds128(uint32_t a) { uint4 v; asm volatile("ld.shared.v4.b32 {%0, %1, %2, %3}, [%4];" : "=r"(v.x), "=r"(v.y), "=r"(v.z), "=r"(v.w) : "r"(a) : "memory"); return v; }
__device__ __forceinline__ void sts32(uint32_t a, uint32_t v) { asm volatile("st.shared.b32 [%0], %1;" :: "r"(a), "r"(v) : "memory"); }
__device__ __forceinline__ void stsf(uint32_t a, float v) { sts32(a, __float_as_uint(v)); }
__device__ __forceinline__ void sts64f(uint32_t a, float x, float y) { asm volatile("st.shared.v2.f32 [%0], {%1, %2};" :: "r"(a), "f"(x), "f"(y) : "memory"); }
__device__ __forceinline__ void sts128(uint32_t a, const uint4& v) { asm volatile("st.shared.v4.b32 [%0], {%1, %2, %3, %4};" :: "r"(a), "r"(v.x), "r"(v.y), "r"(v.z), "r"(v.w) : "memory"); }
__device__ __forceinline__ void stsm4(uint32_t a, uint32_t x, uint32_t y, uint32_t z, uint32_t w) {
    asm volatile("stmatrix.sync.aligned.m8n8.x4.shared.b16 [%0], {%1, %2, %3, %4};" :: "r"(a), "r"(x), "r"(y), "r"(z), "r"(w) : "memory");
}
__device__ __forceinline__ void ldsm4(uint32_t& a0, uint32_t& a1, uint32_t& a2, uint32_t& a3, uint32_t addr) {
    asm volatile("ldmatrix.sync.aligned.m8n8.x4.shared.b16 {%0,%1,%2,%3}, [%4];" : "=r"(a0), "=r"(a1), "=r"(a2), "=r"(a3) : "r"(addr) : "memory");
}
__device__ __forceinline__ void ldsm4t(uint32_t& a0, uint32_t& a1, uint32_t& a2, uint32_t& a3, uint32_t addr) {
    asm volatile("ldmatrix.sync.aligned.m8n8.x4.trans.shared.b16 {%0,%1,%2,%3}, [%4];" : "=r"(a0), "=r"(a1), "=r"(a2), "=r"(a3) : "r"(addr) : "memory");
}
__device__ __forceinline__ void mma_bf16(float (&c)[4], uint32_t a0, uint32_t a1, uint32_t a2, uint32_t a3, uint32_t b0, uint32_t b1) {
    asm("mma.sync.aligned.m16n8k16.row.col.f32.bf16.bf16.f32 {%0,%1,%2,%3}, {%4,%5,%6,%7}, {%8,%9}, {%0,%1,%2,%3};"
        : "+f"(c[0]), "+f"(c[1]), "+f"(c[2]), "+f"(c[3]) : "r"(a0), "r"(a1), "r"(a2), "r"(a3), "r"(b0), "r"(b1));
}
__device__ __forceinline__ void stg128_pred(void* p, const uint4& v, bool on) {
    asm volatile("{\n.reg .pred q;\nsetp.ne.u32 q, %5, 0;\n@q st.global.v4.b32 [%0], {%1, %2, %3, %4};\n}"
                 :: "l"(p), "r"(v.x), "r"(v.y), "r"(v.z), "r"(v.w), "r"((uint32_t)on) : "memory");
}
__device__ __forceinline__ uint32_t ld_relaxed(const void* p) { uint32_t v; asm volatile("ld.relaxed.gpu.global.u32 %0, [%1];" : "=r"(v) : "l"(p) : "memory"); return v; }
__device__ __forceinline__ uint4 ld_relaxed4(const void* p) {
    uint4 v; asm volatile("ld.relaxed.gpu.global.v4.b32 {%0, %1, %2, %3}, [%4];" : "=r"(v.x), "=r"(v.y), "=r"(v.z), "=r"(v.w) : "l"(p) : "memory"); return v;
}
__device__ __forceinline__ void st_relaxed(void* p, uint32_t v) { asm volatile("st.relaxed.gpu.global.u32 [%0], %1;" :: "l"(p), "r"(v) : "memory"); }
__device__ __forceinline__ void st_relaxed4(void* p, const uint4& v) {
    asm volatile("st.relaxed.gpu.global.v4.b32 [%0], {%1, %2, %3, %4};" :: "l"(p), "r"(v.x), "r"(v.y), "r"(v.z), "r"(v.w) : "memory");
}
__device__ __forceinline__ uint32_t not_sent(float v) { const uint32_t u = __float_as_uint(v); return u == SENT ? 0x7FFFFFFFu : u; }
__device__ __forceinline__ bool has_sent(const uint4& v) { return v.x == SENT || v.y == SENT || v.z == SENT || v.w == SENT; }
constexpr uint32_t SPIN_MAX = 1u << 22;
__device__ __forceinline__ void spin_check(uint32_t n) { asm volatile("{\n.reg .pred p;\nsetp.ge.u32 p, %0, %1;\n@p st.global.u32 [%2], %0;\n}" :: "r"(n), "n"(SPIN_MAX), "l"(0ull) : "memory"); }
__device__ __forceinline__ void ctr_arrive(uint32_t* c) { asm volatile("red.release.gpu.global.add.u32 [%0], 1;" :: "l"(c) : "memory"); }
__device__ __forceinline__ void ctr_wait(const uint32_t* c, uint32_t target) {
    asm volatile("{\n.reg .pred p;\n.reg .u32 n, v;\nmov.u32 n, 0;\n"
                 "LAB_WAIT:\nld.acquire.gpu.global.u32 v, [%0];\nsetp.ge.u32 p, v, %1;\n@p bra LAB_DONE;\n"
                 "add.u32 n, n, 1;\nsetp.lt.u32 p, n, 0x400000;\n@p bra LAB_WAIT;\ntrap;\nLAB_DONE:\n}" :: "l"(c), "r"(target) : "memory");
}
__device__ __forceinline__ void publish(uint32_t* c) { bulk_wait(); fence_async_global(); ctr_arrive(c); }

__device__ __forceinline__ void wg_fence() { asm volatile("wgmma.fence.sync.aligned;" ::: "memory"); }
__device__ __forceinline__ void wg_commit() { asm volatile("wgmma.commit_group.sync.aligned;" ::: "memory"); }
template <int N> __device__ __forceinline__ void wg_wait() { asm volatile("wgmma.wait_group.sync.aligned %0;" :: "n"(N) : "memory"); }
template <int N> __device__ __forceinline__ void reg_inc() { asm volatile("setmaxnreg.inc.sync.aligned.u32 %0;" :: "n"(N)); }
template <int N> __device__ __forceinline__ void reg_dec() { asm volatile("setmaxnreg.dec.sync.aligned.u32 %0;" :: "n"(N)); }
__host__ __device__ constexpr uint64_t desc_plain(uint32_t addr, uint32_t lbo, uint32_t sbo) {
    return (uint64_t)((addr & 0x3FFFF) >> 4) | ((uint64_t)(lbo >> 4) << 16) | ((uint64_t)(sbo >> 4) << 32);
}
__host__ __device__ constexpr uint64_t desc_sw128(uint32_t addr, uint32_t lbo, uint32_t sbo) { return desc_plain(addr, lbo, sbo) | (1ull << 62); }

__device__ __forceinline__ float ex2(float x) { float y; asm("ex2.approx.ftz.f32 %0, %1;" : "=f"(y) : "f"(x)); return y; }
__device__ __forceinline__ uint32_t pack_bf16(float lo, float hi) { uint32_t r; asm("cvt.rn.bf16x2.f32 %0, %1, %2;" : "=r"(r) : "f"(hi), "f"(lo)); return r; }
__device__ __forceinline__ uint32_t pack_f16(float lo, float hi) { uint32_t r; asm("cvt.rn.f16x2.f32 %0, %1, %2;" : "=r"(r) : "f"(hi), "f"(lo)); return r; }
__device__ __forceinline__ float bf_lo(uint32_t v) { return __uint_as_float(v << 16); }
__device__ __forceinline__ float bf_hi(uint32_t v) { return __uint_as_float(v & 0xFFFF0000u); }
__device__ __forceinline__ float bf_round(float x) { return __uint_as_float(pack_bf16(0.f, x)); }
__device__ __forceinline__ uint32_t badd2(uint32_t a, uint32_t b) { uint32_t r; asm("add.rn.bf16x2 %0, %1, %2;" : "=r"(r) : "r"(a), "r"(b)); return r; }
__device__ __forceinline__ void h2_unpack(uint32_t v, float& lo, float& hi) {
    asm("{.reg .f16 l, h; mov.b32 {l, h}, %2; cvt.f32.f16 %0, l; cvt.f32.f16 %1, h;}" : "=f"(lo), "=f"(hi) : "r"(v));
}
__device__ __forceinline__ uint32_t add_ln2(uint32_t x, float rstd, float nb) { return badd2(x, pack_bf16(fmaf(bf_lo(x), rstd, nb), fmaf(bf_hi(x), rstd, nb))); }
__device__ __forceinline__ float warp_sum(float v) {
    #pragma unroll
    for (int o = 16; o > 0; o >>= 1) v += __shfl_xor_sync(0xffffffffu, v, o);
    return v;
}
__device__ __forceinline__ float warp_max(float v) {
    #pragma unroll
    for (int o = 16; o > 0; o >>= 1) v = fmaxf(v, __shfl_xor_sync(0xffffffffu, v, o));
    return v;
}
__device__ __forceinline__ uint32_t redux_max(uint32_t v) { uint32_t r; asm volatile("redux.sync.max.u32 %0, %1, 0xffffffff;" : "=r"(r) : "r"(v)); return r; }
__device__ __forceinline__ uint32_t redux_min(uint32_t v) { uint32_t r; asm volatile("redux.sync.min.u32 %0, %1, 0xffffffff;" : "=r"(r) : "r"(v)); return r; }

#define TL(i)

__device__ __forceinline__ void wg_gemm_n128(float (&d)[64], uint64_t desca, uint64_t desc) {
    asm volatile("{\n.reg .pred p;\nsetp.ne.b32 p, 1, 0;\n"
        "wgmma.mma_async.sync.aligned.m64n128k16.f32.bf16.bf16 "
        "{%0,%1,%2,%3,%4,%5,%6,%7,%8,%9,%10,%11,%12,%13,%14,%15,%16,%17,%18,%19,%20,%21,%22,%23,%24,%25,%26,%27,%28,%29,%30,%31,%32,%33,%34,%35,%36,%37,%38,%39,%40,%41,%42,%43,%44,%45,%46,%47,%48,%49,%50,%51,%52,%53,%54,%55,%56,%57,%58,%59,%60,%61,%62,%63}, "
        "%64, %65, p, 1, 1, 0, 1;\n}\n"
        : "+f"(d[0]), "+f"(d[1]), "+f"(d[2]), "+f"(d[3]), "+f"(d[4]), "+f"(d[5]), "+f"(d[6]), "+f"(d[7]),
          "+f"(d[8]), "+f"(d[9]), "+f"(d[10]), "+f"(d[11]), "+f"(d[12]), "+f"(d[13]), "+f"(d[14]), "+f"(d[15]),
          "+f"(d[16]), "+f"(d[17]), "+f"(d[18]), "+f"(d[19]), "+f"(d[20]), "+f"(d[21]), "+f"(d[22]), "+f"(d[23]),
          "+f"(d[24]), "+f"(d[25]), "+f"(d[26]), "+f"(d[27]), "+f"(d[28]), "+f"(d[29]), "+f"(d[30]), "+f"(d[31]),
          "+f"(d[32]), "+f"(d[33]), "+f"(d[34]), "+f"(d[35]), "+f"(d[36]), "+f"(d[37]), "+f"(d[38]), "+f"(d[39]),
          "+f"(d[40]), "+f"(d[41]), "+f"(d[42]), "+f"(d[43]), "+f"(d[44]), "+f"(d[45]), "+f"(d[46]), "+f"(d[47]),
          "+f"(d[48]), "+f"(d[49]), "+f"(d[50]), "+f"(d[51]), "+f"(d[52]), "+f"(d[53]), "+f"(d[54]), "+f"(d[55]),
          "+f"(d[56]), "+f"(d[57]), "+f"(d[58]), "+f"(d[59]), "+f"(d[60]), "+f"(d[61]), "+f"(d[62]), "+f"(d[63])
        : "l"(desca), "l"(desc));
}
__device__ __forceinline__ void wg_gemm_n192(float (&d)[96], uint64_t desca, uint64_t desc) {
    asm volatile("{\n.reg .pred p;\nsetp.ne.b32 p, 1, 0;\n"
        "wgmma.mma_async.sync.aligned.m64n192k16.f32.bf16.bf16 "
        "{%0,%1,%2,%3,%4,%5,%6,%7,%8,%9,%10,%11,%12,%13,%14,%15,%16,%17,%18,%19,%20,%21,%22,%23,%24,%25,%26,%27,%28,%29,%30,%31,%32,%33,%34,%35,%36,%37,%38,%39,%40,%41,%42,%43,%44,%45,%46,%47,%48,%49,%50,%51,%52,%53,%54,%55,%56,%57,%58,%59,%60,%61,%62,%63,%64,%65,%66,%67,%68,%69,%70,%71,%72,%73,%74,%75,%76,%77,%78,%79,%80,%81,%82,%83,%84,%85,%86,%87,%88,%89,%90,%91,%92,%93,%94,%95}, "
        "%96, %97, p, 1, 1, 0, 1;\n}\n"
        : "+f"(d[0]), "+f"(d[1]), "+f"(d[2]), "+f"(d[3]), "+f"(d[4]), "+f"(d[5]), "+f"(d[6]), "+f"(d[7]),
          "+f"(d[8]), "+f"(d[9]), "+f"(d[10]), "+f"(d[11]), "+f"(d[12]), "+f"(d[13]), "+f"(d[14]), "+f"(d[15]),
          "+f"(d[16]), "+f"(d[17]), "+f"(d[18]), "+f"(d[19]), "+f"(d[20]), "+f"(d[21]), "+f"(d[22]), "+f"(d[23]),
          "+f"(d[24]), "+f"(d[25]), "+f"(d[26]), "+f"(d[27]), "+f"(d[28]), "+f"(d[29]), "+f"(d[30]), "+f"(d[31]),
          "+f"(d[32]), "+f"(d[33]), "+f"(d[34]), "+f"(d[35]), "+f"(d[36]), "+f"(d[37]), "+f"(d[38]), "+f"(d[39]),
          "+f"(d[40]), "+f"(d[41]), "+f"(d[42]), "+f"(d[43]), "+f"(d[44]), "+f"(d[45]), "+f"(d[46]), "+f"(d[47]),
          "+f"(d[48]), "+f"(d[49]), "+f"(d[50]), "+f"(d[51]), "+f"(d[52]), "+f"(d[53]), "+f"(d[54]), "+f"(d[55]),
          "+f"(d[56]), "+f"(d[57]), "+f"(d[58]), "+f"(d[59]), "+f"(d[60]), "+f"(d[61]), "+f"(d[62]), "+f"(d[63]),
          "+f"(d[64]), "+f"(d[65]), "+f"(d[66]), "+f"(d[67]), "+f"(d[68]), "+f"(d[69]), "+f"(d[70]), "+f"(d[71]),
          "+f"(d[72]), "+f"(d[73]), "+f"(d[74]), "+f"(d[75]), "+f"(d[76]), "+f"(d[77]), "+f"(d[78]), "+f"(d[79]),
          "+f"(d[80]), "+f"(d[81]), "+f"(d[82]), "+f"(d[83]), "+f"(d[84]), "+f"(d[85]), "+f"(d[86]), "+f"(d[87]),
          "+f"(d[88]), "+f"(d[89]), "+f"(d[90]), "+f"(d[91]), "+f"(d[92]), "+f"(d[93]), "+f"(d[94]), "+f"(d[95])
        : "l"(desca), "l"(desc));
}
__device__ __forceinline__ void wg_qk_init(uint32_t (&d)[32], uint64_t desca, uint64_t desc) {
    asm volatile("{\n.reg .pred p;\nsetp.ne.b32 p, 0, 0;\n"
        "wgmma.mma_async.sync.aligned.m64n128k16.f16.f16.f16 "
        "{%0,%1,%2,%3,%4,%5,%6,%7,%8,%9,%10,%11,%12,%13,%14,%15,%16,%17,%18,%19,%20,%21,%22,%23,%24,%25,%26,%27,%28,%29,%30,%31}, "
        "%32, %33, p, 1, 1, 0, 0;\n}\n"
        : "=r"(d[0]), "=r"(d[1]), "=r"(d[2]), "=r"(d[3]), "=r"(d[4]), "=r"(d[5]), "=r"(d[6]), "=r"(d[7]),
          "=r"(d[8]), "=r"(d[9]), "=r"(d[10]), "=r"(d[11]), "=r"(d[12]), "=r"(d[13]), "=r"(d[14]), "=r"(d[15]),
          "=r"(d[16]), "=r"(d[17]), "=r"(d[18]), "=r"(d[19]), "=r"(d[20]), "=r"(d[21]), "=r"(d[22]), "=r"(d[23]),
          "=r"(d[24]), "=r"(d[25]), "=r"(d[26]), "=r"(d[27]), "=r"(d[28]), "=r"(d[29]), "=r"(d[30]), "=r"(d[31])
        : "l"(desca), "l"(desc));
}
__device__ __forceinline__ void wg_qk_acc(uint32_t (&d)[32], uint64_t desca, uint64_t desc) {
    asm volatile("{\n.reg .pred p;\nsetp.ne.b32 p, 1, 0;\n"
        "wgmma.mma_async.sync.aligned.m64n128k16.f16.f16.f16 "
        "{%0,%1,%2,%3,%4,%5,%6,%7,%8,%9,%10,%11,%12,%13,%14,%15,%16,%17,%18,%19,%20,%21,%22,%23,%24,%25,%26,%27,%28,%29,%30,%31}, "
        "%32, %33, p, 1, 1, 0, 0;\n}\n"
        : "+r"(d[0]), "+r"(d[1]), "+r"(d[2]), "+r"(d[3]), "+r"(d[4]), "+r"(d[5]), "+r"(d[6]), "+r"(d[7]),
          "+r"(d[8]), "+r"(d[9]), "+r"(d[10]), "+r"(d[11]), "+r"(d[12]), "+r"(d[13]), "+r"(d[14]), "+r"(d[15]),
          "+r"(d[16]), "+r"(d[17]), "+r"(d[18]), "+r"(d[19]), "+r"(d[20]), "+r"(d[21]), "+r"(d[22]), "+r"(d[23]),
          "+r"(d[24]), "+r"(d[25]), "+r"(d[26]), "+r"(d[27]), "+r"(d[28]), "+r"(d[29]), "+r"(d[30]), "+r"(d[31])
        : "l"(desca), "l"(desc));
}
__device__ __forceinline__ void wg_pv_init(uint32_t (&d)[10], uint32_t a0, uint32_t a1, uint32_t a2, uint32_t a3, uint64_t desc) {
    asm volatile("{\n.reg .pred p;\nsetp.ne.b32 p, 0, 0;\n"
        "wgmma.mma_async.sync.aligned.m64n40k16.f16.f16.f16 "
        "{%0,%1,%2,%3,%4,%5,%6,%7,%8,%9}, "
        "{%10,%11,%12,%13}, %14, p, 1, 1, 1;\n}\n"
        : "=r"(d[0]), "=r"(d[1]), "=r"(d[2]), "=r"(d[3]), "=r"(d[4]), "=r"(d[5]), "=r"(d[6]), "=r"(d[7]),
          "=r"(d[8]), "=r"(d[9])
        : "r"(a0), "r"(a1), "r"(a2), "r"(a3), "l"(desc));
}
__device__ __forceinline__ void wg_pv_acc(uint32_t (&d)[10], uint32_t a0, uint32_t a1, uint32_t a2, uint32_t a3, uint64_t desc) {
    asm volatile("{\n.reg .pred p;\nsetp.ne.b32 p, 1, 0;\n"
        "wgmma.mma_async.sync.aligned.m64n40k16.f16.f16.f16 "
        "{%0,%1,%2,%3,%4,%5,%6,%7,%8,%9}, "
        "{%10,%11,%12,%13}, %14, p, 1, 1, 1;\n}\n"
        : "+r"(d[0]), "+r"(d[1]), "+r"(d[2]), "+r"(d[3]), "+r"(d[4]), "+r"(d[5]), "+r"(d[6]), "+r"(d[7]),
          "+r"(d[8]), "+r"(d[9])
        : "r"(a0), "r"(a1), "r"(a2), "r"(a3), "l"(desc));
}

constexpr int Q_ABYTES = 256 * 64 * 2, Q_STB = Q_ABYTES + 192 * 64 * 2;
constexpr int OFF_SIDE = 3 * Q_STB;
constexpr int OFF_XS = OFF_SIDE + 49152;
constexpr int OFF_CS = OFF_XS + 4096;
constexpr int OFF_RC = OFF_CS + 768;
constexpr int OFF_FIX = OFF_RC + 2048;
constexpr int A_TILE = KV_TILE + 2048, A_WIN = 2 * A_TILE;
constexpr int OFF_QA = 3 * A_WIN;
constexpr int OFF_FE = 147456;
constexpr int OFF_XT = 196608;
__host__ __device__ constexpr uint32_t o_stage(uint32_t s) { return s == 3 ? OFF_QA : s == 2 ? 0 : (s + 1) * A_WIN; }
__host__ __device__ constexpr uint32_t gu_piece(uint32_t i) { return i < 3 ? OFF_FE + i * 16384 : i < 6 ? (i - 1) * 16384 : (i - 6) * 16384; }
constexpr int OFF_FD = 5 * 16384;
constexpr int OFF_BAR = OFF_XT + 32768;
constexpr int OFF_PART = OFF_BAR + 640;
constexpr int OFF_RED = OFF_PART + 2048;
constexpr int OFF_RT = OFF_RED + 128;
constexpr int OFF_M = OFF_RT + 80;
constexpr int K_SMEM = OFF_M + 96;
static_assert(K_SMEM <= 232448 && OFF_FIX + 768 <= OFF_BAR && OFF_QA + 32768 <= OFF_FE && OFF_FD + 65536 == OFF_FE, "smem");
constexpr int M_SC = 0,
              M_IVS = 24,
              M_ISC = 32,
              M_OK = 40,
              M_WS = 48,
              M_RIDX = 60,
              M_DUMP = 64;
constexpr uint32_t BB = SB + OFF_BAR;
constexpr uint32_t B_EPI = BB, B_KV0 = BB + 8, B_KV1 = BB + 24, B_SL2 = BB + 40, B_OST = BB + 48, B_QAF = BB + 80, B_RES = BB + 88, B_RES2 = BB + 96,
                   B_XST = BB + 104, B_FE = BB + 120, B_FL = BB + 128, B_GD = BB + 200, B_DD = BB + 208, B_RT = BB + 216,
                   B_PR = BB + 224, B_SW = BB + 248,
                   B_OF = BB + 256, B_OE = BB + 288, B_RING = BB + 320;
constexpr uint32_t R_QF = 0, R_QE = 24, R_AF = 48, R_AE = 72, R_SZ = 96;
static_assert(320 + 2 * R_SZ <= 640, "barriers");

struct Maps { CUtensorMap x0, x, wqkv, wo, r, g, u, d; };

__device__ __forceinline__ void prep_work(const bf16* __restrict__ x0, const CUtensorMap* tmW, int t) {
    const int c = blockIdx.x, lane = t & 31, warp = t >> 5;
    const int ki = c >> 4, n = c & 15;
    constexpr uint32_t red = SB + OFF_SIDE, xs = red + 4096;
    if (t == 0) {
        mbar_expect_tx(B_PR, 32768);
        bulk_load(xs, x0 + (size_t)c * 16 * D_, 32768, B_PR);
        mbar_expect_tx(B_PR + 8, 16384);
        tma_load(xs + 32768, tmW, 2 * D_ + n * 64, ki * 128, B_PR + 8);
        tma_load(xs + 32768 + 8192, tmW, 2 * D_ + n * 64, ki * 128 + 64, B_PR + 8);
    }
    if (t < 32) g_sums[t >> 4][c * 16 + (t & 15)] = make_float4(0.f, 0.f, 0.f, 0.f);
    const uint4 sent = make_uint4(SENT, SENT, SENT, SENT);
    for (int i = t; i < 2 * NFC * 2; i += 96) reinterpret_cast<uint4*>(&g_ypart[0][0][0])[c * (2 * NFC * 2) + i] = sent;
    if (t < 2) reinterpret_cast<uint4*>(g_x2row)[c * 2 + t] = sent;
    else if (t < 8) reinterpret_cast<uint4*>(g_fix)[c * 6 + t - 2] = sent;
    else if (t < 12) (&g_kvc[0][0][0])[c * 4 + t - 8] = 0u;
    else if (t == 12 && c < 64) (&g_oc[0][0][0])[c] = 0u;
    else if (t == 13 && c < 16) (&g_xc[0][0])[c] = 0u;
    mbar_wait(B_PR, 0);
    #pragma unroll 1
    for (int r = warp; r < 16; r += 3) {
        float s = 0.f, q = 0.f;
        #pragma unroll
        for (int i = 0; i < 4; i++) {
            const uint4 u = lds128(xs + r * 2048 + (lane + 32 * i) * 16);
            const float f[8] = {bf_lo(u.x), bf_hi(u.x), bf_lo(u.y), bf_hi(u.y), bf_lo(u.z), bf_hi(u.z), bf_lo(u.w), bf_hi(u.w)};
            #pragma unroll
            for (int e = 0; e < 8; e++) { s += f[e]; q = fmaf(f[e], f[e], q); }
        }
        #pragma unroll
        for (int o = 16; o > 0; o >>= 1) { s += __shfl_xor_sync(0xffffffffu, s, o); q += __shfl_xor_sync(0xffffffffu, q, o); }
        const float mean = s * (1.f / D_);
        const float var = fmaxf(q * (1.f / D_) - mean * mean, 0.f);
        if (lane == 0) g_rs0[c * 16 + r] = make_float2(rsqrtf(var + LN_EPS), mean);
    }
    named_sync(2, 96);
    if (t == 0) {
        mbar_expect_tx(B_PR + 16, 32768);
        #pragma unroll
        for (int b = 0; b < 4; b++) tma_load(xs + b * 8192, tmW, (b >> 1) * D_ + n * 64, ki * 128 + (b & 1) * 64, B_PR + 16);
    }
    const int j = t & 7, rg = t >> 3;
    #pragma unroll 1
    for (int blk = 0; blk < 3; blk++) {
        const int type = blk == 0 ? 2 : blk - 1;
        const uint32_t wb = xs + type * 16384;
        if (blk < 2) mbar_wait(B_PR + 8 + 8 * blk, 0);
        float cs[8];
        uint32_t z2[4] = {0u, 0u, 0u, 0u};
        #pragma unroll
        for (int i = 0; i < 8; i++) cs[i] = 0.f;
        #pragma unroll 4
        for (int r = rg; r < 128; r += 12) {
            const uint4 u = lds128(wb + r * 128 + ((j ^ (r & 7)) << 4));
            cs[0] += bf_lo(u.x); cs[1] += bf_hi(u.x); cs[2] += bf_lo(u.y); cs[3] += bf_hi(u.y);
            cs[4] += bf_lo(u.z); cs[5] += bf_hi(u.z); cs[6] += bf_lo(u.w); cs[7] += bf_hi(u.w);
            asm("fma.rn.bf16x2 %0, %1, %1, %0;" : "+r"(z2[0]) : "r"(u.x));
            asm("fma.rn.bf16x2 %0, %1, %1, %0;" : "+r"(z2[1]) : "r"(u.y));
            asm("fma.rn.bf16x2 %0, %1, %1, %0;" : "+r"(z2[2]) : "r"(u.z));
            asm("fma.rn.bf16x2 %0, %1, %1, %0;" : "+r"(z2[3]) : "r"(u.w));
        }
        #pragma unroll
        for (int i = 0; i < 8; i++) { cs[i] += __shfl_xor_sync(0xffffffffu, cs[i], 8); cs[i] += __shfl_xor_sync(0xffffffffu, cs[i], 16); }
        float z = ((bf_lo(z2[0]) + bf_hi(z2[0])) + (bf_lo(z2[1]) + bf_hi(z2[1]))) + ((bf_lo(z2[2]) + bf_hi(z2[2])) + (bf_lo(z2[3]) + bf_hi(z2[3])));
        z += __shfl_xor_sync(0xffffffffu, z, 1); z += __shfl_xor_sync(0xffffffffu, z, 2);
        z += __shfl_xor_sync(0xffffffffu, z, 8); z += __shfl_xor_sync(0xffffffffu, z, 16);
        if (lane < 8) {
            #pragma unroll
            for (int i = 0; i < 8; i++) stsf(red + (warp * 200 + type * 64 + j * 8 + i) * 4, cs[i]);
            if ((lane & 3) == 0) stsf(red + (warp * 200 + 192 + type * 2 + (lane >> 2)) * 4, z);
        }
    }
    named_sync(2, 96);
    for (int i = t; i < 198; i += 96) {
        const float v = ldsf(red + i * 4) + ldsf(red + (200 + i) * 4) + ldsf(red + (400 + i) * 4);
        if (i < 192) g_csum[ki * (3 * D_) + (i >> 6) * D_ + n * 64 + (i & 63)] = v;
        else g_wsq[ki * 96 + ((i - 192) >> 1) * 32 + n * 2 + (i & 1)] = v;
    }
    named_sync(2, 96);
    if (t == 0) { ctr_arrive(&g_c0); ctr_wait(&g_c0, 128); }
    named_sync(2, 96);
}

__device__ __forceinline__ float pow2_inv(float b) {
    const int e = min(max((int)(__float_as_uint(b) >> 23) + 1, 20), 234);
    return __uint_as_float((uint32_t)(254 - e) << 23);
}
__device__ __forceinline__ void epi_inputs(int L) {
    const int t = tid_now() - 288, mt = cta_now() >> 4, nt = cta_now() & 15;
    float p[2][8], r0[3], r1[3];
    #pragma unroll
    for (int k = 0; k < 2; k++)
        #pragma unroll
        for (int q = 0; q < 8; q++) p[k][q] = __ldcg(g_csum + q * (3 * D_) + ((t + 96 * k) >> 6) * D_ + nt * 64 + ((t + 96 * k) & 63));
    #pragma unroll
    for (int k = 0; k < 3; k++) {
        const int row = mt * 256 + min(t + 96 * k, 255);
        const float2 s = __ldcg(L == 0 ? &g_rs0[row] : reinterpret_cast<const float2*>(&g_sums[0][row]));
        r0[k] = s.x; r1[k] = s.y;
    }
    #pragma unroll
    for (int k = 0; k < 2; k++) stsf(SB + OFF_CS + (t + 96 * k) * 4, ((p[k][0] + p[k][1]) + (p[k][2] + p[k][3])) + ((p[k][4] + p[k][5]) + (p[k][6] + p[k][7])));
    #pragma unroll
    for (int k = 0; k < 3; k++) {
        if (L != 0) {
            const float mean = r0[k] * (1.f / D_);
            const float var = fmaxf(r1[k] * (1.f / D_) - mean * mean, 0.f);
            const float a = 1.f + rsqrtf(var + LN_EPS);
            r0[k] = a * rsqrtf(a * a * var + LN_EPS); r1[k] = mean;
        }
        if (t + 96 * k < 256) sts64f(SB + OFF_RC + (t + 96 * k) * 8, r0[k], r1[k]);
    }
    if (L == 0 && t < 32) {
        float z = 0.f;
        if (t < 6) {
            #pragma unroll
            for (int q = 0; q < 8; q++) z += __ldcg(g_wsq + q * 96 + (t >> 1) * 32 + nt * 2 + (t & 1));
        }
        const float b = sqrtf(z) * (t < 2 ? 34.f * QSCALE : 34.f);
        const float sc = t < 4 ? fminf(pow2_inv(b) * 32768.f, 1.f) : pow2_inv(b);
        const float bk = __shfl_down_sync(0xffffffffu, b, 2), sk = __shfl_down_sync(0xffffffffu, sc, 2);
        if (t < 6) stsf(SB + OFF_M + M_SC + t * 4, t < 2 ? sc * QSCALE : sc);
        if (t < 2) { stsf(SB + OFF_M + M_ISC + t * 4, 1.f / (sc * sk)); sts32(SB + OFF_M + M_OK + t * 4, sc == 1.f && sk == 1.f && b * bk < 60000.f); }
        if (t == 4 || t == 5) stsf(SB + OFF_M + M_IVS + (t - 4) * 4, 1.f / sc);
    }
}

__device__ __forceinline__ int ypos_col(int p) { return (p >> 7) * 128 + ((p >> 1) & 7) * 16 + (p & 1) * 8 + ((p >> 4) & 7); }

__device__ __forceinline__ float ffn_finish(int L, const RouteOut& rt) {
    const int t = tid_now() - 288, c = cta_now(), lane = t & 31;
    const float xv = bf_lo(__ldcg(reinterpret_cast<const unsigned short*>(g_x) + (size_t)rt.idx * D_ + ypos_col(c * 8 + (t & 7))));
    const uint32_t* src = &g_ypart[L][t >> 1][c * 8 + (t & 1) * 4];
    uint4 v[3];
    uint32_t n = 0;
    do {
        v[0] = ld_relaxed4(src); v[1] = ld_relaxed4(src + 48 * D_);
        v[2] = t < 2 * NFC - 192 ? ld_relaxed4(src + 96 * D_) : make_uint4(0u, 0u, 0u, 0u);
    } while ((has_sent(v[0]) || has_sent(v[1]) || has_sent(v[2])) && ++n < SPIN_MAX);
    spin_check(n);
    __syncwarp();
    float a[4] = {__uint_as_float(v[0].x) + __uint_as_float(v[1].x) + __uint_as_float(v[2].x), __uint_as_float(v[0].y) + __uint_as_float(v[1].y) + __uint_as_float(v[2].y),
                  __uint_as_float(v[0].z) + __uint_as_float(v[1].z) + __uint_as_float(v[2].z), __uint_as_float(v[0].w) + __uint_as_float(v[1].w) + __uint_as_float(v[2].w)};
    #pragma unroll
    for (int o = 2; o < 32; o <<= 1)
        #pragma unroll
        for (int i = 0; i < 4; i++) a[i] += __shfl_xor_sync(0xffffffffu, a[i], o);
    if (lane < 2) sts128(SB + OFF_RED + (t >> 5) * 32 + lane * 16, make_uint4(__float_as_uint(a[0]), __float_as_uint(a[1]), __float_as_uint(a[2]), __float_as_uint(a[3])));
    named_sync(2, 96);
    const uint32_t ra = SB + OFF_RED + (t & 7) * 4;
    const float y = bf_round(ldsf(ra) + ldsf(ra + 32) + ldsf(ra + 64));
    const float rsel = bf_round(1.f / (1.f + __expf(-bf_round(rt.r))));
    const float xn = bf_round((xv - rt.mean) * rt.rstd);
    return bf_round(xv + bf_round(xn + bf_round(y * rsel)));
}

__device__ __forceinline__ void routed_qkv(int ridx) {
    const int t = tid_now() - 288, c = cta_now(), lane = t & 31, warp = t >> 5;
    constexpr uint32_t red = SB + OFF_RED + 96;
    {
        uint4 v[3];
        uint32_t n = 0;
        do {
            v[0] = ld_relaxed4(g_x2row + t * 4); v[1] = ld_relaxed4(g_x2row + (t + 96) * 4);
            v[2] = t < 64 ? ld_relaxed4(g_x2row + (t + 192) * 4) : make_uint4(0u, 0u, 0u, 0u);
        } while ((has_sent(v[0]) || has_sent(v[1]) || has_sent(v[2])) && ++n < SPIN_MAX);
        spin_check(n);
        __syncwarp();
        float f[12];
        float s = 0.f;
        #pragma unroll
        for (int i = 0; i < 3; i++) { f[4*i] = __uint_as_float(v[i].x); f[4*i+1] = __uint_as_float(v[i].y); f[4*i+2] = __uint_as_float(v[i].z); f[4*i+3] = __uint_as_float(v[i].w); }
        #pragma unroll
        for (int i = 0; i < 12; i++) s += f[i];
        s = warp_sum(s);
        if (lane == 0) stsf(red + warp * 4, s);
        named_sync(2, 96);
        const float mean = (ldsf(red) + ldsf(red + 4) + ldsf(red + 8)) * (1.f / D_);
        float q = 0.f;
        #pragma unroll
        for (int i = 0; i < 12; i++) { f[i] -= mean; if (i < 8 || t < 64) q = fmaf(f[i], f[i], q); }
        q = warp_sum(q);
        if (lane == 0) stsf(red + 16 + warp * 4, q);
        named_sync(2, 96);
        const float rstd = rsqrtf((ldsf(red + 16) + ldsf(red + 20) + ldsf(red + 24)) * (1.f / D_) + LN_EPS);
        #pragma unroll
        for (int i = 0; i < 3; i++)
            if (i < 2 || t < 64) sts128(SB + OFF_XS + (t + 96 * i) * 16, make_uint4(pack_bf16(0.f, f[4*i] * rstd), pack_bf16(0.f, f[4*i+1] * rstd), pack_bf16(0.f, f[4*i+2] * rstd), pack_bf16(0.f, f[4*i+3] * rstd)));
    }
    named_sync(2, 96);
    mbar_wait(B_SW, 0);
    float a[8];
    #pragma unroll
    for (int i = 0; i < 8; i++) a[i] = 0.f;
    const uint32_t wa = SB + OFF_SIDE + t * 16, xa = SB + OFF_XS + (t / 3) * 4;
    #pragma unroll 4
    for (int i = 0; i < 32; i++) {
        const uint4 u = lds128(wa + i * 1536);
        const float xv = ldsf(xa + i * 128);
        a[0] = fmaf(xv, bf_lo(u.x), a[0]); a[1] = fmaf(xv, bf_hi(u.x), a[1]); a[2] = fmaf(xv, bf_lo(u.y), a[2]); a[3] = fmaf(xv, bf_hi(u.y), a[3]);
        a[4] = fmaf(xv, bf_lo(u.z), a[4]); a[5] = fmaf(xv, bf_hi(u.z), a[5]); a[6] = fmaf(xv, bf_lo(u.w), a[6]); a[7] = fmaf(xv, bf_hi(u.w), a[7]);
    }
    named_sync(2, 96);
    sts128(SB + OFF_SIDE + t * 32, make_uint4(__float_as_uint(a[0]), __float_as_uint(a[1]), __float_as_uint(a[2]), __float_as_uint(a[3])));
    sts128(SB + OFF_SIDE + t * 32 + 16, make_uint4(__float_as_uint(a[4]), __float_as_uint(a[5]), __float_as_uint(a[6]), __float_as_uint(a[7])));
    named_sync(2, 96);
    {
        float y = 0.f;
        #pragma unroll
        for (int i = 0; i < 8; i++) y += ldsf(SB + OFF_SIDE + ((t & 3) * 8 + i) * 96 + (t >> 2) * 4);
        y += __shfl_xor_sync(0xffffffffu, y, 1); y += __shfl_xor_sync(0xffffffffu, y, 2);
        if ((t & 3) == 0) st_relaxed(g_fix + c * 24 + (t >> 2), not_sent(y));
    }
    if ((ridx >> 8) == (c >> 4) && t < 48) {
        uint4 v;
        uint32_t n = 0;
        do {
            v = ld_relaxed4(g_fix + (t >> 4) * D_ + (c & 15) * 64 + (t & 15) * 4);
        } while (has_sent(v) && ++n < SPIN_MAX);
        spin_check(n);
        sts128(SB + OFF_FIX + t * 16, v);
    }
    __syncwarp();
}

__device__ __forceinline__ void residual_prep() {
    const int t = tid_now() - 288, c = cta_now(), row0 = (c >> 4) * 256 + (c & 1) * 128, col0 = ((c & 15) >> 1) * 128;
    for (int i = t; i < 128; i += 96) {
        const float2 s = __ldcg(reinterpret_cast<const float2*>(&g_sums[0][row0 + i]));
        const float mean = s.x * (1.f / D_);
        const float rstd = rsqrtf(fmaxf(s.y * (1.f / D_) - mean * mean, 0.f) + LN_EPS);
        sts64f(SB + OFF_PART + i * 8, rstd, -mean * rstd);
    }
    named_sync(2, 96);
    #pragma unroll 2
    for (int i = t; i < 2048; i += 96) {
        const uint4 u = lds128(SB + OFF_XT + i * 16);
        const float2 r = lds64f(SB + OFF_PART + ((i >> 3) & 127) * 8);
        sts128(SB + OFF_XT + i * 16, make_uint4(add_ln2(u.x, r.x, r.y), add_ln2(u.y, r.x, r.y), add_ln2(u.z, r.x, r.y), add_ln2(u.w, r.x, r.y)));
    }
    const uint32_t lr = lds32(SB + OFF_M + M_RIDX) - row0;
    if (lr < 128u) {
        named_sync(2, 96);
        if (t < 16) {
            const uint4 a = ld_relaxed4(g_x2row + col0 + t * 8), b = ld_relaxed4(g_x2row + col0 + t * 8 + 4);
            sts128(SB + OFF_XT + (t >> 3) * 16384 + lr * 128 + (((t & 7) ^ (lr & 7)) << 4),
                   make_uint4(__byte_perm(a.x, a.y, 0x7632), __byte_perm(a.z, a.w, 0x7632), __byte_perm(b.x, b.y, 0x7632), __byte_perm(b.z, b.w, 0x7632)));
        }
    }
    __syncwarp();
}

__device__ __forceinline__ void side_role(const Maps& mp, const bf16* __restrict__ x0, const bf16* __restrict__ w_r, bf16* __restrict__ out) {
    prep_work(x0, &mp.wqkv, threadIdx.x - 288);
    epi_inputs(0);
    #pragma unroll 1
    for (int L = 0; L < 2; L++) {
        const int t = tid_now() - 288, lane = t & 31, sw = t >> 5;
        const int c = cta_now(), mt = c >> 4, nt = c & 15;
        __syncwarp();
        if (lane == 0) mbar_arrive(B_EPI);
        if (t == 0) TL(L * 48 + 5);
        if (L == 0) {
            float ws = 0.f;
            for (int i = t; i < D_ / 8; i += 96) {
                const uint4 v = reinterpret_cast<const uint4*>(w_r)[i];
                ws += ((bf_lo(v.x) + bf_hi(v.x)) + (bf_lo(v.y) + bf_hi(v.y))) + ((bf_lo(v.z) + bf_hi(v.z)) + (bf_lo(v.w) + bf_hi(v.w)));
            }
            ws = warp_sum(ws);
            if (lane == 0) stsf(SB + OFF_M + M_WS + sw * 4, ws);
        }
        if (sw < 2 && lane == 0) {
            char* kv = g_kv + ((size_t)(nt * 2) * 16 + mt * 2 + sw) * KV_TILE;
            mbar_wait(B_KV0 + 8 * sw, L);
            bulk_store(kv, SB + sw * A_TILE, KV_TILE);
            bulk_commit();
            publish(&g_kvc[L][nt * 2][mt]);
            if (sw == 0) TL(L * 48 + 6);
            mbar_wait(B_KV1 + 8 * sw, L);
            bulk_store(kv + 16 * KV_TILE, SB + 2 * A_WIN + sw * A_TILE, KV_TILE);
            bulk_commit();
            bulk_wait_read();
            mbar_arrive(B_SL2);
            publish(&g_kvc[L][nt * 2 + 1][mt]);
            #pragma unroll 1
            for (int p = 0; p < 2; p++) {
                mbar_wait(B_OST + 16 * p + 8 * sw, L);
                #pragma unroll
                for (int u = 0; u < 2; u++) bulk_store(g_o + (size_t)(((mt * 4 + sw * 2 + u) * 2 + p) * 16 + nt) * 4096, SB + OFF_QA + p * 16384 + (sw * 2 + u) * 4096, 4096);
                bulk_commit();
                if (p == 1) { bulk_wait_read(); mbar_arrive(B_QAF); }
                publish(&g_oc[L][mt * 2 + sw][p]);
            }
        }
        __syncwarp();
        mbar_wait(B_QAF, L);
        mbar_wait(B_RES, L);
        if (L == 1) residual_prep();
        if (lane == 0) mbar_arrive(B_RES2);
        if (sw < 2 && lane == 0) {
            mbar_wait(B_XST + 8 * sw, L);
            #pragma unroll
            for (int h = 0; h < 2; h++) tma_store(&mp.x, SB + OFF_XT + h * 16384 + sw * 8192, (nt >> 1) * 128 + h * 64, mt * 256 + (nt & 1) * 128 + sw * 64);
            bulk_commit();
            publish(&g_xc[L][mt]);
            if (sw == 0) TL(L * 48 + 14);
        }
        __syncwarp();
        mbar_wait(B_RT, L);
        RouteOut rt;
        { const uint4 v = lds128(SB + OFF_RT + 64); rt.idx = v.x; rt.r = __uint_as_float(v.y); rt.mean = __uint_as_float(v.z); rt.rstd = __uint_as_float(v.w); }
        if (L == 0) {
            if (t == 0) { sts32(SB + OFF_M + M_RIDX, rt.idx); if (c == 0) g_c0 = 0u; }
            epi_inputs(1);
        }
        const float v = ffn_finish(L, rt);
        if (t == 0) TL(L * 48 + 20);
        if (L == 0) {
            if (t < 8) st_relaxed(g_x2row + ypos_col(c * 8 + t), not_sent(v));
            routed_qkv(rt.idx);
        } else if (t < 8) {
            reinterpret_cast<unsigned short*>(out)[(size_t)rt.idx * D_ + ypos_col(c * 8 + t)] = (unsigned short)(__float_as_uint(v) >> 16);
        }
    }
}

template <int HH>
__device__ __forceinline__ void qkv_epi_head(const float (&acc0)[96], const float (&acc1)[96], const float (&cf)[4], const float (&nm)[4], uint32_t dst, int t) {
    float2 c2[4];
    #pragma unroll
    for (int jj = 0; jj < 4; jj++) c2[jj] = lds64f(SB + OFF_CS + (HH * 32 + jj * 8) * 4 + t * 8);
    const float hs = ldsf(SB + OFF_M + M_SC + HH * 4);
    #pragma unroll
    for (int i = 0; i < 4; i++) {
        const float* a = (i >> 1) ? acc1 : acc0;
        const float sc = cf[i] * hs;
        uint32_t pk[4];
        #pragma unroll
        for (int jj = 0; jj < 4; jj++)
            pk[jj] = pack_f16(fmaf(nm[i], c2[jj].x, a[4 * (4 * HH + jj) + 2 * (i & 1)]) * sc, fmaf(nm[i], c2[jj].y, a[4 * (4 * HH + jj) + 2 * (i & 1) + 1]) * sc);
        stsm4(dst + (i >> 1) * (HH < 2 ? 4096 : 1024) + (i & 1) * 128, pk[0], pk[1], pk[2], pk[3]);
    }
}
__device__ __forceinline__ void qkv_patch(int lr, int lane, uint32_t groups) {
    __syncwarp();
    const int hh = lane >> 2, ch = lane & 3;
    if ((groups >> hh) & 1) {
        const float hs = ldsf(SB + OFF_M + M_SC + hh * 4);
        const uint4 a = lds128(SB + OFF_FIX + lane * 32), b = lds128(SB + OFF_FIX + lane * 32 + 16);
        const uint32_t dst = hh < 2 ? OFF_QA + hh * 16384 + (lr >> 6) * 4096 + ch * 1024 + (lr & 63) * 16
                                    : (hh & 1) * 2 * A_WIN + (lr >> 7) * A_TILE + (hh >> 2) * 8192 + ch * 2048 + (lr & 127) * 16;
        sts128(SB + dst, make_uint4(pack_f16(__uint_as_float(a.x) * hs, __uint_as_float(a.y) * hs), pack_f16(__uint_as_float(a.z) * hs, __uint_as_float(a.w) * hs),
                                    pack_f16(__uint_as_float(b.x) * hs, __uint_as_float(b.y) * hs), pack_f16(__uint_as_float(b.z) * hs, __uint_as_float(b.w) * hs)));
    }
}

__device__ __forceinline__ void qkv_phase(int L, int wg) {
    const uint32_t rb = B_RING + L * R_SZ;
    float acc0[96], acc1[96];
    #pragma unroll
    for (int i = 0; i < 96; i++) { acc0[i] = 0.f; acc1[i] = 0.f; }
    const bool leader = (tid_now() & 127) == 0;
    uint32_t st = 0, ph = 0;
    #pragma unroll 1
    for (int k = 0; k < 16; k++) {
        mbar_wait(rb + R_QF + 8 * st, ph);
        if (threadIdx.x == 0 && k == 0) TL(L * 48 + 1);
        const uint64_t da = desc_sw128(SB, 16, 1024) + ((st * Q_STB + wg * 16384) >> 4);
        const uint64_t db = desc_sw128(SB + Q_ABYTES, 8192, 1024) + ((st * Q_STB) >> 4);
        wg_fence();
        #pragma unroll
        for (int kk = 0; kk < 4; kk++) {
            wg_gemm_n192(acc0, da + kk * 2, db + kk * 128);
            wg_gemm_n192(acc1, da + (8192 >> 4) + kk * 2, db + kk * 128);
        }
        wg_commit();
        if (k > 0) {
            wg_wait<1>();
            if (leader) mbar_arrive(rb + R_QE + 8 * (st == 0 ? 2 : st - 1));
        }
        if (++st == 3) { st = 0; ph ^= 1; }
    }
    const int tid = tid_now(), lane = tid & 31, w = (tid >> 5) & 3, g = lane >> 2, t = lane & 3;
    mbar_wait(B_EPI, L);
    float cf[4], nm[4];
    #pragma unroll
    for (int i = 0; i < 4; i++) { const float2 r = lds64f(SB + OFF_RC + (wg * 128 + w * 16 + g + (i >> 1) * 64 + (i & 1) * 8) * 8); cf[i] = r.x; nm[i] = -r.y; }
    int lr = -1;
    if (L == 1) {
        const int d = (int)lds32(SB + OFF_M + M_RIDX) - (cta_now() >> 4) * 256;
        if ((d >> 7) == wg && ((d >> 4) & 3) == w) lr = d;
    }
    wg_wait<0>();
    if (threadIdx.x == 0) TL(L * 48 + 2);
    named_sync(1, 256);
    const uint32_t dk = SB + wg * A_TILE + (lane >> 3) * 2048 + (w * 16 + (lane & 7)) * 16;
    const uint32_t dq = SB + OFF_QA + wg * 8192 + (lane >> 3) * 1024 + (w * 16 + (lane & 7)) * 16;
    qkv_epi_head<2>(acc0, acc1, cf, nm, dk, t);
    qkv_epi_head<4>(acc0, acc1, cf, nm, dk + 8192, t);
    if (lr >= 0) qkv_patch(lr, lane, 0x14u);
    fence_async_smem();
    __syncwarp();
    mbar_arrive_elect(B_KV0 + 8 * wg);
    qkv_epi_head<3>(acc0, acc1, cf, nm, dk + 2 * A_WIN, t);
    qkv_epi_head<5>(acc0, acc1, cf, nm, dk + 2 * A_WIN + 8192, t);
    qkv_epi_head<0>(acc0, acc1, cf, nm, dq, t);
    qkv_epi_head<1>(acc0, acc1, cf, nm, dq + 16384, t);
    if (lr >= 0) qkv_patch(lr, lane, 0x2Bu);
    #pragma unroll
    for (int s = 0; s < 3; s++) sts128(SB + s * A_WIN + wg * A_TILE + KV_TILE + (tid & 127) * 16, make_uint4(0x3C003C00u, 0x3C003C00u, 0x3C003C00u, 0x3C003C00u));
    fence_async_smem();
    named_sync(1, 256);
    if (leader) { mbar_arrive(B_KV1 + 8 * wg); if (wg == 0) mbar_arrive(rb + R_AF); }
    if (threadIdx.x == 0) TL(L * 48 + 3);
}

struct Unit {
    uint32_t o[10];
    uint32_t bz[2];
    uint32_t sc[2];
    uint32_t ch[2];
};
constexpr uint32_t CH_OK = 0x38003800u;
__device__ __forceinline__ uint32_t hmax2(uint32_t a, uint32_t b) { uint32_t r; asm("max.f16x2 %0, %1, %2;" : "=r"(r) : "r"(a), "r"(b)); return r; }
__device__ __forceinline__ uint32_t hadd2(uint32_t a, uint32_t b) { uint32_t r; asm("add.rn.f16x2 %0, %1, %2;" : "=r"(r) : "r"(a), "r"(b)); return r; }
__device__ __forceinline__ uint32_t hsub2(uint32_t a, uint32_t b) { uint32_t r; asm("sub.rn.f16x2 %0, %1, %2;" : "=r"(r) : "r"(a), "r"(b)); return r; }
__device__ __forceinline__ uint32_t hfma2(uint32_t a, uint32_t b, uint32_t c) { uint32_t r; asm("fma.rn.f16x2 %0, %1, %2, %3;" : "=r"(r) : "r"(a), "r"(b), "r"(c)); return r; }
__device__ __forceinline__ uint32_t exp2_h2(uint32_t s, uint32_t bz, uint32_t& ch) {
    uint32_t z, w, d;
    asm("fma.rn.relu.f16x2 %0, %1, %2, %3;" : "=r"(z) : "r"(s), "r"(0x00400040u), "r"(bz));
    asm("lop3.b32 %0, %1, 0x003F003F, %0, 0xC2;" : "+r"(ch) : "r"(z));
    asm("fma.rn.f16x2 %0, %1, %2, %3;" : "=r"(w) : "r"(ch), "r"(0x30A630A6u), "r"(0xACCCACCCu));
    asm("{.reg .b32 n; neg.f16x2 n, %1; fma.rn.relu.f16x2 %0, n, %1, %2;}" : "=r"(d) : "r"(w), "r"(0x00580058u));
    return (z << 4) - d;
}
__device__ __forceinline__ void exp_tile(uint32_t (&p)[32], const uint32_t (&s)[32], Unit& u) {
    #pragma unroll
    for (int i = 0; i < 32; i++) p[i] = exp2_h2(s[i], u.bz[i & 1], u.ch[i & 1]);
}
__device__ __forceinline__ void issue_qk(uint32_t (&s)[32], uint64_t dq, uint64_t dk) {
    wg_qk_init(s, dq, dk); wg_qk_acc(s, dq + (2048 >> 4), dk + (4096 >> 4));
    wg_commit();
}
template <bool INIT>
__device__ __forceinline__ void issue_pv(uint32_t (&h)[10], const uint32_t (&p)[32], uint64_t dv) {
    #pragma unroll
    for (int k = 0; k < 8; k++) {
        if (INIT && k == 0) wg_pv_init(h, p[0], p[1], p[2], p[3], dv);
        else wg_pv_acc(h, p[4*k], p[4*k+1], p[4*k+2], p[4*k+3], dv + k * 16);
    }
    wg_commit();
}
__device__ __forceinline__ void unit_init(Unit& u, const uint32_t (&s)[32]) {
    uint32_t m0 = s[0], m1 = s[1];
    #pragma unroll
    for (int i = 1; i < 16; i++) { m0 = hmax2(m0, s[2 * i]); m1 = hmax2(m1, s[2 * i + 1]); }
    uint32_t m = hmax2(__byte_perm(m0, m1, 0x5410), __byte_perm(m0, m1, 0x7632));
    m = hmax2(m, __shfl_xor_sync(0xffffffffu, m, 1)); m = hmax2(m, __shfl_xor_sync(0xffffffffu, m, 2));
    float f0, f1; h2_unpack(m, f0, f1);
    u.ch[0] = fabsf(f0) < 1000.f ? CH_OK : 0u; u.ch[1] = fabsf(f1) < 1000.f ? CH_OK : 0u;
    f0 = (18.f - ceilf(f0)) * 3.814697265625e-06f; f1 = (18.f - ceilf(f1)) * 3.814697265625e-06f;
    u.bz[0] = pack_f16(f0, f0); u.bz[1] = pack_f16(f1, f1);
    u.sc[0] = u.sc[1] = 0x3C003C00u;
    #pragma unroll
    for (int i = 0; i < 10; i++) u.o[i] = 0u;
}
template <bool MORE>
__device__ __forceinline__ void unit_flush(Unit& u, const uint32_t (&h)[10]) {
    #pragma unroll
    for (int i = 0; i < 10; i++) u.o[i] = hfma2(u.o[i], u.sc[i & 1], h[i]);
    if (MORE) {
        #pragma unroll
        for (int r = 0; r < 2; r++) {
            const uint32_t ex = u.o[8 + r] & 0x7C007C00u;
            u.sc[r] = 0x84008400u - ex;
            u.bz[r] = hsub2(hadd2(u.bz[r], 0x04800480u), ex >> 4);
        }
    }
}
__device__ __forceinline__ uint32_t unit_store(const Unit& u, uint32_t dst, float ivs, bool head_ok, int lane) {
    uint32_t bad = 0;
    #pragma unroll
    for (int h = 0; h < 2; h++) {
        const uint32_t l = u.o[8 + h] & 0xFFFFu;
        uint32_t b = __ballot_sync(0xffffffffu, !head_ok || (u.ch[h] & CH_OK) != CH_OK || l >= 0x7C00u || l < 0x4000u);
        b |= b >> 1; b |= b >> 2;
        float lf, unused; h2_unpack(l, lf, unused);
        const float inv = __fdividef(ivs, lf);
        uint32_t pk[4];
        #pragma unroll
        for (int j = 0; j < 4; j++) { float x, y; h2_unpack(u.o[2 * j + h], x, y); pk[j] = pack_bf16(x * inv, y * inv); }
        const bool mine = (b >> (4 * (lane & 7))) & 1;
        stsm4(mine ? SB + OFF_M + M_DUMP : dst + h * 128, pk[0], pk[1], pk[2], pk[3]);
        bad |= (__ballot_sync(0xffffffffu, mine) & 0xFFu) << (8 * h);
    }
    return bad;
}
__device__ __forceinline__ void exact_rows(int L, int pass, int wg, uint32_t bad) {
    const int tid = tid_now() & 127, lane = tid & 31, w = tid >> 5;
    const int head = (cta_now() & 15) * 2 + pass;
    const uint32_t scr = SB + OFF_PART + wg * 1024;
    if (lane == 0) sts32(scr + w * 4, bad);
    if (tid < 8) ctr_wait(&g_kvc[L][head][tid], 2);
    named_sync(3 + wg, 128);
    const float isc = ldsf(SB + OFF_M + M_ISC + pass * 4), ivs = ldsf(SB + OFF_M + M_IVS + pass * 4);
    const char* kv = g_kv + (size_t)head * 16 * KV_TILE + tid * 16;
    #pragma unroll 1
    for (int ww = 0; ww < 4; ww++) {
        uint32_t m = lds32(scr + ww * 4);
        #pragma unroll 1
        while (m) {
            const int bit = __ffs(m) - 1;
            m &= m - 1;
            const uint32_t qa = SB + OFF_QA + pass * 16384 + (wg * 2 + (bit >> 4)) * 4096 + (ww * 16 + (bit & 15)) * 16;
            float q[32], a[32], mx = -INFINITY, l = 0.f;
            #pragma unroll
            for (int ch = 0; ch < 4; ch++) {
                const uint4 u = lds128(qa + ch * 1024);
                h2_unpack(u.x, q[8*ch], q[8*ch+1]); h2_unpack(u.y, q[8*ch+2], q[8*ch+3]); h2_unpack(u.z, q[8*ch+4], q[8*ch+5]); h2_unpack(u.w, q[8*ch+6], q[8*ch+7]);
            }
            #pragma unroll
            for (int i = 0; i < 32; i++) a[i] = 0.f;
            #pragma unroll 1
            for (int it = 0; it < 16; it += 4) {
                uint4 u[4][8];
                #pragma unroll
                for (int i = 0; i < 4; i++)
                    #pragma unroll
                    for (int ch = 0; ch < 8; ch++) u[i][ch] = __ldcg(reinterpret_cast<const uint4*>(kv + (it + i) * KV_TILE + ch * 2048));
                float s[4], mn = mx;
                #pragma unroll
                for (int i = 0; i < 4; i++) {
                    s[i] = 0.f;
                    #pragma unroll
                    for (int ch = 0; ch < 4; ch++) {
                        const uint32_t v[4] = {u[i][ch].x, u[i][ch].y, u[i][ch].z, u[i][ch].w};
                        #pragma unroll
                        for (int e = 0; e < 4; e++) { float x, y; h2_unpack(v[e], x, y); s[i] = fmaf(x, q[8*ch + 2*e], fmaf(y, q[8*ch + 2*e + 1], s[i])); }
                    }
                    mn = fmaxf(mn, s[i]);
                }
                const float al = ex2((mx - mn) * isc);
                mx = mn; l *= al;
                #pragma unroll
                for (int i = 0; i < 32; i++) a[i] *= al;
                #pragma unroll
                for (int i = 0; i < 4; i++) {
                    const float p = ex2((s[i] - mx) * isc);
                    l += p;
                    #pragma unroll
                    for (int ch = 0; ch < 4; ch++) {
                        const uint32_t v[4] = {u[i][4 + ch].x, u[i][4 + ch].y, u[i][4 + ch].z, u[i][4 + ch].w};
                        #pragma unroll
                        for (int e = 0; e < 4; e++) { float x, y; h2_unpack(v[e], x, y); a[8*ch + 2*e] = fmaf(p, x, a[8*ch + 2*e]); a[8*ch + 2*e + 1] = fmaf(p, y, a[8*ch + 2*e + 1]); }
                    }
                }
            }
            const float mw = warp_max(mx);
            if (lane == 0) stsf(scr + 16 + w * 4, mw);
            named_sync(3 + wg, 128);
            const float al = ex2((mx - fmaxf(fmaxf(ldsf(scr + 16), ldsf(scr + 20)), fmaxf(ldsf(scr + 24), ldsf(scr + 28)))) * isc);
            l *= al;
            #pragma unroll
            for (int i = 0; i < 32; i++) a[i] *= al;
            l = warp_sum(l);
            #pragma unroll
            for (int j = 0; j < 31; j++) {
                const int o = j < 16 ? 16 : j < 24 ? 8 : j < 28 ? 4 : j < 30 ? 2 : 1, i = j - (32 - 2 * o);
                const bool up = lane & o;
                const float lo = a[i], hi = a[i + o];
                a[i] = (up ? hi : lo) + __shfl_xor_sync(0xffffffffu, up ? lo : hi, o);
            }
            stsf(scr + 32 + (w * 33 + lane) * 4, a[0]);
            if (lane == 0) stsf(scr + 32 + (w * 33 + 32) * 4, l);
            named_sync(3 + wg, 128);
            if (w == 0) {
                float o = 0.f, ls = 0.f;
                #pragma unroll
                for (int i = 0; i < 4; i++) { o += ldsf(scr + 32 + (i * 33 + lane) * 4); ls += ldsf(scr + 32 + (i * 33 + 32) * 4); }
                asm volatile("st.shared.u16 [%0], %1;" :: "r"(qa + (lane >> 3) * 1024 + (lane & 7) * 2), "h"((unsigned short)(pack_bf16(o * ivs / ls, 0.f))) : "memory");
            }
        }
    }
    named_sync(3 + wg, 128);
}

__device__ __forceinline__ void attention_phase(int L, int wg) {
    const uint32_t rb = B_RING + L * R_SZ;
    constexpr uint64_t dk0 = desc_plain(SB, 2048, 128), dv0 = desc_plain(SB + 8192, 128, 2048);
    constexpr int T1 = A_TILE >> 4;
    uint32_t st = 0, ph = 0;
    #pragma unroll 1
    for (int pass = 0; pass < 2; pass++) {
        const uint64_t dqa = desc_plain(SB + OFF_QA, 1024, 128) + (pass * 4 + wg * 2) * (4096 >> 4), dqc = dqa + (4096 >> 4);
        Unit a, c;
        st = warp_uniform(st); ph = warp_uniform(ph);
        uint32_t SA[32], SC[32], PA[32], PC[32], ha[10], hc[10], pst = 0;
        #pragma unroll
        for (int i = 0; i < 10; i++) hc[i] = 0u;
        #pragma unroll
        for (int i = 0; i < 32; i++) PC[i] = 0u;
        mbar_wait(rb + R_AF + 8 * st, ph);
        wg_fence();
        issue_qk(SA, dqa, dk0 + st * (A_WIN >> 4));
        issue_qk(SC, dqc, dk0 + st * (A_WIN >> 4));
        wg_wait<1>();
        unit_init(a, SA);
        exp_tile(PA, SA, a);
        wg_wait<0>();
        unit_init(c, SC);
        #pragma unroll 1
        for (int s = 0;; s++) {
            const uint64_t dkb = dk0 + st * (A_WIN >> 4), dvb = dv0 + st * (A_WIN >> 4);
            uint32_t nst = st + 1, nph = ph;
            if (nst == 3) { nst = 0; nph ^= 1; }
            const uint64_t dkn = dk0 + nst * (A_WIN >> 4);
            wg_fence();
            issue_pv<true>(ha, PA, dvb); issue_qk(SA, dqa, dkb + T1);
            wg_wait<2>();
            if (s > 0) { mbar_arrive_elect(rb + R_AE + 8 * pst); unit_flush<true>(c, hc); }
            else {
                #pragma unroll
                for (int i = 0; i < 32; i++) c.o[i & 7] |= PC[i];
            }
            exp_tile(PC, SC, c);
            wg_fence();
            issue_pv<true>(hc, PC, dvb); issue_qk(SC, dqc, dkb + T1);
            wg_wait<2>();
            exp_tile(PA, SA, a);
            if (s == 7) {
                wg_fence(); issue_pv<false>(ha, PA, dvb + T1);
                wg_wait<1>();
                exp_tile(PC, SC, c);
                wg_fence(); issue_pv<false>(hc, PC, dvb + T1);
                wg_wait<1>();
                unit_flush<false>(a, ha);
                wg_wait<0>();
                unit_flush<false>(c, hc);
                mbar_arrive_elect(rb + R_AE + 8 * st);
                st = nst; ph = nph;
                break;
            }
            mbar_wait(rb + R_AF + 8 * nst, nph);
            wg_fence();
            issue_pv<false>(ha, PA, dvb + T1); issue_qk(SA, dqa, dkn);
            wg_wait<2>();
            exp_tile(PC, SC, c);
            wg_fence();
            issue_pv<false>(hc, PC, dvb + T1); issue_qk(SC, dqc, dkn);
            wg_wait<2>();
            unit_flush<true>(a, ha);
            exp_tile(PA, SA, a);
            pst = st; st = nst; ph = nph;
        }
        const int tid = tid_now(), lane = tid & 31;
        const float ivs = ldsf(SB + OFF_M + M_IVS + pass * 4);
        const bool head_ok = lds32(SB + OFF_M + M_OK + pass * 4) != 0;
        const uint32_t dst = SB + OFF_QA + pass * 16384 + wg * 8192 + (lane >> 3) * 1024 + (((tid >> 5) & 3) * 16 + (lane & 7)) * 16;
        const uint32_t bad = unit_store(a, dst, ivs, head_ok, lane) | unit_store(c, dst + 4096, ivs, head_ok, lane) << 16;
        if (__builtin_expect(named_any(bad != 0, 3 + wg), 0)) {
            exact_rows(L, pass, wg, bad);
        }
        fence_async_smem();
        __syncwarp();
        mbar_arrive_elect(B_OST + 16 * pass + 8 * wg);
        if (threadIdx.x == 0) TL(L * 48 + 8 + pass);
    }
}

__device__ __forceinline__ uint32_t order_bits(float r) { const uint32_t u = __float_as_uint(r); return (u & 0x80000000u) ? ~u : (u | 0x80000000u); }

__device__ __forceinline__ void oproj_phase(int L, int wg, const bf16* __restrict__ w_r, bf16* __restrict__ out) {
    const int c = cta_now(), tid = tid_now(), lane = tid & 31, W = tid >> 5, g = lane >> 2, t = lane & 3;
    const int row0 = (c >> 4) * 256 + (c & 1) * 128, col0 = ((c & 15) >> 1) * 128;
    uint32_t wb[16];
    #pragma unroll
    for (int i = 0; i < 16; i++) {
        wb[i] = g == 0 ? 0x3F803F80u : 0u;
        if (g == 1) wb[i] = __ldg(reinterpret_cast<const uint32_t*>(w_r + col0) + i * 4 + t);
    }
    float acc[64];
    #pragma unroll
    for (int i = 0; i < 64; i++) acc[i] = 0.f;
    #pragma unroll 1
    for (int k = 0; k < 16; k++) {
        const uint32_t s = k & 3;
        mbar_wait(B_OF + 8 * s, (k >> 2) & 1);
        if (tid == 0 && (k & 7) == 0) TL(L * 48 + 10 + (k >> 3));
        const uint64_t da = desc_plain(SB, 1024, 128) + ((o_stage(s) + wg * 8192) >> 4);
        const uint64_t db = desc_sw128(SB + 16384, 8192, 1024) + (o_stage(s) >> 4);
        wg_fence();
        #pragma unroll
        for (int kk = 0; kk < 4; kk++) wg_gemm_n128(acc, da + kk * 128, db + kk * 128);
        wg_commit();
        if (k > 0) {
            wg_wait<1>();
            if ((tid & 127) == 0) mbar_arrive(B_OE + 8 * ((k - 1) & 3));
        }
    }
    mbar_wait(B_RES2, L);
    const uint32_t xa = SB + OFF_XT + (W * 16 + ((lane >> 3) & 1) * 8 + (lane & 7)) * 128, xs = (lane >> 4) ^ (lane & 7);
    uint32_t x[32];
    #pragma unroll
    for (int ks = 0; ks < 8; ks++) ldsm4(x[4*ks], x[4*ks+1], x[4*ks+2], x[4*ks+3], xa + (ks >> 2) * 16384 + ((xs ^ ((ks & 3) * 2)) << 4));
    wg_wait<0>();
    if ((tid & 127) == 0) mbar_arrive(B_OE + 24);
    if (tid == 0) TL(L * 48 + 12);
    {
        float sd[4] = {0.f, 0.f, 0.f, 0.f}, q0[4] = {0.f, 0.f, 0.f, 0.f}, q1[4] = {0.f, 0.f, 0.f, 0.f};
        #pragma unroll
        for (int ks = 0; ks < 8; ks++) {
            #pragma unroll
            for (int i = 0; i < 4; i++) x[4*ks + i] = badd2(x[4*ks + i], pack_bf16(acc[8*ks + 2*i], acc[8*ks + 2*i + 1]));
            mma_bf16(sd, x[4*ks], x[4*ks+1], x[4*ks+2], x[4*ks+3], wb[2*ks], wb[2*ks+1]);
            mma_bf16(q0, x[4*ks], x[4*ks+1], x[4*ks+2], x[4*ks+3], x[4*ks], x[4*ks+2]);
            mma_bf16(q1, x[4*ks], x[4*ks+1], x[4*ks+2], x[4*ks+3], x[4*ks+1], x[4*ks+3]);
        }
        const float s0 = __shfl_sync(0xffffffffu, (g & 1) ? q0[1] : q0[0], 4 * g + (g >> 1));
        const float s1 = __shfl_sync(0xffffffffu, (g & 1) ? q1[3] : q1[2], 4 * g + (g >> 1));
        if (t == 0) {
            float4* p = &g_sums[L][row0 + W * 16 + g];
            asm volatile("red.relaxed.gpu.global.add.v4.f32 [%0], {%1, %2, %3, %4};" :: "l"(p), "f"(sd[0]), "f"(s0), "f"(sd[1]), "f"(1.f) : "memory");
            asm volatile("red.relaxed.gpu.global.add.v4.f32 [%0], {%1, %2, %3, %4};" :: "l"(p + 8), "f"(sd[2]), "f"(s1), "f"(sd[3]), "f"(1.f) : "memory");
        }
    }
    #pragma unroll
    for (int ks = 0; ks < 8; ks++) stsm4(xa + (ks >> 2) * 16384 + ((xs ^ ((ks & 3) * 2)) << 4), x[4*ks], x[4*ks+1], x[4*ks+2], x[4*ks+3]);
    fence_async_smem();
    __syncwarp();
    mbar_arrive_elect(B_XST + 8 * wg);
    if (tid == 0) TL(L * 48 + 13);
    RouteOut rt;
    float2 r0, r1;
    {
        const float ws = ldsf(SB + OFF_M + M_WS) + ldsf(SB + OFF_M + M_WS + 4) + ldsf(SB + OFF_M + M_WS + 8);
        uint4 sv[8];
        uint32_t n = 0;
        bool done;
        do {
            done = true;
            #pragma unroll
            for (int i = 0; i < 8; i++) sv[i] = ld_relaxed4(&g_sums[L][tid + 256 * i]);
            #pragma unroll
            for (int i = 0; i < 8; i++) done = done && sv[i].w == 0x41000000u;
        } while (!done && ++n < SPIN_MAX);
        spin_check(n);
        __syncwarp();
        if (tid == 0) TL(L * 48 + 15);
        uint32_t best = 0;
        rt.idx = 0x7FFFFFFF; rt.r = 0.f; rt.mean = 0.f; rt.rstd = 0.f;
        #pragma unroll
        for (int i = 0; i < 8; i++) {
            const float mean = __uint_as_float(sv[i].x) * (1.f / D_);
            const float rstd = rsqrtf(fmaxf(__uint_as_float(sv[i].y) * (1.f / D_) - mean * mean, 0.f) + LN_EPS);
            const float r = rstd * (__uint_as_float(sv[i].z) - mean * ws);
            const uint32_t k = order_bits(r);
            if (k > best || i == 0) { best = k; rt.idx = tid + 256 * i; rt.r = r; rt.mean = mean; rt.rstd = rstd; }
            if ((uint32_t)(tid + 256 * i - row0) < 128u) sts64f(SB + OFF_PART + (tid & 127) * 8, rstd, -mean * rstd);
        }
        uint32_t m = redux_max(best);
        uint32_t mrow = redux_min(best == m ? rt.idx : 0x7FFFFFFF);
        if (lane == 0) sts64f(SB + OFF_RT + W * 8, __uint_as_float(m), __uint_as_float(mrow));
        named_sync(1, 256);
        const float2 e = lds64f(SB + OFF_RT + (lane & 7) * 8);
        r0 = lds64f(SB + OFF_PART + (W * 16 + g) * 8); r1 = lds64f(SB + OFF_PART + (W * 16 + g + 8) * 8);
        m = redux_max(__float_as_uint(e.x));
        mrow = redux_min(__float_as_uint(e.x) == m ? __float_as_uint(e.y) : 0x7FFFFFFFu);
        if (rt.idx == (int)mrow) sts128(SB + OFF_RT + 64, make_uint4(rt.idx, __float_as_uint(rt.r), __float_as_uint(rt.mean), __float_as_uint(rt.rstd)));
        if (tid >= 248) ctr_wait(&g_xc[L][tid - 248], 32);
        named_sync(1, 256);
        const uint4 v = lds128(SB + OFF_RT + 64);
        rt.idx = v.x; rt.r = __uint_as_float(v.y); rt.mean = __uint_as_float(v.z); rt.rstd = __uint_as_float(v.w);
    }
    if (tid == 0) { mbar_arrive(B_RT); TL(L * 48 + 16); }
    const uint2 xrow = __ldcg(reinterpret_cast<const uint2*>(g_x + (size_t)rt.idx * D_) + tid);
    if (L == 1) {
        #pragma unroll
        for (int ks = 0; ks < 8; ks++)
            stsm4(xa + (ks >> 2) * 16384 + ((xs ^ ((ks & 3) * 2)) << 4), add_ln2(x[4*ks], r0.x, r0.y), add_ln2(x[4*ks+1], r1.x, r1.y),
                  add_ln2(x[4*ks+2], r0.x, r0.y), add_ln2(x[4*ks+3], r1.x, r1.y));
        __syncwarp();
        #pragma unroll
        for (int it = 0; it < 8; it++) {
            const int lr = W * 16 + it * 2 + (lane >> 4), ch = lane & 15;
            const uint4 v = lds128(SB + OFF_XT + (ch >> 3) * 16384 + lr * 128 + (((ch & 7) ^ (lr & 7)) << 4));
            stg128_pred(out + (size_t)(row0 + lr) * D_ + col0 + ch * 8, v, row0 + lr != rt.idx);
        }
    }
    if (c < NFC) {
        const float nb = -rt.mean * rt.rstd;
        const uint32_t n0 = pack_bf16(fmaf(bf_lo(xrow.x), rt.rstd, nb), fmaf(bf_hi(xrow.x), rt.rstd, nb));
        const uint32_t n1 = pack_bf16(fmaf(bf_lo(xrow.y), rt.rstd, nb), fmaf(bf_hi(xrow.y), rt.rstd, nb));
        if (tid == 0) TL(L * 48 + 17);
        mbar_wait(W < 3 ? B_FE : B_FL + 8 * (W - 3), L);
        float gu[4][4];
        #pragma unroll
        for (int i = 0; i < 4; i++) { gu[i][0] = 0.f; gu[i][1] = 0.f; gu[i][2] = 0.f; gu[i][3] = 0.f; }
        const uint32_t ga = SB + gu_piece(W) + ((lane >> 4) * 8 + (lane & 7)) * 64, gs = ((lane >> 3) & 1) ^ ((lane >> 1) & 3);
        #pragma unroll
        for (int ks = 0; ks < 8; ks++) {
            const uint32_t e0 = __shfl_sync(0xffffffffu, n0, 4 * ks + (t >> 1)), o0 = __shfl_sync(0xffffffffu, n1, 4 * ks + (t >> 1));
            const uint32_t e1 = __shfl_sync(0xffffffffu, n0, 4 * ks + 2 + (t >> 1)), o1 = __shfl_sync(0xffffffffu, n1, 4 * ks + 2 + (t >> 1));
            const uint32_t b0 = (t & 1) ? o0 : e0, b1 = (t & 1) ? o1 : e1;
            #pragma unroll
            for (int mb = 0; mb < 4; mb++) {
                uint32_t a0, a1, a2, a3;
                ldsm4t(a0, a1, a2, a3, ga + (mb >> 1) * 8192 + ks * 1024 + ((gs ^ ((mb & 1) * 2)) << 4));
                mma_bf16(gu[mb], a0, a1, a2, a3, b0, b1);
            }
        }
        mbar_arrive_elect(B_GD);
        {
            const float lo = t == 0 ? gu[0][0] : t == 1 ? gu[1][0] : t == 2 ? gu[2][0] : gu[3][0];
            const float hi = t == 0 ? gu[0][2] : t == 1 ? gu[1][2] : t == 2 ? gu[2][2] : gu[3][2];
            stsf(SB + OFF_PART + (W * 64 + t * 16 + g) * 4, lo); stsf(SB + OFF_PART + (W * 64 + t * 16 + g + 8) * 4, hi);
        }
        named_sync(1, 256);
        if (tid == 0) TL(L * 48 + 18);
        float gsum = 0.f, usum = 0.f;
        #pragma unroll
        for (int i = 0; i < 8; i++) { gsum += ldsf(SB + OFF_PART + (i * 64 + lane) * 4); usum += ldsf(SB + OFF_PART + (i * 64 + 32 + lane) * 4); }
        const float gv = bf_round(gsum), uv = bf_round(usum);
        const float hv = bf_round(__fdividef(gv, 1.f + __expf(-gv))) * uv;
        const uint32_t hp = pack_bf16(hv, __shfl_down_sync(0xffffffffu, hv, 1));
        uint32_t hb[4];
        #pragma unroll
        for (int i = 0; i < 4; i++) hb[i] = __shfl_sync(0xffffffffu, hp, 8 * i + 2 * t);
        mbar_wait(B_FL + 8 * (5 + (W >> 1)), L);
        const uint32_t wa = SB + OFF_FD + W * 8192 + ((lane >> 4) * 8 + (lane & 7)) * 128, wsw = ((lane >> 3) & 1) ^ (lane & 7);
        float y[8][4];
        #pragma unroll
        for (int mb = 0; mb < 8; mb++) {
            y[mb][0] = 0.f; y[mb][1] = 0.f; y[mb][2] = 0.f; y[mb][3] = 0.f;
            #pragma unroll
            for (int ks = 0; ks < 2; ks++) {
                uint32_t a0, a1, a2, a3;
                ldsm4t(a0, a1, a2, a3, wa + (mb >> 2) * 4096 + ks * 2048 + ((wsw ^ ((mb & 3) * 2)) << 4));
                mma_bf16(y[mb], a0, a1, a2, a3, hb[2 * ks], hb[2 * ks + 1]);
            }
        }
        uint4 v;
        v.x = not_sent(t == 0 ? y[0][0] : t == 1 ? y[2][0] : t == 2 ? y[4][0] : y[6][0]);
        v.y = not_sent(t == 0 ? y[0][2] : t == 1 ? y[2][2] : t == 2 ? y[4][2] : y[6][2]);
        v.z = not_sent(t == 0 ? y[1][0] : t == 1 ? y[3][0] : t == 2 ? y[5][0] : y[7][0]);
        v.w = not_sent(t == 0 ? y[1][2] : t == 1 ? y[3][2] : t == 2 ? y[5][2] : y[7][2]);
        st_relaxed4(&g_ypart[L][c][tid * 4], v);
    } else {
        mbar_arrive_elect(B_GD);
    }
    mbar_arrive_elect(B_DD);
    if (tid == 0) TL(L * 48 + 19);
}

#define PACE 2
__device__ __forceinline__ void qkv_fill(const CUtensorMap* tx, const CUtensorMap* tw, uint32_t bar, int st, int k) {
    const int mt = blockIdx.x >> 4, nt = blockIdx.x & 15;
    const uint32_t sa = SB + st * Q_STB;
    mbar_expect_tx(bar, Q_STB);
    #pragma unroll
    for (int a = 0; a < 4; a++) tma_load(sa + a * 8192, tx, k * 64, mt * 256 + a * 64, bar);
    #pragma unroll
    for (int b = 0; b < 3; b++) tma_load(sa + Q_ABYTES + b * 8192, tw, b * D_ + nt * 64, k * 64, bar);
}
__device__ __forceinline__ void gu_load(const Maps& mp, int i, uint32_t bar) {
    tma_load(SB + gu_piece(i), &mp.g, blockIdx.x * 32, i * 128, bar);
    tma_load(SB + gu_piece(i) + 8192, &mp.u, blockIdx.x * 32, i * 128, bar);
}
__device__ __forceinline__ void producer_role(const Maps& mp, const bf16* __restrict__ wo, const bf16* __restrict__ w_down) {
    const int c = blockIdx.x, mt = c >> 4, nt = c & 15;
    const bool ffn = c < NFC;
    tm_prefetch(&mp.x); tm_prefetch(&mp.wo); tm_prefetch(&mp.r); tm_prefetch(&mp.g); tm_prefetch(&mp.u); tm_prefetch(&mp.d);
    #pragma unroll 1
    for (int L = 0; L < 2; L++) {
        const uint32_t rb = B_RING + L * R_SZ;
        const CUtensorMap* tx = L == 0 ? &mp.x0 : &mp.x;
        uint32_t st = 0, ph = 1;
        #pragma unroll 1
        for (int k = 0; k < 16; k++) {
            if (L == 1 && k == 0) { ctr_wait(&g_xc[0][mt], 32); fence_async_global(); mbar_wait(B_GD, 0); }
            if (L == 1 && k == 1) mbar_wait(B_DD, 0);
            if (L == 1 || k >= 3) {
                mbar_wait(rb + R_QE + 8 * st, ph);
                qkv_fill(tx, &mp.wqkv, rb + R_QF + 8 * st, st, k);
            }
            if (L == 1 && k >= 3 && k < 7) {
                if (k == 3) mbar_expect_tx(B_SW, 4 * 12288);
                tma_load(SB + OFF_SIDE + (k - 3) * 12288, &mp.r, c * 24, (k - 3) * 256, B_SW);
            }
            if (++st == 3) { st = 0; ph ^= 1; }
        }
        mbar_wait(B_KV0, L);
        st = 1; ph = 1;
        #pragma unroll 1
        for (int w = 1; w < 16; w++) {
            const int head = nt * 2 + (w >> 3), blk = (mt + w) & 7;
            if (w == 2) mbar_wait(B_SL2, L);
            mbar_wait(rb + R_AE + 8 * st, ph);
            ctr_wait(&g_kvc[L][head][blk], 2);
            fence_async_global();
            if (w == 1) TL(L * 48 + 7);
            const char* src = g_kv + ((size_t)head * 16 + blk * 2) * KV_TILE;
            mbar_expect_tx(rb + R_AF + 8 * st, 2 * KV_TILE);
            bulk_load(SB + st * A_WIN, src, KV_TILE, rb + R_AF + 8 * st);
            bulk_load(SB + st * A_WIN + A_TILE, src + KV_TILE, KV_TILE, rb + R_AF + 8 * st);
            if (ffn && w >= 4 && w < 7) {
                if (w == 4) mbar_expect_tx(B_FE, 3 * 16384);
                gu_load(mp, w - 4, B_FE);
            }
            if (w == 7) {
                mbar_expect_tx(B_RES, 32768);
                #pragma unroll
                for (int i = 0; i < 4; i++) tma_load(SB + OFF_XT + i * 8192, tx, (nt >> 1) * 128 + (i >> 1) * 64, mt * 256 + (nt & 1) * 128 + (i & 1) * 64, B_RES);
            }
            if (w == 8) l2_prefetch(reinterpret_cast<const char*>(wo) + (size_t)c * 16384, 16384);
            if (ffn && w >= 9 && w < 14) { tma_prefetch(&mp.g, c * 32, (w - 6) * 128); tma_prefetch(&mp.u, c * 32, (w - 6) * 128); }
            if (ffn && w >= 14) l2_prefetch(reinterpret_cast<const char*>(w_down) + (size_t)c * 65536 + (w - 14) * 32768, 32768);
            if (++st == 3) { st = 0; ph ^= 1; }
        }
        #pragma unroll 1
        for (int k = 0; k < 16; k++) {
            const uint32_t s = k & 3, fb = B_OF + 8 * s, sa = SB + o_stage(s);
            if (k < 2) mbar_wait(rb + R_AE + 8 + 8 * k, 0);
            else if (k == 2) mbar_wait(rb + R_AE, 1);
            else if (k == 3) mbar_wait(B_QAF, L);
            else mbar_wait(B_OE + 8 * s, ((k >> 2) - 1) & 1);
            const int par = k >> 3, pair = ((k + (nt >> 1)) & 7) * 2;
            mbar_expect_tx(fb, 32768);
            #pragma unroll
            for (int b = 0; b < 2; b++) tma_load4(sa + 16384 + b * 8192, &mp.wo, (nt >> 1) * 128 + b * 64, 0, par, pair, fb);
            if ((k & 7) == 0) { ctr_wait(&g_oc[L][mt * 2 + (nt & 1)][par], 16); fence_async_global(); }
            #pragma unroll
            for (int a = 0; a < 2; a++) bulk_load(sa + a * 8192, g_o + (size_t)(((mt * 4 + (nt & 1) * 2 + a) * 2 + par) * 16 + pair) * 4096, 8192, fb);
        }
        if (ffn) {
            #pragma unroll 1
            for (int i = 0; i < 9; i++) {
                if (i == 0) mbar_wait(B_OE, 1);
                if (i == 2) mbar_wait(B_OE + 8, 1);
                if (i == 3) mbar_wait(B_OE + 16, 1);
                if (i == 6) mbar_wait(B_OE + 24, 1);
                if (i >= PACE) mbar_wait(B_FL + 8 * (i - PACE), L);
                mbar_expect_tx(B_FL + 8 * i, 16384);
                if (i < 5) gu_load(mp, 3 + i, B_FL + 8 * i);
                else tma_load3(SB + OFF_FD + (i - 5) * 16384, &mp.d, 0, c * 32, (i - 5) * 4, B_FL + 8 * i);
            }
        }
    }
}

__global__ void __launch_bounds__(384, 1) k_all(const __grid_constant__ Maps mp, const bf16* __restrict__ x0, const bf16* __restrict__ wo,
                                                const bf16* __restrict__ w_down, const bf16* __restrict__ w_r, bf16* __restrict__ out) {
    extern __shared__ __align__(1024) char smem[];
    if (smem_u32(smem) != SB) __trap();
    const int wg = warp_uniform(threadIdx.x >> 7);
    if (threadIdx.x == 0) TL(0);
    if (threadIdx.x == 256) {
        tm_prefetch(&mp.wqkv); tm_prefetch(&mp.x0);
        for (int s = 0; s < 3; s++) mbar_init(B_RING + R_QF + 8 * s, 1);
        fence_mbar_init();
        #pragma unroll 1
        for (int s = 0; s < 3; s++) qkv_fill(&mp.x0, &mp.wqkv, B_RING + R_QF + 8 * s, s, s);
    }
    if (threadIdx.x >= 288 && threadIdx.x < 288 + 64) {
        const uint32_t b = BB + (threadIdx.x - 288) * 8, r = (b - B_RING) % R_SZ;
        int cnt = 1;
        if (b == B_EPI || b == B_RES2) cnt = 3;
        if ((b >= B_KV0 && b < B_KV1) || (b >= B_OST && b < B_QAF) || (b >= B_XST && b < B_FE)) cnt = 4;
        if (b == B_SL2 || b == B_QAF || (b >= B_OE && b < B_RING)) cnt = 2;
        if (b == B_GD || b == B_DD) cnt = 8;
        if (b >= B_RING) cnt = r >= R_AE ? 8 : (r >= R_QE && r < R_AF) ? 2 : 1;
        if (b < B_RING || b >= B_RING + R_QE) mbar_init(b, cnt);
        fence_mbar_init();
    }
    __syncthreads();
    if (wg == 2) {
        reg_dec<40>();
        if (threadIdx.x >= 288) side_role(mp, x0, w_r, out);
        if (threadIdx.x == 256) producer_role(mp, wo, w_down);
    } else {
        reg_inc<232>();
        #pragma unroll 1
        for (int L = 0; L < 2; L++) {
            qkv_phase(L, wg);
            attention_phase(L, wg);
            oproj_phase(L, wg, w_r, out);
        }
    }
}

typedef CUresult (*EncodeFn)(CUtensorMap*, CUtensorMapDataType, cuuint32_t, void*, const cuuint64_t*, const cuuint64_t*, const cuuint32_t*,
                             const cuuint32_t*, CUtensorMapInterleave, CUtensorMapSwizzle, CUtensorMapL2promotion, CUtensorMapFloatOOBfill);

void make_map(EncodeFn enc, CUtensorMap* tm, const void* ptr, int rank, const cuuint64_t* dims, const cuuint64_t* strides, const cuuint32_t* box, CUtensorMapSwizzle sw) {
    const cuuint32_t es[4] = {1, 1, 1, 1};
    enc(tm, CU_TENSOR_MAP_DATA_TYPE_BFLOAT16, rank, const_cast<void*>(ptr), dims, strides, box, es, CU_TENSOR_MAP_INTERLEAVE_NONE, sw,
        box[0] == 64 ? CU_TENSOR_MAP_L2_PROMOTION_L2_128B : CU_TENSOR_MAP_L2_PROMOTION_NONE, CU_TENSOR_MAP_FLOAT_OOB_FILL_NONE);
}
void make_map2(EncodeFn enc, CUtensorMap* tm, const void* ptr, uint64_t cols, uint64_t rows, uint32_t bc, uint32_t br, CUtensorMapSwizzle sw) {
    const cuuint64_t dims[2] = {cols, rows}, strides[1] = {cols * 2};
    const cuuint32_t box[2] = {bc, br};
    make_map(enc, tm, ptr, 2, dims, strides, box, sw);
}

}

extern "C" void kernel_launch(void* const* d_in, const int* in_sizes, int n_in, void* d_out, int out_size) {
    const bf16* x0 = (const bf16*)d_in[0];
    const bf16* wqkv = (const bf16*)d_in[1];
    const bf16* wo = (const bf16*)d_in[2];
    const bf16* w_r = (const bf16*)d_in[4];
    const bf16* w_gate = (const bf16*)d_in[5];
    const bf16* w_up = (const bf16*)d_in[6];
    const bf16* w_down = (const bf16*)d_in[7];

    EncodeFn enc = nullptr;
    cudaDriverEntryPointQueryResult qr;
    cudaGetDriverEntryPoint("cuTensorMapEncodeTiled", (void**)&enc, cudaEnableDefault, &qr);
    void* p_x;
    cudaGetSymbolAddress(&p_x, g_x);
    Maps mp;
    const CUtensorMapSwizzle S128 = CU_TENSOR_MAP_SWIZZLE_128B;
    make_map2(enc, &mp.x0, x0, D_, S_, 64, 64, S128);
    make_map2(enc, &mp.x, p_x, D_, S_, 64, 64, S128);
    make_map2(enc, &mp.wqkv, wqkv, 3 * D_, D_, 64, 64, S128);
    make_map2(enc, &mp.r, wqkv, 3 * D_, D_, 24, 256, CU_TENSOR_MAP_SWIZZLE_NONE);
    make_map2(enc, &mp.g, w_gate, FF, D_, 32, 128, CU_TENSOR_MAP_SWIZZLE_64B);
    make_map2(enc, &mp.u, w_up, FF, D_, 32, 128, CU_TENSOR_MAP_SWIZZLE_64B);
    {
        const cuuint64_t dims[4] = {D_, 32, 2, 16}, strides[3] = {D_ * 2, 32 * D_ * 2, 64 * D_ * 2};
        const cuuint32_t box[4] = {64, 32, 1, 2};
        make_map(enc, &mp.wo, wo, 4, dims, strides, box, S128);
    }
    {
        const cuuint64_t dims[3] = {64, FF, 16}, strides[2] = {D_ * 2, 128};
        const cuuint32_t box[3] = {64, 32, 4};
        make_map(enc, &mp.d, w_down, 3, dims, strides, box, S128);
    }
    cudaFuncSetAttribute(k_all, cudaFuncAttributeMaxDynamicSharedMemorySize, K_SMEM);
    k_all<<<128, 384, K_SMEM, cudaStreamPerThread>>>(mp, x0, wo, w_down, w_r, (bf16*)d_out);
}
```

```cpp
#include <cuda_runtime.h>
#include <cuda_bf16.h>
#include <cuda_fp16.h>
#include <cuda.h>
#include <cudaTypedefs.h>
#include <stdint.h>

namespace {

typedef __nv_bfloat16 bf16;

constexpr int S_ = 2048, D_ = 1024, NH = 32, FF = 3584, NFC = FF / 32;
constexpr float LN_EPS = 1e-5f;
constexpr float QSCALE = 0.17677669529663687f * 1.4426950408889634f;
constexpr uint32_t SENT = 0xFFFFFFFFu;

constexpr int KV_WIN = 32768;
__device__ __align__(1024) char g_kv[NH * 8 * KV_WIN];
__device__ __align__(1024) char g_o[32 * 2 * 16 * 4096];
__device__ __align__(1024) bf16 g_x[S_ * D_];
__device__ float g_csum[8 * 3 * D_];
__device__ float g_wsq[8 * 96];
__device__ float2 g_rs0[S_];
__device__ __align__(16) float4 g_sums[2][S_];
__device__ __align__(16) uint32_t g_ypart[2][NFC][D_];
__device__ __align__(16) uint32_t g_xrow[2][D_ / 2];
__device__ __align__(16) uint32_t g_x2row[D_];
__device__ __align__(16) uint32_t g_fix[3 * D_];
__device__ uint32_t g_c0;
__device__ uint32_t g_kvc[2][NH][8];
__device__ uint32_t g_oc[2][16][2];
__device__ uint32_t g_xc[2][8];
struct RouteOut { int idx; float r; float mean; float rstd; };

constexpr uint32_t SB = 1024;

__device__ __forceinline__ uint32_t smem_u32(const void* p) { return (uint32_t)__cvta_generic_to_shared(p); }
__device__ __forceinline__ void mbar_arrive(uint32_t bar) { asm volatile("mbarrier.arrive.shared::cta.b64 _, [%0];" :: "r"(bar) : "memory"); }
__device__ __forceinline__ void mbar_wait(uint32_t bar, uint32_t parity) {
    asm volatile("{\n.reg .pred p;\n.reg .u32 n;\nmov.u32 n, 0;\n"
                 "LAB_WAIT:\nmbarrier.try_wait.parity.shared::cta.b64 p, [%0], %1, 2000;\n@p bra LAB_DONE;\n"
                 "add.u32 n, n, 1;\nsetp.lt.u32 p, n, 0x200000;\n@p bra LAB_WAIT;\ntrap;\nLAB_DONE:\n}" :: "r"(bar), "r"(parity) : "memory");
}
__device__ __forceinline__ void mbar_arrive_elect(uint32_t bar) {
    asm volatile("{\n.reg .pred p;\nelect.sync _|p, 0xffffffff;\n@p mbarrier.arrive.shared::cta.b64 _, [%0];\n}" :: "r"(bar) : "memory");
}
__device__ __forceinline__ int tid_now() { int v; asm volatile("mov.u32 %0, %%tid.x;" : "=r"(v)); return v; }
__device__ __forceinline__ int cta_now() { int v; asm volatile("mov.u32 %0, %%ctaid.x;" : "=r"(v)); return v; }
__device__ __forceinline__ int warp_uniform(int v) { return __shfl_sync(0xffffffffu, v, 0); }
__device__ __forceinline__ void fence_mbar_init() { asm volatile("fence.mbarrier_init.release.cluster;" ::: "memory"); }
__device__ __forceinline__ void fence_async_smem() { asm volatile("fence.proxy.async.shared::cta;" ::: "memory"); }
__device__ __forceinline__ void fence_async_global() { asm volatile("fence.proxy.async.global;" ::: "memory"); }
__device__ __forceinline__ void named_sync(int id, int n) { asm volatile("bar.sync %0, %1;" :: "r"(id), "r"(n) : "memory"); }
__device__ __forceinline__ void named_arrive(int id, int n) { asm volatile("bar.arrive %0, %1;" :: "r"(id), "r"(n) : "memory"); }
__device__ __forceinline__ bool named_any(bool p, int id) {
    uint32_t r;
    asm volatile("{\n.reg .pred a, b;\nsetp.ne.u32 a, %1, 0;\nbarrier.cta.red.or.pred b, %2, 128, a;\nselp.u32 %0, 1, 0, b;\n}" : "=r"(r) : "r"((uint32_t)p), "r"(id) : "memory");
    return r != 0;
}
#define ELECT(op) "{\n.reg .pred e;\nelect.sync _|e, 0xffffffff;\n@e " op "\n}"
__device__ __forceinline__ void mbar_init(uint32_t bar, int cnt) { asm volatile(ELECT("mbarrier.init.shared::cta.b64 [%0], %1;") :: "r"(bar), "r"(cnt) : "memory"); }
__device__ __forceinline__ void mbar_expect_tx(uint32_t bar, uint32_t bytes) { asm volatile(ELECT("mbarrier.arrive.expect_tx.shared::cta.b64 _, [%0], %1;") :: "r"(bar), "r"(bytes) : "memory"); }
__device__ __forceinline__ void bulk_load(uint32_t dst, const void* src, uint32_t bytes, uint32_t bar) {
    asm volatile(ELECT("cp.async.bulk.shared::cluster.global.mbarrier::complete_tx::bytes [%0], [%1], %2, [%3];") :: "r"(dst), "l"(src), "r"(bytes), "r"(bar) : "memory");
}
__device__ __forceinline__ void bulk_store(void* dst, uint32_t src, uint32_t bytes) {
    asm volatile(ELECT("cp.async.bulk.global.shared::cta.bulk_group [%0], [%1], %2;") :: "l"(dst), "r"(src), "r"(bytes) : "memory");
}
__device__ __forceinline__ void bulk_commit() { asm volatile("cp.async.bulk.commit_group;" ::: "memory"); }
__device__ __forceinline__ void bulk_wait() { asm volatile("cp.async.bulk.wait_group 0;" ::: "memory"); }
__device__ __forceinline__ void bulk_wait_read() { asm volatile("cp.async.bulk.wait_group.read 0;" ::: "memory"); }
__device__ __forceinline__ void l2_prefetch(const void* src, uint32_t bytes) {
    asm volatile(ELECT("cp.async.bulk.prefetch.L2.global [%0], %1;") :: "l"(src), "r"(bytes) : "memory");
}
__device__ __forceinline__ void tma_load(uint32_t dst, const CUtensorMap* tm, int c0, int c1, uint32_t bar) {
    asm volatile(ELECT("cp.async.bulk.tensor.2d.shared::cluster.global.mbarrier::complete_tx::bytes [%0], [%1, {%3, %4}], [%2];")
                 :: "r"(dst), "l"(tm), "r"(bar), "r"(c0), "r"(c1) : "memory");
}
__device__ __forceinline__ void tma_load3(uint32_t dst, const CUtensorMap* tm, int c0, int c1, int c2, uint32_t bar) {
    asm volatile(ELECT("cp.async.bulk.tensor.3d.shared::cluster.global.mbarrier::complete_tx::bytes [%0], [%1, {%3, %4, %5}], [%2];")
                 :: "r"(dst), "l"(tm), "r"(bar), "r"(c0), "r"(c1), "r"(c2) : "memory");
}
__device__ __forceinline__ void tma_load5(uint32_t dst, const CUtensorMap* tm, int c0, int c1, int c2, int c3, int c4, uint32_t bar) {
    asm volatile(ELECT("cp.async.bulk.tensor.5d.shared::cluster.global.mbarrier::complete_tx::bytes [%0], [%1, {%3, %4, %5, %6, %7}], [%2];")
                 :: "r"(dst), "l"(tm), "r"(bar), "r"(c0), "r"(c1), "r"(c2), "r"(c3), "r"(c4) : "memory");
}
__device__ __forceinline__ void tma_store(const CUtensorMap* tm, uint32_t src, int c0, int c1) {
    asm volatile(ELECT("cp.async.bulk.tensor.2d.global.shared::cta.bulk_group [%0, {%2, %3}], [%1];") :: "l"(tm), "r"(src), "r"(c0), "r"(c1) : "memory");
}
__device__ __forceinline__ void tm_prefetch(const CUtensorMap* tm) { asm volatile(ELECT("prefetch.tensormap [%0];") :: "l"(tm) : "memory"); }
__device__ __forceinline__ uint32_t lds32(uint32_t a) { uint32_t v; asm volatile("ld.shared.b32 %0, [%1];" : "=r"(v) : "r"(a) : "memory"); return v; }
__device__ __forceinline__ float ldsf(uint32_t a) { return __uint_as_float(lds32(a)); }
__device__ __forceinline__ float2 lds64f(uint32_t a) { float2 v; asm volatile("ld.shared.v2.f32 {%0, %1}, [%2];" : "=f"(v.x), "=f"(v.y) : "r"(a) : "memory"); return v; }
__device__ __forceinline__ uint4 lds128(uint32_t a) { uint4 v; asm volatile("ld.shared.v4.b32 {%0, %1, %2, %3}, [%4];" : "=r"(v.x), "=r"(v.y), "=r"(v.z), "=r"(v.w) : "r"(a) : "memory"); return v; }
__device__ __forceinline__ void sts32(uint32_t a, uint32_t v) { asm volatile("st.shared.b32 [%0], %1;" :: "r"(a), "r"(v) : "memory"); }
__device__ __forceinline__ void stsf(uint32_t a, float v) { sts32(a, __float_as_uint(v)); }
__device__ __forceinline__ void sts64f(uint32_t a, float x, float y) { asm volatile("st.shared.v2.f32 [%0], {%1, %2};" :: "r"(a), "f"(x), "f"(y) : "memory"); }
__device__ __forceinline__ void sts128(uint32_t a, const uint4& v) { asm volatile("st.shared.v4.b32 [%0], {%1, %2, %3, %4};" :: "r"(a), "r"(v.x), "r"(v.y), "r"(v.z), "r"(v.w) : "memory"); }
__device__ __forceinline__ void stsm4(uint32_t a, uint32_t x, uint32_t y, uint32_t z, uint32_t w) {
    asm volatile("stmatrix.sync.aligned.m8n8.x4.shared.b16 [%0], {%1, %2, %3, %4};" :: "r"(a), "r"(x), "r"(y), "r"(z), "r"(w) : "memory");
}
__device__ __forceinline__ void ldsm4(uint32_t& a0, uint32_t& a1, uint32_t& a2, uint32_t& a3, uint32_t addr) {
    asm volatile("ldmatrix.sync.aligned.m8n8.x4.shared.b16 {%0,%1,%2,%3}, [%4];" : "=r"(a0), "=r"(a1), "=r"(a2), "=r"(a3) : "r"(addr) : "memory");
}
__device__ __forceinline__ void ldsm4t(uint32_t& a0, uint32_t& a1, uint32_t& a2, uint32_t& a3, uint32_t addr) {
    asm volatile("ldmatrix.sync.aligned.m8n8.x4.trans.shared.b16 {%0,%1,%2,%3}, [%4];" : "=r"(a0), "=r"(a1), "=r"(a2), "=r"(a3) : "r"(addr) : "memory");
}
__device__ __forceinline__ void mma_bf16(float (&c)[4], uint32_t a0, uint32_t a1, uint32_t a2, uint32_t a3, uint32_t b0, uint32_t b1) {
    asm("mma.sync.aligned.m16n8k16.row.col.f32.bf16.bf16.f32 {%0,%1,%2,%3}, {%4,%5,%6,%7}, {%8,%9}, {%0,%1,%2,%3};"
        : "+f"(c[0]), "+f"(c[1]), "+f"(c[2]), "+f"(c[3]) : "r"(a0), "r"(a1), "r"(a2), "r"(a3), "r"(b0), "r"(b1));
}
__device__ __forceinline__ void stg128_pred(void* p, const uint4& v, bool on) {
    asm volatile("{\n.reg .pred q;\nsetp.ne.u32 q, %5, 0;\n@q st.global.v4.b32 [%0], {%1, %2, %3, %4};\n}"
                 :: "l"(p), "r"(v.x), "r"(v.y), "r"(v.z), "r"(v.w), "r"((uint32_t)on) : "memory");
}
__device__ __forceinline__ uint32_t ld_relaxed(const void* p) { uint32_t v; asm volatile("ld.relaxed.gpu.global.u32 %0, [%1];" : "=r"(v) : "l"(p) : "memory"); return v; }
__device__ __forceinline__ uint4 ld_relaxed4(const void* p) {
    uint4 v; asm volatile("ld.relaxed.gpu.global.v4.b32 {%0, %1, %2, %3}, [%4];" : "=r"(v.x), "=r"(v.y), "=r"(v.z), "=r"(v.w) : "l"(p) : "memory"); return v;
}
__device__ __forceinline__ void ld_relaxed4_unless(uint4& v, const void* p, uint32_t full) {
    asm volatile("{\n.reg .pred q;\nsetp.ne.u32 q, %3, %5;\n@q ld.relaxed.gpu.global.v4.b32 {%0, %1, %2, %3}, [%4];\n}"
                 : "+r"(v.x), "+r"(v.y), "+r"(v.z), "+r"(v.w) : "l"(p), "r"(full) : "memory");
}
__device__ __forceinline__ void st_relaxed(void* p, uint32_t v) { asm volatile("st.relaxed.gpu.global.u32 [%0], %1;" :: "l"(p), "r"(v) : "memory"); }
__device__ __forceinline__ void st_relaxed4_if(void* p, const uint4& v, bool on) {
    asm volatile("{\n.reg .pred q;\nsetp.ne.u32 q, %5, 0;\n@q st.relaxed.gpu.global.v4.b32 [%0], {%1, %2, %3, %4};\n}"
                 :: "l"(p), "r"(v.x), "r"(v.y), "r"(v.z), "r"(v.w), "r"((uint32_t)on) : "memory");
}
__device__ __forceinline__ uint32_t not_sent(float v) { const uint32_t u = __float_as_uint(v); return u == SENT ? 0x7FFFFFFFu : u; }
__device__ __forceinline__ bool has_sent(const uint4& v) { return v.x == SENT || v.y == SENT || v.z == SENT || v.w == SENT; }
constexpr uint32_t SPIN_MAX = 1u << 22;
__device__ __forceinline__ void spin_check(uint32_t n) { asm volatile("{\n.reg .pred p;\nsetp.ge.u32 p, %0, %1;\n@p st.global.u32 [%2], %0;\n}" :: "r"(n), "n"(SPIN_MAX), "l"(0ull) : "memory"); }
__device__ __forceinline__ void ctr_arrive(uint32_t* c) { asm volatile(ELECT("red.release.gpu.global.add.u32 [%0], 1;") :: "l"(c) : "memory"); }
__device__ __forceinline__ void ctr_wait(const uint32_t* c, uint32_t target) {
    asm volatile("{\n.reg .pred p;\n.reg .u32 n, v;\nmov.u32 n, 0;\n"
                 "LAB_WAIT:\nld.acquire.gpu.global.u32 v, [%0];\nsetp.ge.u32 p, v, %1;\n@p bra LAB_DONE;\n"
                 "add.u32 n, n, 1;\nsetp.lt.u32 p, n, 0x400000;\n@p bra LAB_WAIT;\ntrap;\nLAB_DONE:\n}" :: "l"(c), "r"(target) : "memory");
}
__device__ __forceinline__ void publish(uint32_t* c) { bulk_wait(); fence_async_global(); ctr_arrive(c); }

__device__ __forceinline__ void wg_fence() { asm volatile("wgmma.fence.sync.aligned;" ::: "memory"); }
__device__ __forceinline__ void wg_commit() { asm volatile("wgmma.commit_group.sync.aligned;" ::: "memory"); }
template <int N> __device__ __forceinline__ void wg_wait() { asm volatile("wgmma.wait_group.sync.aligned %0;" :: "n"(N) : "memory"); }
template <int N> __device__ __forceinline__ void reg_inc() { asm volatile("setmaxnreg.inc.sync.aligned.u32 %0;" :: "n"(N)); }
template <int N> __device__ __forceinline__ void reg_dec() { asm volatile("setmaxnreg.dec.sync.aligned.u32 %0;" :: "n"(N)); }
__host__ __device__ constexpr uint64_t desc_plain(uint32_t addr, uint32_t lbo, uint32_t sbo) {
    return (uint64_t)((addr & 0x3FFFF) >> 4) | ((uint64_t)(lbo >> 4) << 16) | ((uint64_t)(sbo >> 4) << 32);
}
__host__ __device__ constexpr uint64_t desc_sw128(uint32_t addr, uint32_t lbo, uint32_t sbo) { return desc_plain(addr, lbo, sbo) | (1ull << 62); }

__device__ __forceinline__ float ex2(float x) { float y; asm("ex2.approx.ftz.f32 %0, %1;" : "=f"(y) : "f"(x)); return y; }
__device__ __forceinline__ float rsq(float x) { float y; asm("rsqrt.approx.ftz.f32 %0, %1;" : "=f"(y) : "f"(x)); return y; }
__device__ __forceinline__ uint32_t pack_bf16(float lo, float hi) { uint32_t r; asm("cvt.rn.bf16x2.f32 %0, %1, %2;" : "=r"(r) : "f"(hi), "f"(lo)); return r; }
__device__ __forceinline__ uint32_t pack_f16(float lo, float hi) { uint32_t r; asm("cvt.rn.f16x2.f32 %0, %1, %2;" : "=r"(r) : "f"(hi), "f"(lo)); return r; }
__device__ __forceinline__ float bf_lo(uint32_t v) { return __uint_as_float(v << 16); }
__device__ __forceinline__ float bf_hi(uint32_t v) { return __uint_as_float(v & 0xFFFF0000u); }
__device__ __forceinline__ float bf_round(float x) { return __uint_as_float(pack_bf16(0.f, x)); }
__device__ __forceinline__ uint32_t badd2(uint32_t a, uint32_t b) { uint32_t r; asm("add.rn.bf16x2 %0, %1, %2;" : "=r"(r) : "r"(a), "r"(b)); return r; }
__device__ __forceinline__ void h2_unpack(uint32_t v, float& lo, float& hi) {
    asm("{.reg .f16 l, h; mov.b32 {l, h}, %2; cvt.f32.f16 %0, l; cvt.f32.f16 %1, h;}" : "=f"(lo), "=f"(hi) : "r"(v));
}
__device__ __forceinline__ uint32_t add_ln2(uint32_t x, float rstd, float nb) { return badd2(x, pack_bf16(fmaf(bf_lo(x), rstd, nb), fmaf(bf_hi(x), rstd, nb))); }
__device__ __forceinline__ float sel4(int t, float a0, float a1, float a2, float a3) {
    float r;
    asm("{\n.reg .pred p, q;\n.reg .f32 x, y;\nsetp.ne.u32 p, %1, 0;\nsetp.ne.u32 q, %2, 0;\nselp.f32 x, %4, %3, p;\nselp.f32 y, %6, %5, p;\nselp.f32 %0, y, x, q;\n}"
        : "=f"(r) : "r"(t & 1), "r"(t & 2), "f"(a0), "f"(a1), "f"(a2), "f"(a3));
    return r;
}
__device__ __forceinline__ float warp_sum(float v) {
    #pragma unroll
    for (int o = 16; o > 0; o >>= 1) v += __shfl_xor_sync(0xffffffffu, v, o);
    return v;
}
__device__ __forceinline__ float warp_max(float v) {
    #pragma unroll
    for (int o = 16; o > 0; o >>= 1) v = fmaxf(v, __shfl_xor_sync(0xffffffffu, v, o));
    return v;
}
__device__ __forceinline__ uint32_t redux_max(uint32_t v) { uint32_t r; asm volatile("redux.sync.max.u32 %0, %1, 0xffffffff;" : "=r"(r) : "r"(v)); return r; }
__device__ __forceinline__ uint32_t redux_min(uint32_t v) { uint32_t r; asm volatile("redux.sync.min.u32 %0, %1, 0xffffffff;" : "=r"(r) : "r"(v)); return r; }

#define TL(T, i)

__device__ __forceinline__ void wg_gemm_n128(float (&d)[64], uint64_t desca, uint64_t desc) {
    asm volatile("{\n.reg .pred p;\nsetp.ne.b32 p, 1, 0;\n"
        "wgmma.mma_async.sync.aligned.m64n128k16.f32.bf16.bf16 "
        "{%0,%1,%2,%3,%4,%5,%6,%7,%8,%9,%10,%11,%12,%13,%14,%15,%16,%17,%18,%19,%20,%21,%22,%23,%24,%25,%26,%27,%28,%29,%30,%31,%32,%33,%34,%35,%36,%37,%38,%39,%40,%41,%42,%43,%44,%45,%46,%47,%48,%49,%50,%51,%52,%53,%54,%55,%56,%57,%58,%59,%60,%61,%62,%63}, "
        "%64, %65, p, 1, 1, 0, 1;\n}\n"
        : "+f"(d[0]), "+f"(d[1]), "+f"(d[2]), "+f"(d[3]), "+f"(d[4]), "+f"(d[5]), "+f"(d[6]), "+f"(d[7]),
          "+f"(d[8]), "+f"(d[9]), "+f"(d[10]), "+f"(d[11]), "+f"(d[12]), "+f"(d[13]), "+f"(d[14]), "+f"(d[15]),
          "+f"(d[16]), "+f"(d[17]), "+f"(d[18]), "+f"(d[19]), "+f"(d[20]), "+f"(d[21]), "+f"(d[22]), "+f"(d[23]),
          "+f"(d[24]), "+f"(d[25]), "+f"(d[26]), "+f"(d[27]), "+f"(d[28]), "+f"(d[29]), "+f"(d[30]), "+f"(d[31]),
          "+f"(d[32]), "+f"(d[33]), "+f"(d[34]), "+f"(d[35]), "+f"(d[36]), "+f"(d[37]), "+f"(d[38]), "+f"(d[39]),
          "+f"(d[40]), "+f"(d[41]), "+f"(d[42]), "+f"(d[43]), "+f"(d[44]), "+f"(d[45]), "+f"(d[46]), "+f"(d[47]),
          "+f"(d[48]), "+f"(d[49]), "+f"(d[50]), "+f"(d[51]), "+f"(d[52]), "+f"(d[53]), "+f"(d[54]), "+f"(d[55]),
          "+f"(d[56]), "+f"(d[57]), "+f"(d[58]), "+f"(d[59]), "+f"(d[60]), "+f"(d[61]), "+f"(d[62]), "+f"(d[63])
        : "l"(desca), "l"(desc));
}
__device__ __forceinline__ void wg_gemm_n192(float (&d)[96], uint64_t desca, uint64_t desc) {
    asm volatile("{\n.reg .pred p;\nsetp.ne.b32 p, 1, 0;\n"
        "wgmma.mma_async.sync.aligned.m64n192k16.f32.bf16.bf16 "
        "{%0,%1,%2,%3,%4,%5,%6,%7,%8,%9,%10,%11,%12,%13,%14,%15,%16,%17,%18,%19,%20,%21,%22,%23,%24,%25,%26,%27,%28,%29,%30,%31,%32,%33,%34,%35,%36,%37,%38,%39,%40,%41,%42,%43,%44,%45,%46,%47,%48,%49,%50,%51,%52,%53,%54,%55,%56,%57,%58,%59,%60,%61,%62,%63,%64,%65,%66,%67,%68,%69,%70,%71,%72,%73,%74,%75,%76,%77,%78,%79,%80,%81,%82,%83,%84,%85,%86,%87,%88,%89,%90,%91,%92,%93,%94,%95}, "
        "%96, %97, p, 1, 1, 0, 1;\n}\n"
        : "+f"(d[0]), "+f"(d[1]), "+f"(d[2]), "+f"(d[3]), "+f"(d[4]), "+f"(d[5]), "+f"(d[6]), "+f"(d[7]),
          "+f"(d[8]), "+f"(d[9]), "+f"(d[10]), "+f"(d[11]), "+f"(d[12]), "+f"(d[13]), "+f"(d[14]), "+f"(d[15]),
          "+f"(d[16]), "+f"(d[17]), "+f"(d[18]), "+f"(d[19]), "+f"(d[20]), "+f"(d[21]), "+f"(d[22]), "+f"(d[23]),
          "+f"(d[24]), "+f"(d[25]), "+f"(d[26]), "+f"(d[27]), "+f"(d[28]), "+f"(d[29]), "+f"(d[30]), "+f"(d[31]),
          "+f"(d[32]), "+f"(d[33]), "+f"(d[34]), "+f"(d[35]), "+f"(d[36]), "+f"(d[37]), "+f"(d[38]), "+f"(d[39]),
          "+f"(d[40]), "+f"(d[41]), "+f"(d[42]), "+f"(d[43]), "+f"(d[44]), "+f"(d[45]), "+f"(d[46]), "+f"(d[47]),
          "+f"(d[48]), "+f"(d[49]), "+f"(d[50]), "+f"(d[51]), "+f"(d[52]), "+f"(d[53]), "+f"(d[54]), "+f"(d[55]),
          "+f"(d[56]), "+f"(d[57]), "+f"(d[58]), "+f"(d[59]), "+f"(d[60]), "+f"(d[61]), "+f"(d[62]), "+f"(d[63]),
          "+f"(d[64]), "+f"(d[65]), "+f"(d[66]), "+f"(d[67]), "+f"(d[68]), "+f"(d[69]), "+f"(d[70]), "+f"(d[71]),
          "+f"(d[72]), "+f"(d[73]), "+f"(d[74]), "+f"(d[75]), "+f"(d[76]), "+f"(d[77]), "+f"(d[78]), "+f"(d[79]),
          "+f"(d[80]), "+f"(d[81]), "+f"(d[82]), "+f"(d[83]), "+f"(d[84]), "+f"(d[85]), "+f"(d[86]), "+f"(d[87]),
          "+f"(d[88]), "+f"(d[89]), "+f"(d[90]), "+f"(d[91]), "+f"(d[92]), "+f"(d[93]), "+f"(d[94]), "+f"(d[95])
        : "l"(desca), "l"(desc));
}
__device__ __forceinline__ void wg_qk_init(uint32_t (&d)[32], uint64_t desca, uint64_t desc) {
    asm volatile("{\n.reg .pred p;\nsetp.ne.b32 p, 0, 0;\n"
        "wgmma.mma_async.sync.aligned.m64n128k16.f16.f16.f16 "
        "{%0,%1,%2,%3,%4,%5,%6,%7,%8,%9,%10,%11,%12,%13,%14,%15,%16,%17,%18,%19,%20,%21,%22,%23,%24,%25,%26,%27,%28,%29,%30,%31}, "
        "%32, %33, p, 1, 1, 0, 0;\n}\n"
        : "=r"(d[0]), "=r"(d[1]), "=r"(d[2]), "=r"(d[3]), "=r"(d[4]), "=r"(d[5]), "=r"(d[6]), "=r"(d[7]),
          "=r"(d[8]), "=r"(d[9]), "=r"(d[10]), "=r"(d[11]), "=r"(d[12]), "=r"(d[13]), "=r"(d[14]), "=r"(d[15]),
          "=r"(d[16]), "=r"(d[17]), "=r"(d[18]), "=r"(d[19]), "=r"(d[20]), "=r"(d[21]), "=r"(d[22]), "=r"(d[23]),
          "=r"(d[24]), "=r"(d[25]), "=r"(d[26]), "=r"(d[27]), "=r"(d[28]), "=r"(d[29]), "=r"(d[30]), "=r"(d[31])
        : "l"(desca), "l"(desc));
}
__device__ __forceinline__ void wg_qk_acc(uint32_t (&d)[32], uint64_t desca, uint64_t desc) {
    asm volatile("{\n.reg .pred p;\nsetp.ne.b32 p, 1, 0;\n"
        "wgmma.mma_async.sync.aligned.m64n128k16.f16.f16.f16 "
        "{%0,%1,%2,%3,%4,%5,%6,%7,%8,%9,%10,%11,%12,%13,%14,%15,%16,%17,%18,%19,%20,%21,%22,%23,%24,%25,%26,%27,%28,%29,%30,%31}, "
        "%32, %33, p, 1, 1, 0, 0;\n}\n"
        : "+r"(d[0]), "+r"(d[1]), "+r"(d[2]), "+r"(d[3]), "+r"(d[4]), "+r"(d[5]), "+r"(d[6]), "+r"(d[7]),
          "+r"(d[8]), "+r"(d[9]), "+r"(d[10]), "+r"(d[11]), "+r"(d[12]), "+r"(d[13]), "+r"(d[14]), "+r"(d[15]),
          "+r"(d[16]), "+r"(d[17]), "+r"(d[18]), "+r"(d[19]), "+r"(d[20]), "+r"(d[21]), "+r"(d[22]), "+r"(d[23]),
          "+r"(d[24]), "+r"(d[25]), "+r"(d[26]), "+r"(d[27]), "+r"(d[28]), "+r"(d[29]), "+r"(d[30]), "+r"(d[31])
        : "l"(desca), "l"(desc));
}
__device__ __forceinline__ void wg_pv_init(uint32_t (&d)[10], uint32_t a0, uint32_t a1, uint32_t a2, uint32_t a3, uint64_t desc) {
    asm volatile("{\n.reg .pred p;\nsetp.ne.b32 p, 0, 0;\n"
        "wgmma.mma_async.sync.aligned.m64n40k16.f16.f16.f16 "
        "{%0,%1,%2,%3,%4,%5,%6,%7,%8,%9}, "
        "{%10,%11,%12,%13}, %14, p, 1, 1, 1;\n}\n"
        : "=r"(d[0]), "=r"(d[1]), "=r"(d[2]), "=r"(d[3]), "=r"(d[4]), "=r"(d[5]), "=r"(d[6]), "=r"(d[7]),
          "=r"(d[8]), "=r"(d[9])
        : "r"(a0), "r"(a1), "r"(a2), "r"(a3), "l"(desc));
}
__device__ __forceinline__ void wg_pv_acc(uint32_t (&d)[10], uint32_t a0, uint32_t a1, uint32_t a2, uint32_t a3, uint64_t desc) {
    asm volatile("{\n.reg .pred p;\nsetp.ne.b32 p, 1, 0;\n"
        "wgmma.mma_async.sync.aligned.m64n40k16.f16.f16.f16 "
        "{%0,%1,%2,%3,%4,%5,%6,%7,%8,%9}, "
        "{%10,%11,%12,%13}, %14, p, 1, 1, 1;\n}\n"
        : "+r"(d[0]), "+r"(d[1]), "+r"(d[2]), "+r"(d[3]), "+r"(d[4]), "+r"(d[5]), "+r"(d[6]), "+r"(d[7]),
          "+r"(d[8]), "+r"(d[9])
        : "r"(a0), "r"(a1), "r"(a2), "r"(a3), "l"(desc));
}

constexpr int Q_ABYTES = 256 * 64 * 2, Q_STB = Q_ABYTES + 192 * 64 * 2;
constexpr int OFF_SIDE = 3 * Q_STB;
constexpr int OFF_XS = OFF_SIDE + 49152;
constexpr int OFF_CS = OFF_XS + 4096;
constexpr int OFF_RC = OFF_CS + 768;
constexpr int OFF_FIX = OFF_RC + 2048;
constexpr int A_WIN = KV_WIN + 4096;
constexpr int OFF_QA = 3 * A_WIN;
constexpr int OFF_FE = 147456;
constexpr int OFF_XT = 196608;
__host__ __device__ constexpr uint32_t o_stage(uint32_t s) { return s == 3 ? OFF_QA : s == 2 ? 0 : (s + 1) * A_WIN; }
__host__ __device__ constexpr uint32_t gu_piece(uint32_t i) { return i < 3 ? OFF_FE + i * 16384 : i < 6 ? (i - 1) * 16384 : (i - 6) * 16384; }
constexpr int OFF_FD = 5 * 16384;
constexpr int OFF_OUT = OFF_FD + 32768;
constexpr int OFF_BAR = OFF_XT + 32768;
constexpr int OFF_PART = OFF_BAR + 384;
constexpr int OFF_RED = OFF_PART + 2048;
constexpr int OFF_RT = OFF_RED + 96;
constexpr int OFF_M = OFF_RT + 128;
constexpr int OFF_WR = OFF_M + 64;
constexpr int K_SMEM = OFF_WR + 264;
static_assert(K_SMEM <= 232448 && OFF_FIX + 768 <= OFF_BAR && OFF_QA + 32768 <= OFF_FE, "smem");
constexpr int M_SC = 0,
              M_IVS = 24,
              M_ISC = 32,
              M_OK = 40,
              M_WS = 48,
              M_RIDX = 60;
constexpr uint32_t BB = SB + OFF_BAR;
constexpr uint32_t B_QF = BB, B_EPI = BB + 24, B_RES2 = BB + 56, B_AF = BB + 64, B_SL2 = BB + 88, B_RES = BB + 120, B_OF = BB + 128,
                   B_FE = BB + 160, B_FL = BB + 168, B_DD = BB + 176, B_FD = BB + 184, B_PR = BB + 192, B_FW = B_PR, B_SW = BB + 216,
                   B_QE = BB + 224, B_QAF = BB + 248, B_XRD = BB + 280, B_OE = BB + 288, B_AE = BB + 320, B_GD = BB + 344, B_KV0 = BB + 376;

constexpr int N_OST = 5, N_XST = 9, N_RT = 11, N_KV1 = 12, N_FW = 13;

struct Maps { CUtensorMap xa0, wqkv, xa, x0, x, out, w64, wo, r, g, u, d; };

__device__ __forceinline__ uint32_t order_bits(float r) { const uint32_t u = __float_as_uint(r); return (u & 0x80000000u) ? ~u : (u | 0x80000000u); }
__device__ __forceinline__ RouteOut route_result(int lane) {
    const uint4 e = lds128(SB + OFF_RT + (lane & 7) * 16);
    const uint32_t m = redux_max(e.x), row = redux_min(e.x == m ? e.y : 0x7FFFFFFFu);
    const int src = __ffs(__ballot_sync(0xffffffffu, e.y == row)) - 1;
    RouteOut rt;
    rt.idx = row;
    rt.r = __uint_as_float((m & 0x80000000u) ? m & 0x7FFFFFFFu : ~m);
    rt.mean = __uint_as_float(__shfl_sync(0xffffffffu, e.z, src));
    rt.rstd = __uint_as_float(__shfl_sync(0xffffffffu, e.w, src));
    return rt;
}

__device__ __forceinline__ void prep_work(const bf16* __restrict__ x0, const CUtensorMap* tmW, int t) {
    const int c = blockIdx.x, lane = t & 31, warp = warp_uniform(t >> 5);
    const int ki = c >> 4, n = c & 15;
    constexpr uint32_t red = SB + OFF_SIDE, xs = red + 4096;
    if (warp == 0) {
        mbar_expect_tx(B_PR, 32768);
        bulk_load(xs, x0 + (size_t)c * 16 * D_, 32768, B_PR);
        mbar_expect_tx(B_PR + 8, 16384);
        tma_load(xs + 32768, tmW, 2 * D_ + n * 64, ki * 128, B_PR + 8);
        tma_load(xs + 32768 + 8192, tmW, 2 * D_ + n * 64, ki * 128 + 64, B_PR + 8);
    }
    if (t < 32) g_sums[t >> 4][c * 16 + (t & 15)] = make_float4(0.f, 0.f, 0.f, 0.f);
    const uint4 sent = make_uint4(SENT, SENT, SENT, SENT);
    for (int i = t; i < 2 * NFC * 2; i += 96) reinterpret_cast<uint4*>(&g_ypart[0][0][0])[c * (2 * NFC * 2) + i] = sent;
    if (t < 2) reinterpret_cast<uint4*>(g_x2row)[c * 2 + t] = sent;
    else if (t < 8) reinterpret_cast<uint4*>(g_fix)[c * 6 + t - 2] = sent;
    else if (t < 12) (&g_kvc[0][0][0])[c * 4 + t - 8] = 0u;
    else if (t == 12 && c < 64) (&g_oc[0][0][0])[c] = 0u;
    else if (t == 13 && c < 16) (&g_xc[0][0])[c] = 0u;
    else if (t >= 14 && t < 16) reinterpret_cast<uint4*>(&g_xrow[0][0])[c * 2 + t - 14] = sent;
    mbar_wait(B_PR, 0);
    #pragma unroll 1
    for (int r = warp; r < 16; r += 3) {
        float s = 0.f, q = 0.f;
        #pragma unroll
        for (int i = 0; i < 4; i++) {
            const uint4 u = lds128(xs + r * 2048 + (lane + 32 * i) * 16);
            const float f[8] = {bf_lo(u.x), bf_hi(u.x), bf_lo(u.y), bf_hi(u.y), bf_lo(u.z), bf_hi(u.z), bf_lo(u.w), bf_hi(u.w)};
            #pragma unroll
            for (int e = 0; e < 8; e++) { s += f[e]; q = fmaf(f[e], f[e], q); }
        }
        #pragma unroll
        for (int o = 16; o > 0; o >>= 1) { s += __shfl_xor_sync(0xffffffffu, s, o); q += __shfl_xor_sync(0xffffffffu, q, o); }
        const float mean = s * (1.f / D_);
        const float var = fmaxf(q * (1.f / D_) - mean * mean, 0.f);
        if (lane == 0) g_rs0[c * 16 + r] = make_float2(rsqrtf(var + LN_EPS), mean);
    }
    named_sync(2, 96);
    if (warp == 0) {
        mbar_expect_tx(B_PR + 16, 32768);
        #pragma unroll
        for (int b = 0; b < 4; b++) tma_load(xs + b * 8192, tmW, (b >> 1) * D_ + n * 64, ki * 128 + (b & 1) * 64, B_PR + 16);
    }
    const int j = t & 7, rg = t >> 3;
    #pragma unroll 1
    for (int blk = 0; blk < 3; blk++) {
        const int type = blk == 0 ? 2 : blk - 1;
        const uint32_t wb = xs + type * 16384;
        if (blk < 2) mbar_wait(B_PR + 8 + 8 * blk, 0);
        float cs[8];
        uint32_t z2[4] = {0u, 0u, 0u, 0u};
        #pragma unroll
        for (int i = 0; i < 8; i++) cs[i] = 0.f;
        #pragma unroll 4
        for (int r = rg; r < 128; r += 12) {
            const uint4 u = lds128(wb + r * 128 + ((j ^ (r & 7)) << 4));
            cs[0] += bf_lo(u.x); cs[1] += bf_hi(u.x); cs[2] += bf_lo(u.y); cs[3] += bf_hi(u.y);
            cs[4] += bf_lo(u.z); cs[5] += bf_hi(u.z); cs[6] += bf_lo(u.w); cs[7] += bf_hi(u.w);
            asm("fma.rn.bf16x2 %0, %1, %1, %0;" : "+r"(z2[0]) : "r"(u.x));
            asm("fma.rn.bf16x2 %0, %1, %1, %0;" : "+r"(z2[1]) : "r"(u.y));
            asm("fma.rn.bf16x2 %0, %1, %1, %0;" : "+r"(z2[2]) : "r"(u.z));
            asm("fma.rn.bf16x2 %0, %1, %1, %0;" : "+r"(z2[3]) : "r"(u.w));
        }
        #pragma unroll
        for (int i = 0; i < 8; i++) { cs[i] += __shfl_xor_sync(0xffffffffu, cs[i], 8); cs[i] += __shfl_xor_sync(0xffffffffu, cs[i], 16); }
        float z = ((bf_lo(z2[0]) + bf_hi(z2[0])) + (bf_lo(z2[1]) + bf_hi(z2[1]))) + ((bf_lo(z2[2]) + bf_hi(z2[2])) + (bf_lo(z2[3]) + bf_hi(z2[3])));
        z += __shfl_xor_sync(0xffffffffu, z, 1); z += __shfl_xor_sync(0xffffffffu, z, 2);
        z += __shfl_xor_sync(0xffffffffu, z, 8); z += __shfl_xor_sync(0xffffffffu, z, 16);
        if (lane < 8) {
            #pragma unroll
            for (int i = 0; i < 8; i++) stsf(red + (warp * 200 + type * 64 + j * 8 + i) * 4, cs[i]);
            if ((lane & 3) == 0) stsf(red + (warp * 200 + 192 + type * 2 + (lane >> 2)) * 4, z);
        }
    }
    named_sync(2, 96);
    for (int i = t; i < 198; i += 96) {
        const float v = ldsf(red + i * 4) + ldsf(red + (200 + i) * 4) + ldsf(red + (400 + i) * 4);
        if (i < 192) g_csum[ki * (3 * D_) + (i >> 6) * D_ + n * 64 + (i & 63)] = v;
        else g_wsq[ki * 96 + ((i - 192) >> 1) * 32 + n * 2 + (i & 1)] = v;
    }
    named_sync(2, 96);
    if (warp == 0) { ctr_arrive(&g_c0); ctr_wait(&g_c0, 128); }
    named_sync(2, 96);
}

__device__ __forceinline__ float pow2_inv(float b) {
    const int e = min(max((int)(__float_as_uint(b) >> 23) + 1, 20), 234);
    return __uint_as_float((uint32_t)(254 - e) << 23);
}
__device__ __forceinline__ void epi_inputs(int L) {
    const int t = tid_now() - 288, mt = cta_now() >> 4, nt = cta_now() & 15;
    float p[2][8], r0[3], r1[3];
    #pragma unroll
    for (int k = 0; k < 2; k++)
        #pragma unroll
        for (int q = 0; q < 8; q++) p[k][q] = __ldcg(g_csum + q * (3 * D_) + ((t + 96 * k) >> 6) * D_ + nt * 64 + ((t + 96 * k) & 63));
    #pragma unroll
    for (int k = 0; k < 3; k++) {
        const int row = mt * 256 + min(t + 96 * k, 255);
        const float2 s = __ldcg(L == 0 ? &g_rs0[row] : reinterpret_cast<const float2*>(&g_sums[0][row]));
        r0[k] = s.x; r1[k] = s.y;
    }
    #pragma unroll
    for (int k = 0; k < 2; k++) stsf(SB + OFF_CS + (t + 96 * k) * 4, ((p[k][0] + p[k][1]) + (p[k][2] + p[k][3])) + ((p[k][4] + p[k][5]) + (p[k][6] + p[k][7])));
    #pragma unroll
    for (int k = 0; k < 3; k++) {
        if (L != 0) {
            const float mean = r0[k] * (1.f / D_);
            const float var = fmaxf(r1[k] * (1.f / D_) - mean * mean, 0.f);
            const float a = 1.f + rsqrtf(var + LN_EPS);
            r0[k] = a * rsqrtf(a * a * var + LN_EPS); r1[k] = mean;
        }
        if (t + 96 * k < 256) sts64f(SB + OFF_RC + (t + 96 * k) * 8, r0[k], r1[k]);
    }
    if (L == 0 && t < 32) {
        float z = 0.f;
        if (t < 6) {
            #pragma unroll
            for (int q = 0; q < 8; q++) z += __ldcg(g_wsq + q * 96 + (t >> 1) * 32 + nt * 2 + (t & 1));
        }
        const float b = sqrtf(z) * (t < 2 ? 34.f * QSCALE : 34.f);
        const float sc = t < 4 ? fminf(pow2_inv(b) * 32768.f, 1.f) : pow2_inv(b);
        const float bk = __shfl_down_sync(0xffffffffu, b, 2), sk = __shfl_down_sync(0xffffffffu, sc, 2);
        if (t < 6) stsf(SB + OFF_M + M_SC + t * 4, t < 2 ? sc * QSCALE : sc);
        if (t < 2) { stsf(SB + OFF_M + M_ISC + t * 4, 1.f / (sc * sk)); sts32(SB + OFF_M + M_OK + t * 4, sc == 1.f && sk == 1.f && b * bk < 60000.f); }
        if (t == 4 || t == 5) stsf(SB + OFF_M + M_IVS + (t - 4) * 4, 1.f / sc);
    }
}

__device__ __forceinline__ int ypos_col(int p) { return (p >> 7) * 128 + ((p >> 1) & 7) * 16 + (p & 1) * 8 + ((p >> 4) & 7); }

__device__ __forceinline__ float ffn_finish(int L, const RouteOut& rt) {
    const int t = tid_now() - 288, c = cta_now(), lane = t & 31;
    const int col = ypos_col(c * 8 + (t & 7));
    uint32_t n = 0, xp;
    do { xp = ld_relaxed(&g_xrow[L][col >> 1]); } while (xp == SENT && ++n < SPIN_MAX);
    const float xv = (col & 1) ? bf_hi(xp) : bf_lo(xp);
    float rsel = bf_round(__fdividef(1.f, 1.f + __expf(-bf_round(rt.r)))), xn = bf_round((xv - rt.mean) * rt.rstd);
    asm volatile("" : "+f"(rsel), "+f"(xn));
    const uint32_t* src = &g_ypart[L][t >> 1][c * 8 + (t & 1) * 4];
    uint4 v[3];
    do {
        v[0] = ld_relaxed4(src); v[1] = ld_relaxed4(src + 48 * D_);
        v[2] = t < 2 * NFC - 192 ? ld_relaxed4(src + 96 * D_) : make_uint4(0u, 0u, 0u, 0u);
    } while ((has_sent(v[0]) || has_sent(v[1]) || has_sent(v[2])) && ++n < SPIN_MAX);
    spin_check(n);
    __syncwarp();
    TL(288, L * 48 + 42);
    float a[4] = {__uint_as_float(v[0].x) + __uint_as_float(v[1].x) + __uint_as_float(v[2].x), __uint_as_float(v[0].y) + __uint_as_float(v[1].y) + __uint_as_float(v[2].y),
                  __uint_as_float(v[0].z) + __uint_as_float(v[1].z) + __uint_as_float(v[2].z), __uint_as_float(v[0].w) + __uint_as_float(v[1].w) + __uint_as_float(v[2].w)};
    #pragma unroll
    for (int o = 2; o < 32; o <<= 1)
        #pragma unroll
        for (int i = 0; i < 4; i++) a[i] += __shfl_xor_sync(0xffffffffu, a[i], o);
    if (lane < 2) sts128(SB + OFF_RED + (t >> 5) * 32 + lane * 16, make_uint4(__float_as_uint(a[0]), __float_as_uint(a[1]), __float_as_uint(a[2]), __float_as_uint(a[3])));
    named_sync(2, 96);
    const uint32_t ra = SB + OFF_RED + (t & 7) * 4;
    const float y = bf_round(ldsf(ra) + ldsf(ra + 32) + ldsf(ra + 64));
    return bf_round(xv + bf_round(xn + bf_round(y * rsel)));
}

__device__ __forceinline__ void routed_qkv(int ridx) {
    const int t = tid_now() - 288, c = cta_now(), lane = t & 31, warp = t >> 5;
    constexpr uint32_t red = SB + OFF_RED;
    {
        uint4 v[3];
        uint32_t n = 0;
        do {
            v[0] = ld_relaxed4(g_x2row + t * 4); v[1] = ld_relaxed4(g_x2row + (t + 96) * 4);
            v[2] = t < 64 ? ld_relaxed4(g_x2row + (t + 192) * 4) : make_uint4(0u, 0u, 0u, 0u);
        } while ((has_sent(v[0]) || has_sent(v[1]) || has_sent(v[2])) && ++n < SPIN_MAX);
        spin_check(n);
        __syncwarp();
        TL(288, 21);
        float f[12];
        float s = 0.f;
        #pragma unroll
        for (int i = 0; i < 3; i++) { f[4*i] = __uint_as_float(v[i].x); f[4*i+1] = __uint_as_float(v[i].y); f[4*i+2] = __uint_as_float(v[i].z); f[4*i+3] = __uint_as_float(v[i].w); }
        #pragma unroll
        for (int i = 0; i < 12; i++) s += f[i];
        s = warp_sum(s);
        if (lane == 0) stsf(red + warp * 4, s);
        named_sync(2, 96);
        const float mean = (ldsf(red) + ldsf(red + 4) + ldsf(red + 8)) * (1.f / D_);
        float q = 0.f;
        #pragma unroll
        for (int i = 0; i < 12; i++) { f[i] -= mean; if (i < 8 || t < 64) q = fmaf(f[i], f[i], q); }
        q = warp_sum(q);
        if (lane == 0) stsf(red + 16 + warp * 4, q);
        named_sync(2, 96);
        const float rstd = rsqrtf((ldsf(red + 16) + ldsf(red + 20) + ldsf(red + 24)) * (1.f / D_) + LN_EPS);
        #pragma unroll
        for (int i = 0; i < 3; i++)
            if (i < 2 || t < 64) sts128(SB + OFF_XS + (t + 96 * i) * 16, make_uint4(pack_bf16(0.f, f[4*i] * rstd), pack_bf16(0.f, f[4*i+1] * rstd), pack_bf16(0.f, f[4*i+2] * rstd), pack_bf16(0.f, f[4*i+3] * rstd)));
    }
    named_sync(2, 96);
    TL(288, 22);
    mbar_wait(B_SW, 0);
    TL(288, 23);
    float a[8];
    #pragma unroll
    for (int i = 0; i < 8; i++) a[i] = 0.f;
    const uint32_t wa = SB + OFF_SIDE + t * 16, xa = SB + OFF_XS + (t / 3) * 4;
    #pragma unroll 4
    for (int i = 0; i < 32; i++) {
        const uint4 u = lds128(wa + i * 1536);
        const float xv = ldsf(xa + i * 128);
        a[0] = fmaf(xv, bf_lo(u.x), a[0]); a[1] = fmaf(xv, bf_hi(u.x), a[1]); a[2] = fmaf(xv, bf_lo(u.y), a[2]); a[3] = fmaf(xv, bf_hi(u.y), a[3]);
        a[4] = fmaf(xv, bf_lo(u.z), a[4]); a[5] = fmaf(xv, bf_hi(u.z), a[5]); a[6] = fmaf(xv, bf_lo(u.w), a[6]); a[7] = fmaf(xv, bf_hi(u.w), a[7]);
    }
    named_sync(2, 96);
    TL(288, 41);
    sts128(SB + OFF_SIDE + t * 32, make_uint4(__float_as_uint(a[0]), __float_as_uint(a[1]), __float_as_uint(a[2]), __float_as_uint(a[3])));
    sts128(SB + OFF_SIDE + t * 32 + 16, make_uint4(__float_as_uint(a[4]), __float_as_uint(a[5]), __float_as_uint(a[6]), __float_as_uint(a[7])));
    named_sync(2, 96);
    {
        float y = 0.f;
        #pragma unroll
        for (int i = 0; i < 8; i++) y += ldsf(SB + OFF_SIDE + ((t & 3) * 8 + i) * 96 + (t >> 2) * 4);
        y += __shfl_xor_sync(0xffffffffu, y, 1); y += __shfl_xor_sync(0xffffffffu, y, 2);
        if ((t & 3) == 0) st_relaxed(g_fix + c * 24 + (t >> 2), not_sent(y));
    }
    if ((ridx >> 8) == (c >> 4) && t < 48) {
        uint4 v;
        uint32_t n = 0;
        do {
            v = ld_relaxed4(g_fix + (t >> 4) * D_ + (c & 15) * 64 + (t & 15) * 4);
        } while (has_sent(v) && ++n < SPIN_MAX);
        spin_check(n);
        sts128(SB + OFF_FIX + t * 16, v);
    }
    __syncwarp();
}

__device__ __forceinline__ void residual_prep() {
    const int t = tid_now() - 288, c = cta_now(), row0 = (c >> 4) * 256 + (c & 1) * 128, col0 = ((c & 15) >> 1) * 128;
    for (int i = t; i < 128; i += 96) {
        const float2 s = __ldcg(reinterpret_cast<const float2*>(&g_sums[0][row0 + i]));
        const float mean = s.x * (1.f / D_);
        const float rstd = rsqrtf(fmaxf(s.y * (1.f / D_) - mean * mean, 0.f) + LN_EPS);
        sts64f(SB + OFF_PART + i * 8, rstd, -mean * rstd);
    }
    named_sync(2, 96);
    #pragma unroll 2
    for (int i = t; i < 2048; i += 96) {
        const uint4 u = lds128(SB + OFF_XT + i * 16);
        const float2 r = lds64f(SB + OFF_PART + ((i >> 3) & 127) * 8);
        sts128(SB + OFF_XT + i * 16, make_uint4(add_ln2(u.x, r.x, r.y), add_ln2(u.y, r.x, r.y), add_ln2(u.z, r.x, r.y), add_ln2(u.w, r.x, r.y)));
    }
    const uint32_t lr = lds32(SB + OFF_M + M_RIDX) - row0;
    if (lr < 128u) {
        named_sync(2, 96);
        if (t < 16) {
            const uint4 a = ld_relaxed4(g_x2row + col0 + t * 8), b = ld_relaxed4(g_x2row + col0 + t * 8 + 4);
            sts128(SB + OFF_XT + (t >> 3) * 16384 + lr * 128 + (((t & 7) ^ (lr & 7)) << 4),
                   make_uint4(__byte_perm(a.x, a.y, 0x7632), __byte_perm(a.z, a.w, 0x7632), __byte_perm(b.x, b.y, 0x7632), __byte_perm(b.z, b.w, 0x7632)));
        }
    }
    __syncwarp();
}

#define FW_NS 1500
__device__ __forceinline__ void ffn_load(const Maps& mp, int i, uint32_t dst, uint32_t bar) {
    if (i < 8) tma_load(dst, (i & 1) ? &mp.u : &mp.g, blockIdx.x * 32, (i >> 1) * 256, bar);
    else tma_load3(dst, &mp.d, 0, blockIdx.x * 32, (i - 8) * 4, bar);
}
__device__ __forceinline__ void side_role(const Maps& mp, const bf16* __restrict__ x0, const bf16* __restrict__ wo, const bf16* __restrict__ w_r, bf16* __restrict__ out) {
    prep_work(x0, &mp.w64, threadIdx.x - 288);
    epi_inputs(0);
    #pragma unroll 1
    for (int L = 0; L < 2; L++) {
        const int t = tid_now() - 288, lane = t & 31, sw = warp_uniform(t >> 5);
        const int c = blockIdx.x, mt = c >> 4, nt = c & 15;
        named_sync(2, 96);
        if (t == 0) mbar_arrive(B_EPI);
        TL(288, L * 48 + 5);
        if (L == 0) {
            float ws = 0.f;
            for (int i = t; i < D_ / 8; i += 96) {
                const uint4 v = reinterpret_cast<const uint4*>(w_r)[i];
                ws += ((bf_lo(v.x) + bf_hi(v.x)) + (bf_lo(v.y) + bf_hi(v.y))) + ((bf_lo(v.z) + bf_hi(v.z)) + (bf_lo(v.w) + bf_hi(v.w)));
            }
            ws = warp_sum(ws);
            if (lane == 0) stsf(SB + OFF_M + M_WS + sw * 4, ws);
            if (t < 66) sts32(SB + OFF_WR + t * 4, t < 64 ? reinterpret_cast<const uint32_t*>(w_r)[(nt >> 1) * 64 + (t >> 3) * 8 + (t & 1) * 4 + ((t >> 1) & 3)] : 0x3F803F80u);
        }
        __syncwarp();
        if (sw == 0) {
            char* kv = g_kv + (size_t)(nt * 16 + mt) * KV_WIN;
            mbar_wait(B_KV0, L);
            bulk_store(kv, SB, KV_WIN);
            bulk_commit();
            publish(&g_kvc[L][nt * 2][mt]);
            TL(288, L * 48 + 6);
            named_sync(N_KV1, 64);
            bulk_store(kv + 8 * KV_WIN, SB + 2 * A_WIN, KV_WIN);
            bulk_commit();
            bulk_wait_read();
            mbar_arrive_elect(B_SL2);
            publish(&g_kvc[L][nt * 2 + 1][mt]);
        }
        if (sw < 2) {
            #pragma unroll 1
            for (int p = 0; p < 2; p++) {
                named_sync(N_OST + 2 * p + sw, 160);
                bulk_store(g_o + (size_t)(((mt * 2 + sw) * 2 + p) * 16 + nt) * 8192, SB + OFF_QA + p * 16384 + sw * 8192, 8192);
                bulk_commit();
                if (p == 1) { bulk_wait_read(); mbar_arrive_elect(B_QAF); }
                publish(&g_oc[L][mt * 2 + sw][p]);
            }
        } else {
            named_sync(N_FW, 64);
            mbar_expect_tx(B_RES, 32768);
            #pragma unroll
            for (int i = 0; i < 4; i++) tma_load(SB + OFF_XT + i * 8192, L == 0 ? &mp.x0 : &mp.x, (nt >> 1) * 128 + (i >> 1) * 64, mt * 256 + (nt & 1) * 128 + (i & 1) * 64, B_RES);
            l2_prefetch(reinterpret_cast<const char*>(wo) + (size_t)c * 16384, 16384);
            if (c < NFC) {
                #pragma unroll 1
                for (int r = 0; r < 4; r++) {
                    __nanosleep(FW_NS);
                    if (r > 0) mbar_wait(B_FW, (r + L) & 1);
                    const uint32_t bar = r < 3 ? B_FW : B_FE;
                    mbar_expect_tx(bar, 3 * 16384);
                    #pragma unroll 1
                    for (int b = 0; b < 3; b++) ffn_load(mp, 9 - 3 * r + b, SB + OFF_FE + b * 16384, bar);
                }
            }
        }
        named_sync(2, 96);
        mbar_wait(B_RES, L);
        if (L == 1) { residual_prep(); named_sync(2, 96); }
        if (t == 0) mbar_arrive(B_RES2);
        __syncwarp();
        if (sw < 2) {
            named_sync(N_XST + sw, 160);
            if (c < NFC) mbar_wait(B_FL, L);
            #pragma unroll
            for (int h = 0; h < 2; h++)
                tma_store(L == 0 ? &mp.x : &mp.out, SB + (L == 0 ? OFF_XT : OFF_OUT) + h * 16384 + sw * 8192, (nt >> 1) * 128 + h * 64, mt * 256 + (nt & 1) * 128 + sw * 64);
            bulk_commit();
            if (L == 1) { bulk_wait_read(); mbar_arrive_elect(B_XRD); }
            publish(&g_xc[L][mt]);
            TL(288, L * 48 + 14);
        }
        __syncwarp();
        named_sync(N_RT, 128);
        const RouteOut rt = route_result(lane);
        if (L == 0) {
            if (t == 0) { sts32(SB + OFF_M + M_RIDX, rt.idx); if (c == 0) g_c0 = 0u; }
        }
        if (L == 1 && t == 64) ctr_wait(&g_xc[1][rt.idx >> 8], 32);
        __syncwarp();
        const float v = ffn_finish(L, rt);
        TL(288, L * 48 + 20);
        if (L == 0) {
            if (t < 8) st_relaxed(g_x2row + ypos_col(c * 8 + t), not_sent(v));
            mbar_wait(B_DD, 0);
            epi_inputs(1);
            routed_qkv(rt.idx);
        } else if (t < 8) {
            reinterpret_cast<unsigned short*>(out)[(size_t)rt.idx * D_ + ypos_col(c * 8 + t)] = (unsigned short)(__float_as_uint(v) >> 16);
        }
    }
}

template <int HH>
__device__ __forceinline__ void qkv_epi_head(const float (&acc0)[96], const float (&acc1)[96], const float (&cf)[4], const float (&nm)[4], uint32_t dst, int t) {
    float2 c2[4];
    #pragma unroll
    for (int jj = 0; jj < 4; jj++) c2[jj] = lds64f(SB + OFF_CS + (HH * 32 + jj * 8) * 4 + t * 8);
    const float hs = ldsf(SB + OFF_M + M_SC + HH * 4);
    #pragma unroll
    for (int i = 0; i < 4; i++) {
        const float* a = (i >> 1) ? acc1 : acc0;
        const float sc = cf[i] * hs;
        uint32_t pk[4];
        #pragma unroll
        for (int jj = 0; jj < 4; jj++)
            pk[jj] = pack_f16(fmaf(nm[i], c2[jj].x, a[4 * (4 * HH + jj) + 2 * (i & 1)]) * sc, fmaf(nm[i], c2[jj].y, a[4 * (4 * HH + jj) + 2 * (i & 1) + 1]) * sc);
        stsm4(dst + (i >> 1) * (HH < 2 ? 4096 : 1024) + (i & 1) * 128, pk[0], pk[1], pk[2], pk[3]);
    }
}
__device__ __forceinline__ void qkv_patch(int lr, int lane, uint32_t groups) {
    __syncwarp();
    const int hh = lane >> 2, ch = lane & 3;
    if ((groups >> hh) & 1) {
        const float hs = ldsf(SB + OFF_M + M_SC + hh * 4);
        const uint4 a = lds128(SB + OFF_FIX + lane * 32), b = lds128(SB + OFF_FIX + lane * 32 + 16);
        const uint32_t dst = hh < 2 ? OFF_QA + hh * 16384 + (lr >> 6) * 4096 + ch * 1024 + (lr & 63) * 16
                                    : (hh & 1) * 2 * A_WIN + (hh >> 2) * 16384 + ch * 4096 + lr * 16;
        sts128(SB + dst, make_uint4(pack_f16(__uint_as_float(a.x) * hs, __uint_as_float(a.y) * hs), pack_f16(__uint_as_float(a.z) * hs, __uint_as_float(a.w) * hs),
                                    pack_f16(__uint_as_float(b.x) * hs, __uint_as_float(b.y) * hs), pack_f16(__uint_as_float(b.z) * hs, __uint_as_float(b.w) * hs)));
    }
}

__device__ __forceinline__ void qkv_phase(int L, int wg) {
    const uint32_t rb = L * 32;
    float acc0[96], acc1[96];
    #pragma unroll
    for (int i = 0; i < 96; i++) { acc0[i] = 0.f; acc1[i] = 0.f; }
    const bool leader = (tid_now() & 127) == 0;
    uint32_t st = 0, ph = 0;
    #pragma unroll 1
    for (int k = 0; k < 16; k++) {
        mbar_wait(rb + B_QF + 8 * st, ph);
        TL(k == 0 ? 0 : -1, L * 48 + 1);
        const uint64_t da = desc_sw128(SB, 16, 1024) + ((st * Q_STB + wg * 16384) >> 4);
        const uint64_t db = desc_sw128(SB + Q_ABYTES, 8192, 1024) + ((st * Q_STB) >> 4);
        wg_fence();
        #pragma unroll
        for (int kk = 0; kk < 4; kk++) {
            wg_gemm_n192(acc0, da + kk * 2, db + kk * 128);
            wg_gemm_n192(acc1, da + (8192 >> 4) + kk * 2, db + kk * 128);
        }
        wg_commit();
        if (k > 0) {
            wg_wait<1>();
            if (leader) mbar_arrive(rb + B_QE + 8 * (st == 0 ? 2 : st - 1));
        }
        if (++st == 3) { st = 0; ph ^= 1; }
    }
    const int tid = tid_now(), lane = tid & 31, w = (tid >> 5) & 3, g = lane >> 2, t = lane & 3;
    mbar_wait(B_EPI, L);
    float cf[4], nm[4];
    #pragma unroll
    for (int i = 0; i < 4; i++) { const float2 r = lds64f(SB + OFF_RC + (wg * 128 + w * 16 + g + (i >> 1) * 64 + (i & 1) * 8) * 8); cf[i] = r.x; nm[i] = -r.y; }
    int lr = -1;
    if (L == 1) {
        const int d = (int)lds32(SB + OFF_M + M_RIDX) - (cta_now() >> 4) * 256;
        if ((d >> 7) == wg && ((d >> 4) & 3) == w) lr = d;
    }
    wg_wait<0>();
    TL(0, L * 48 + 2);
    TL(128, L * 48 + 40);
    named_sync(1, 256);
    const uint32_t dk = SB + wg * 2048 + (lane >> 3) * 4096 + (w * 16 + (lane & 7)) * 16;
    const uint32_t dq = SB + OFF_QA + wg * 8192 + (lane >> 3) * 1024 + (w * 16 + (lane & 7)) * 16;
    qkv_epi_head<2>(acc0, acc1, cf, nm, dk, t);
    qkv_epi_head<4>(acc0, acc1, cf, nm, dk + 16384, t);
    if (lr >= 0) qkv_patch(lr, lane, 0x14u);
    fence_async_smem();
    __syncwarp();
    mbar_arrive_elect(B_KV0);
    TL(0, L * 48 + 4);
    qkv_epi_head<3>(acc0, acc1, cf, nm, dk + 2 * A_WIN, t);
    qkv_epi_head<5>(acc0, acc1, cf, nm, dk + 2 * A_WIN + 16384, t);
    qkv_epi_head<0>(acc0, acc1, cf, nm, dq, t);
    qkv_epi_head<1>(acc0, acc1, cf, nm, dq + 16384, t);
    if (lr >= 0) qkv_patch(lr, lane, 0x2Bu);
    #pragma unroll
    for (int s = 0; s < 3; s++) sts128(SB + s * A_WIN + KV_WIN + tid * 16, make_uint4(0x3C003C00u, 0x3C003C00u, 0x3C003C00u, 0x3C003C00u));
    fence_async_smem();
    named_sync(1, 256);
    if (tid == 0) mbar_arrive(rb + B_AF);
    if (tid >= 224) named_arrive(N_KV1, 64);
    TL(0, L * 48 + 3);
}

#define TIE 0
struct Unit {
    uint32_t o[10];
    uint32_t bz[2];
    uint32_t sc[2];
    uint32_t ch[2];
};
constexpr uint32_t CH_OK = 0x38003800u;
__device__ __forceinline__ uint32_t hmax2(uint32_t a, uint32_t b) { uint32_t r; asm("max.f16x2 %0, %1, %2;" : "=r"(r) : "r"(a), "r"(b)); return r; }
__device__ __forceinline__ uint32_t hadd2(uint32_t a, uint32_t b) { uint32_t r; asm("add.rn.f16x2 %0, %1, %2;" : "=r"(r) : "r"(a), "r"(b)); return r; }
__device__ __forceinline__ uint32_t hsub2(uint32_t a, uint32_t b) { uint32_t r; asm("sub.rn.f16x2 %0, %1, %2;" : "=r"(r) : "r"(a), "r"(b)); return r; }
__device__ __forceinline__ uint32_t hfma2(uint32_t a, uint32_t b, uint32_t c) { uint32_t r; asm("fma.rn.f16x2 %0, %1, %2, %3;" : "=r"(r) : "r"(a), "r"(b), "r"(c)); return r; }
__device__ __forceinline__ uint32_t exp2_h2(uint32_t s, uint32_t bz, uint32_t& ch) {
    uint32_t z, w, d;
    asm("fma.rn.relu.f16x2 %0, %1, %2, %3;" : "=r"(z) : "r"(s), "r"(0x00400040u), "r"(bz));
    asm("lop3.b32 %0, %1, 0x003F003F, %0, 0xC2;" : "+r"(ch) : "r"(z));
    asm("fma.rn.f16x2 %0, %1, %2, %3;" : "=r"(w) : "r"(ch), "r"(0x30A630A6u), "r"(0xACCCACCCu));
    asm("{.reg .b32 n; neg.f16x2 n, %1; fma.rn.relu.f16x2 %0, n, %1, %2;}" : "=r"(d) : "r"(w), "r"(0x00580058u));
    return (z << 4) - d;
}
__device__ __forceinline__ void exp_tile(uint32_t (&p)[32], const uint32_t (&s)[32], Unit& u) {
    #pragma unroll
    for (int i = 0; i < 32; i++) p[i] = exp2_h2(s[i], u.bz[i & 1], u.ch[i & 1]);
}
__device__ __forceinline__ void issue_qk(uint32_t (&s)[32], uint64_t dq, uint64_t dk) {
    wg_qk_init(s, dq, dk); wg_qk_acc(s, dq + (2048 >> 4), dk + (8192 >> 4));
    wg_commit();
}
template <bool INIT>
__device__ __forceinline__ void issue_pv(uint32_t (&h)[10], const uint32_t (&p)[32], uint64_t dv) {
    #pragma unroll
    for (int k = 0; k < 8; k++) {
        if (INIT && k == 0) wg_pv_init(h, p[0], p[1], p[2], p[3], dv);
        else wg_pv_acc(h, p[4*k], p[4*k+1], p[4*k+2], p[4*k+3], dv + k * 16);
    }
    wg_commit();
}
__device__ __forceinline__ void unit_init(Unit& u, const uint32_t (&s)[32]) {
    uint32_t m0 = s[0], m1 = s[1];
    #pragma unroll
    for (int i = 1; i < 16; i++) { m0 = hmax2(m0, s[2 * i]); m1 = hmax2(m1, s[2 * i + 1]); }
    uint32_t m = hmax2(__byte_perm(m0, m1, 0x5410), __byte_perm(m0, m1, 0x7632));
    m = hmax2(m, __shfl_xor_sync(0xffffffffu, m, 1)); m = hmax2(m, __shfl_xor_sync(0xffffffffu, m, 2));
    float f0, f1; h2_unpack(m, f0, f1);
    u.ch[0] = fabsf(f0) < 1000.f ? CH_OK : 0u; u.ch[1] = fabsf(f1) < 1000.f ? CH_OK : 0u;
    f0 = (18.f - ceilf(f0)) * 3.814697265625e-06f; f1 = (18.f - ceilf(f1)) * 3.814697265625e-06f;
    u.bz[0] = pack_f16(f0, f0); u.bz[1] = pack_f16(f1, f1);
    u.sc[0] = u.sc[1] = 0x3C003C00u;
    #pragma unroll
    for (int i = 0; i < 10; i++) u.o[i] = 0u;
}
template <bool MORE>
__device__ __forceinline__ void unit_flush(Unit& u, const uint32_t (&h)[10]) {
    #pragma unroll
    for (int i = 0; i < 10; i++) u.o[i] = hfma2(u.o[i], u.sc[i & 1], h[i]);
    if (MORE) {
        #pragma unroll
        for (int r = 0; r < 2; r++) {
            const uint32_t ex = u.o[8 + r] & 0x7C007C00u;
            u.sc[r] = 0x84008400u - ex;
            u.bz[r] = hsub2(hadd2(u.bz[r], 0x04800480u), ex >> 4);
        }
    }
}
__device__ __forceinline__ uint32_t unit_store(const Unit& u, uint32_t dst, float ivs, bool head_ok, int lane) {
    uint32_t bad = 0;
    #pragma unroll
    for (int h = 0; h < 2; h++) {
        const uint32_t l = u.o[8 + h] & 0xFFFFu;
        uint32_t b = __ballot_sync(0xffffffffu, !head_ok || (u.ch[h] & CH_OK) != CH_OK || l >= 0x7C00u || l < 0x4000u);
        b |= b >> 1; b |= b >> 2;
        float lf, unused; h2_unpack(l, lf, unused);
        const float inv = __fdividef(ivs, lf);
        uint32_t pk[4];
        #pragma unroll
        for (int j = 0; j < 4; j++) { float x, y; h2_unpack(u.o[2 * j + h], x, y); pk[j] = pack_bf16(x * inv, y * inv); }
        const bool mine = (b >> (4 * (lane & 7))) & 1;
        stsm4(mine ? SB + OFF_RT : dst + h * 128, pk[0], pk[1], pk[2], pk[3]);
        bad |= (__ballot_sync(0xffffffffu, mine) & 0xFFu) << (8 * h);
    }
    return bad;
}
__device__ __noinline__ void exact_rows(int L, int pass, int wg, uint32_t bad) {
    const int tid = tid_now() & 127, lane = tid & 31, w = tid >> 5;
    const int head = (cta_now() & 15) * 2 + pass;
    const uint32_t scr = SB + OFF_PART + wg * 1024;
    if (lane == 0) sts32(scr + w * 4, bad);
    if (tid < 8) ctr_wait(&g_kvc[L][head][tid], 1);
    named_sync(3 + wg, 128);
    const float isc = ldsf(SB + OFF_M + M_ISC + pass * 4), ivs = ldsf(SB + OFF_M + M_IVS + pass * 4);
    const char* kv = g_kv + (size_t)head * 8 * KV_WIN + tid * 16;
    #pragma unroll 1
    for (int ww = 0; ww < 4; ww++) {
        uint32_t m = lds32(scr + ww * 4);
        #pragma unroll 1
        while (m) {
            const int bit = __ffs(m) - 1;
            m &= m - 1;
            const uint32_t qa = SB + OFF_QA + pass * 16384 + (wg * 2 + (bit >> 4)) * 4096 + (ww * 16 + (bit & 15)) * 16;
            float q[32], a[32], mx = -INFINITY, l = 0.f;
            #pragma unroll
            for (int ch = 0; ch < 4; ch++) {
                const uint4 u = lds128(qa + ch * 1024);
                h2_unpack(u.x, q[8*ch], q[8*ch+1]); h2_unpack(u.y, q[8*ch+2], q[8*ch+3]); h2_unpack(u.z, q[8*ch+4], q[8*ch+5]); h2_unpack(u.w, q[8*ch+6], q[8*ch+7]);
            }
            #pragma unroll
            for (int i = 0; i < 32; i++) a[i] = 0.f;
            #pragma unroll 1
            for (int it = 0; it < 16; it += 4) {
                uint4 u[4][8];
                #pragma unroll
                for (int i = 0; i < 4; i++)
                    #pragma unroll
                    for (int ch = 0; ch < 8; ch++) u[i][ch] = __ldcg(reinterpret_cast<const uint4*>(kv + ((it + i) >> 1) * KV_WIN + (i & 1) * 2048 + ch * 4096));
                float s[4], mn = mx;
                #pragma unroll
                for (int i = 0; i < 4; i++) {
                    s[i] = 0.f;
                    #pragma unroll
                    for (int ch = 0; ch < 4; ch++) {
                        const uint32_t v[4] = {u[i][ch].x, u[i][ch].y, u[i][ch].z, u[i][ch].w};
                        #pragma unroll
                        for (int e = 0; e < 4; e++) { float x, y; h2_unpack(v[e], x, y); s[i] = fmaf(x, q[8*ch + 2*e], fmaf(y, q[8*ch + 2*e + 1], s[i])); }
                    }
                    mn = fmaxf(mn, s[i]);
                }
                const float al = ex2((mx - mn) * isc);
                mx = mn; l *= al;
                #pragma unroll
                for (int i = 0; i < 32; i++) a[i] *= al;
                #pragma unroll
                for (int i = 0; i < 4; i++) {
                    const float p = ex2((s[i] - mx) * isc);
                    l += p;
                    #pragma unroll
                    for (int ch = 0; ch < 4; ch++) {
                        const uint32_t v[4] = {u[i][4 + ch].x, u[i][4 + ch].y, u[i][4 + ch].z, u[i][4 + ch].w};
                        #pragma unroll
                        for (int e = 0; e < 4; e++) { float x, y; h2_unpack(v[e], x, y); a[8*ch + 2*e] = fmaf(p, x, a[8*ch + 2*e]); a[8*ch + 2*e + 1] = fmaf(p, y, a[8*ch + 2*e + 1]); }
                    }
                }
            }
            const float mw = warp_max(mx);
            if (lane == 0) stsf(scr + 16 + w * 4, mw);
            named_sync(3 + wg, 128);
            const float al = ex2((mx - fmaxf(fmaxf(ldsf(scr + 16), ldsf(scr + 20)), fmaxf(ldsf(scr + 24), ldsf(scr + 28)))) * isc);
            l *= al;
            #pragma unroll
            for (int i = 0; i < 32; i++) a[i] *= al;
            l = warp_sum(l);
            #pragma unroll
            for (int j = 0; j < 31; j++) {
                const int o = j < 16 ? 16 : j < 24 ? 8 : j < 28 ? 4 : j < 30 ? 2 : 1, i = j - (32 - 2 * o);
                const bool up = lane & o;
                const float lo = a[i], hi = a[i + o];
                a[i] = (up ? hi : lo) + __shfl_xor_sync(0xffffffffu, up ? lo : hi, o);
            }
            stsf(scr + 32 + (w * 33 + lane) * 4, a[0]);
            if (lane == 0) stsf(scr + 32 + (w * 33 + 32) * 4, l);
            named_sync(3 + wg, 128);
            if (w == 0) {
                float o = 0.f, ls = 0.f;
                #pragma unroll
                for (int i = 0; i < 4; i++) { o += ldsf(scr + 32 + (i * 33 + lane) * 4); ls += ldsf(scr + 32 + (i * 33 + 32) * 4); }
                asm volatile("st.shared.u16 [%0], %1;" :: "r"(qa + (lane >> 3) * 1024 + (lane & 7) * 2), "h"((unsigned short)(pack_bf16(o * ivs / ls, 0.f))) : "memory");
            }
        }
    }
    named_sync(3 + wg, 128);
}

__device__ __forceinline__ void attention_phase(int L, int wg) {
    const uint32_t rb = L * 32;
    constexpr uint64_t dk0 = desc_plain(SB, 4096, 128), dv0 = desc_plain(SB + 16384, 128, 4096);
    constexpr int T1 = 2048 >> 4;
    uint32_t st = 0, ph = 0;
    #pragma unroll 1
    for (int pass = 0; pass < 2; pass++) {
        const uint64_t dqa = desc_plain(SB + OFF_QA, 1024, 128) + (pass * 4 + wg * 2) * (4096 >> 4), dqc = dqa + (4096 >> 4);
        Unit a, c;
        st = warp_uniform(st); ph = warp_uniform(ph);
        uint32_t SA[32], SC[32], PA[32], PC[32], ha[10], hc[10], pst = 0;
        #pragma unroll
        for (int i = 0; i < 10; i++) hc[i] = 0u;
        #pragma unroll
        for (int i = 0; i < 32; i++) PC[i] = 0u;
        mbar_wait(rb + B_AF + 8 * st, ph);
        wg_fence();
        issue_qk(SA, dqa, dk0 + st * (A_WIN >> 4));
        issue_qk(SC, dqc, dk0 + st * (A_WIN >> 4));
        wg_wait<1>();
        unit_init(a, SA);
        exp_tile(PA, SA, a);
        wg_wait<0>();
        unit_init(c, SC);
        #pragma unroll 1
        for (int s = 0;; s++) {
            const uint64_t dkb = dk0 + st * (A_WIN >> 4), dvb = dv0 + st * (A_WIN >> 4);
            uint32_t nst = st + 1, nph = ph;
            if (nst == 3) { nst = 0; nph ^= 1; }
            const uint64_t dkn = dk0 + nst * (A_WIN >> 4);
            wg_fence();
            issue_pv<true>(ha, PA, dvb); issue_qk(SA, dqa, dkb + T1);
            wg_wait<2>();
            if (s > 0) { mbar_arrive_elect(rb + B_AE + 8 * pst); unit_flush<true>(c, hc); }
            else {
                #pragma unroll
                for (int i = 0; i < 32; i++) c.o[i & 7] |= PC[i];
            }
            exp_tile(PC, SC, c);
            wg_fence();
            issue_pv<true>(hc, PC, dvb); issue_qk(SC, dqc, dkb + T1);
            wg_wait<2>();
            exp_tile(PA, SA, a);
            if (s == 7) {
                wg_fence(); issue_pv<false>(ha, PA, dvb + T1);
                wg_wait<1>();
                exp_tile(PC, SC, c);
                wg_fence(); issue_pv<false>(hc, PC, dvb + T1);
                wg_wait<1>();
                unit_flush<false>(a, ha);
                wg_wait<0>();
                unit_flush<false>(c, hc);
                mbar_arrive_elect(rb + B_AE + 8 * st);
                st = nst; ph = nph;
                break;
            }
            mbar_wait(rb + B_AF + 8 * nst, nph);
            wg_fence();
            issue_pv<false>(ha, PA, dvb + T1); issue_qk(SA, dqa, dkn);
            wg_wait<2>();
            exp_tile(PC, SC, c);
            wg_fence();
            issue_pv<false>(hc, PC, dvb + T1); issue_qk(SC, dqc, dkn);
            wg_wait<2>();
            unit_flush<true>(a, ha);
            exp_tile(PA, SA, a);
            pst = st; st = nst; ph = nph;
        }
        const int tid = tid_now(), lane = tid & 31;
        const float ivs = ldsf(SB + OFF_M + M_IVS + pass * 4);
        const bool head_ok = lds32(SB + OFF_M + M_OK + pass * 4) != 0;
        const uint32_t dst = SB + OFF_QA + pass * 16384 + wg * 8192 + (lane >> 3) * 1024 + (((tid >> 5) & 3) * 16 + (lane & 7)) * 16;
        const uint32_t bad = unit_store(a, dst, ivs, head_ok, lane) | unit_store(c, dst + 4096, ivs, head_ok, lane) << 16;
        if (__builtin_expect(named_any(bad != 0, 3 + wg), 0)) {
            exact_rows(L, pass, wg, bad);
        }
        fence_async_smem();
        named_arrive(N_OST + 2 * pass + wg, 160);
        TL(0, L * 48 + 8 + pass);
    }
}

constexpr uint32_t STAT_FULL = 0x41000000u;
__device__ __forceinline__ float2 ln_coef(const uint4& s) {
    const float mean = __uint_as_float(s.x) * (1.f / D_);
    return make_float2(rsq(fmaxf(fmaf(-mean, mean, __uint_as_float(s.y) * (1.f / D_)), 0.f) + LN_EPS), mean);
}

__device__ __forceinline__ void oproj_phase(int L, int wg) {
    const int c = cta_now(), tid = tid_now(), lane = tid & 31, W = tid >> 5, g = lane >> 2, t = lane & 3;
    const int row0 = (c >> 4) * 256 + (c & 1) * 128, col0 = ((c & 15) >> 1) * 128;
    float acc[64];
    #pragma unroll
    for (int i = 0; i < 64; i++) acc[i] = 0.f;
    #pragma unroll 1
    for (int k = 0; k < 16; k++) {
        const uint32_t s = k & 3;
        mbar_wait(B_OF + 8 * s, (k >> 2) & 1);
        TL((k & 7) == 0 ? 0 : -1, L * 48 + 10 + (k >> 3));
        const uint64_t da = desc_plain(SB, 1024, 128) + ((o_stage(s) + wg * 4096) >> 4);
        const uint64_t db = desc_sw128(SB + 16384, 8192, 1024) + (o_stage(s) >> 4);
        wg_fence();
        #pragma unroll
        for (int kk = 0; kk < 4; kk++) wg_gemm_n128(acc, da + (kk >> 1) * 512 + (kk & 1) * 128, db + kk * 128);
        wg_commit();
        if (k > 0) {
            wg_wait<1>();
            if ((tid & 127) == 0) mbar_arrive(B_OE + 8 * ((k - 1) & 3));
        }
    }
    mbar_wait(B_RES2, L);
    const uint32_t xa = SB + OFF_XT + (W * 16 + ((lane >> 3) & 1) * 8 + (lane & 7)) * 128, xs = (lane >> 4) ^ (lane & 7);
    uint32_t x[32];
    const uint32_t wra = SB + OFF_WR + (g == 0 ? t * 8 : 256), wrs = g == 0 ? 32 : 0;
    wg_wait<0>();
    if ((tid & 127) == 0) mbar_arrive(B_OE + 24);
    TL(0, L * 48 + 12);
    {
        float sd[4] = {0.f, 0.f, 0.f, 0.f}, q0[4] = {0.f, 0.f, 0.f, 0.f}, q1[4] = {0.f, 0.f, 0.f, 0.f};
        #pragma unroll
        for (int ks = 0; ks < 8; ks++) {
            ldsm4(x[4*ks], x[4*ks+1], x[4*ks+2], x[4*ks+3], xa + (ks >> 2) * 16384 + ((xs ^ ((ks & 3) * 2)) << 4));
            const float2 wb = lds64f(wra + ks * wrs);
            #pragma unroll
            for (int i = 0; i < 4; i++) x[4*ks + i] = badd2(x[4*ks + i], pack_bf16(acc[8*ks + 2*i], acc[8*ks + 2*i + 1]));
            mma_bf16(sd, x[4*ks], x[4*ks+1], x[4*ks+2], x[4*ks+3], __float_as_uint(wb.x), __float_as_uint(wb.y));
            mma_bf16(q0, x[4*ks], x[4*ks+1], x[4*ks+2], x[4*ks+3], x[4*ks], x[4*ks+2]);
            mma_bf16(q1, x[4*ks], x[4*ks+1], x[4*ks+2], x[4*ks+3], x[4*ks+1], x[4*ks+3]);
        }
        const float s0 = __shfl_sync(0xffffffffu, (g & 1) ? q0[1] : q0[0], 4 * g + (g >> 1));
        const float s1 = __shfl_sync(0xffffffffu, (g & 1) ? q1[3] : q1[2], 4 * g + (g >> 1));
        if (t == 0) {
            float4* p = &g_sums[L][row0 + W * 16 + g];
            asm volatile("red.relaxed.gpu.global.add.v4.f32 [%0], {%1, %2, %3, %4};" :: "l"(p), "f"(sd[1]), "f"(s0), "f"(sd[0]), "f"(1.f) : "memory");
            asm volatile("red.relaxed.gpu.global.add.v4.f32 [%0], {%1, %2, %3, %4};" :: "l"(p + 8), "f"(sd[3]), "f"(s1), "f"(sd[2]), "f"(1.f) : "memory");
        }
    }
    #pragma unroll
    for (int ks = 0; ks < 8; ks++) stsm4(xa + (ks >> 2) * 16384 + ((xs ^ ((ks & 3) * 2)) << 4), x[4*ks], x[4*ks+1], x[4*ks+2], x[4*ks+3]);
    TL(0, L * 48 + 13);
    if (L == 1) {
        uint4 s0 = make_uint4(0u, 0u, 0u, 0u), s1 = s0;
        uint32_t n = 0;
        do {
            ld_relaxed4_unless(s0, &g_sums[1][row0 + W * 16 + g], STAT_FULL); ld_relaxed4_unless(s1, &g_sums[1][row0 + W * 16 + g + 8], STAT_FULL);
        } while ((s0.w != STAT_FULL || s1.w != STAT_FULL) && ++n < SPIN_MAX);
        __syncwarp();
        mbar_wait(B_OE + 24, 1);
        const float2 r0 = ln_coef(s0), r1 = ln_coef(s1);
        const float b0 = -r0.x * r0.y, b1 = -r1.x * r1.y;
        #pragma unroll
        for (int ks = 0; ks < 8; ks++)
            stsm4(xa - (OFF_XT - OFF_OUT) + (ks >> 2) * 16384 + ((xs ^ ((ks & 3) * 2)) << 4), add_ln2(x[4*ks], r0.x, b0), add_ln2(x[4*ks+1], r1.x, b1),
                  add_ln2(x[4*ks+2], r0.x, b0), add_ln2(x[4*ks+3], r1.x, b1));
    }
    fence_async_smem();
    named_arrive(N_XST + wg, 160);
    TL(0, L * 48 + 45);
    {
        {
            const float ws = ldsf(SB + OFF_M + M_WS) + ldsf(SB + OFF_M + M_WS + 4) + ldsf(SB + OFF_M + M_WS + 8);
            uint4 sv[8];
            #pragma unroll
            for (int i = 0; i < 8; i++) sv[i] = make_uint4(0u, 0u, 0u, 0u);
            uint32_t n = 0;
            bool done;
            do {
                done = true;
                #pragma unroll
                for (int i = 0; i < 8; i++) ld_relaxed4_unless(sv[i], &g_sums[L][tid + 256 * i], STAT_FULL);
                #pragma unroll
                for (int i = 0; i < 8; i++) done = done && sv[i].w == STAT_FULL;
            } while (!done && ++n < SPIN_MAX);
            spin_check(n);
            __syncwarp();
            TL(0, L * 48 + 15);
            uint4 best;
            #pragma unroll
            for (int i = 0; i < 8; i++) {
                const float2 r = ln_coef(sv[i]);
                const uint32_t k = order_bits(r.x * (__uint_as_float(sv[i].z) - r.y * ws));
                if (i == 0 || k > best.x) best = make_uint4(k, tid + 256 * i, __float_as_uint(r.y), __float_as_uint(r.x));
            }
            const uint32_t m = redux_max(best.x), mrow = redux_min(best.x == m ? best.y : 0x7FFFFFFFu);
            if (best.y == mrow) sts128(SB + OFF_RT + W * 16, best);
        }
        named_sync(1, 256);
        if (W == 7) named_arrive(N_RT, 128);
        const RouteOut rt = route_result(lane);
        const int lrt = rt.idx - row0;
        {
            uint4 v = lds128(SB + OFF_XT + ((lane >> 3) & 1) * 16384 + (lrt & 127) * 128 + (((lane & 7) ^ (lrt & 7)) << 4));
            v.x = min(v.x, SENT - 1); v.y = min(v.y, SENT - 1); v.z = min(v.z, SENT - 1); v.w = min(v.w, SENT - 1);
            st_relaxed4_if(&g_xrow[L][col0 / 2 + lane * 4], v, (lrt >> 4) == W && lane < 16);
        }
        TL(0, L * 48 + 16);
    const bool ffn = c < NFC;
    uint4 fa[32];
    if (ffn) { mbar_wait(B_FE, L); mbar_wait(B_FL, L); }
    TL(224, L * 48 + 44);
    {
        const uint32_t ro = SB + (W & 1) * 8192 + ((lane >> 4) * 8 + (lane & 7)) * 64, ga = ro + gu_piece(W & 6), ua = ro + gu_piece(W | 1), gs = ((lane >> 3) & 1) ^ ((lane >> 1) & 3);
        #pragma unroll
        for (int i = 0; i < 32; i++) ldsm4t(fa[i].x, fa[i].y, fa[i].z, fa[i].w, ((i & 2) ? ua : ga) + (i >> 2) * 1024 + ((gs ^ ((i & 1) * 2)) << 4));
    }
    mbar_arrive_elect(B_GD);
        uint2 xrow;
        {
            uint32_t n = 0;
            const uint32_t* p = &g_xrow[L][(tid >> 2) * 8 + t];
            do { xrow.x = ld_relaxed(p); xrow.y = ld_relaxed(p + 4); } while ((xrow.x == SENT || xrow.y == SENT) && ++n < SPIN_MAX);
            spin_check(n);
            __syncwarp();
        }
        TL(0, L * 48 + 17);
        const float nb = -rt.mean * rt.rstd;
        const uint32_t n0 = pack_bf16(fmaf(bf_lo(xrow.x), rt.rstd, nb), fmaf(bf_hi(xrow.x), rt.rstd, nb));
        const uint32_t n1 = pack_bf16(fmaf(bf_lo(xrow.y), rt.rstd, nb), fmaf(bf_hi(xrow.y), rt.rstd, nb));
        float gu[8][4];
        #pragma unroll
        for (int i = 0; i < 8; i++) { gu[i][0] = 0.f; gu[i][1] = 0.f; gu[i][2] = 0.f; gu[i][3] = 0.f; }
        #pragma unroll
        for (int ks = 0; ks < 8; ks++) {
            const uint32_t b0 = __shfl_sync(0xffffffffu, n0, 4 * ks + t), b1 = __shfl_sync(0xffffffffu, n1, 4 * ks + t);
            #pragma unroll
            for (int i = 0; i < 4; i++) mma_bf16(gu[(ks & 1) * 4 + i], fa[4*ks + i].x, fa[4*ks + i].y, fa[4*ks + i].z, fa[4*ks + i].w, b0, b1);
        }
        stsf(SB + OFF_PART + (W * 64 + t * 16 + g) * 4, sel4(t, gu[0][0] + gu[4][0], gu[1][0] + gu[5][0], gu[2][0] + gu[6][0], gu[3][0] + gu[7][0]));
        stsf(SB + OFF_PART + (W * 64 + t * 16 + g + 8) * 4, sel4(t, gu[0][2] + gu[4][2], gu[1][2] + gu[5][2], gu[2][2] + gu[6][2], gu[3][2] + gu[7][2]));
        if (ffn) mbar_wait(B_FD, L);
        const uint32_t wa = SB + OFF_FD + W * 8192 + ((lane >> 4) * 8 + (lane & 7)) * 128, wsw = ((lane >> 3) & 1) ^ (lane & 7);
        #pragma unroll
        for (int i = 0; i < 16; i++) ldsm4t(fa[i].x, fa[i].y, fa[i].z, fa[i].w, wa + (i >> 3) * 4096 + (i & 1) * 2048 + ((wsw ^ (((i >> 1) & 3) * 2)) << 4));
        named_sync(1, 256);
        if (tid == 0) mbar_arrive(B_DD);
        TL(0, L * 48 + 18);
        float gsum = 0.f, usum = 0.f;
        #pragma unroll
        for (int i = 0; i < 8; i++) { gsum += ldsf(SB + OFF_PART + (i * 64 + lane) * 4); usum += ldsf(SB + OFF_PART + (i * 64 + 32 + lane) * 4); }
        const float gv = bf_round(gsum), uv = bf_round(usum);
        const float hv = bf_round(__fdividef(gv, 1.f + __expf(-gv))) * uv;
        const uint32_t hp = pack_bf16(hv, __shfl_down_sync(0xffffffffu, hv, 1));
        uint32_t hb[4];
        #pragma unroll
        for (int i = 0; i < 4; i++) hb[i] = __shfl_sync(0xffffffffu, hp, 8 * i + 2 * t);
        float y[8][4];
        #pragma unroll
        for (int mb = 0; mb < 8; mb++) {
            y[mb][0] = 0.f; y[mb][1] = 0.f; y[mb][2] = 0.f; y[mb][3] = 0.f;
            #pragma unroll
            for (int ks = 0; ks < 2; ks++) mma_bf16(y[mb], fa[2*mb + ks].x, fa[2*mb + ks].y, fa[2*mb + ks].z, fa[2*mb + ks].w, hb[2 * ks], hb[2 * ks + 1]);
        }
        uint4 v;
        v.x = not_sent(sel4(t, y[0][0], y[2][0], y[4][0], y[6][0]));
        v.y = not_sent(sel4(t, y[0][2], y[2][2], y[4][2], y[6][2]));
        v.z = not_sent(sel4(t, y[1][0], y[3][0], y[5][0], y[7][0]));
        v.w = not_sent(sel4(t, y[1][2], y[3][2], y[5][2], y[7][2]));
        st_relaxed4_if(&g_ypart[L][min(c, NFC - 1)][tid * 4], v, ffn);
        TL(0, L * 48 + 19);
    }
}

#define FW0 8
__device__ __forceinline__ void qkv_fill(const CUtensorMap* tx, const CUtensorMap* tw, uint32_t bar, int st, int k) {
    const uint32_t sa = SB + st * Q_STB;
    mbar_expect_tx(bar, Q_STB);
    tma_load(sa, tx, k * 64, (blockIdx.x >> 4) * 256, bar);
    tma_load3(sa + Q_ABYTES, tw, (blockIdx.x & 15) * 64, k * 64, 0, bar);
}
__device__ __forceinline__ void producer_role(const Maps& mp) {
    const int c = blockIdx.x, mt = c >> 4, nt = c & 15, lane = threadIdx.x & 31;
    #pragma unroll 1
    for (int i = 2; i < 12; i++) tm_prefetch(&mp.xa0 + i);
    #pragma unroll 1
    for (int L = 0; L < 2; L++) {
        const uint32_t rb = L * 32;
        uint32_t st = 0, ph = L;
        #pragma unroll 1
        for (int k = L == 0 ? 3 : 0; k < 16; k++) {
            if (k == 0) { ctr_wait(&g_xc[0][mt], 32); fence_async_global(); mbar_wait(B_GD, 0); }
            if (k == 1) mbar_wait(B_DD, 0);
            mbar_wait(rb + B_QE + 8 * st, ph);
            qkv_fill(L == 0 ? &mp.xa0 : &mp.xa, &mp.wqkv, rb + B_QF + 8 * st, st, k);
            if (L == 1 && k >= 3 && k < 7) {
                if (k == 3) mbar_expect_tx(B_SW, 4 * 12288);
                tma_load(SB + OFF_SIDE + (k - 3) * 12288, &mp.r, c * 24, (k - 3) * 256, B_SW);
            }
            if (++st == 3) { st = 0; ph ^= 1; }
        }
        mbar_wait(B_KV0, L);
        st = 1; ph = 1;
        #pragma unroll 1
        for (int w = 1; w < 16; w++) {
            const int win = (nt * 2 + (w >> 3)) * 8 + ((mt + w) & 7);
            if (w == 2) mbar_wait(B_SL2, L);
            if (w <= 2 || w == 8) {
                ctr_wait(&g_kvc[L][0][0] + (w == 1 ? win : (win & ~7) + (lane & 7)), 1);
                __syncwarp();
                fence_async_global();
            }
            TL(w == 1 ? 256 : -1, L * 48 + 7);
            mbar_wait(rb + B_AE + 8 * st, ph);
            mbar_expect_tx(rb + B_AF + 8 * st, KV_WIN);
            bulk_load(SB + st * A_WIN, g_kv + (size_t)win * KV_WIN, KV_WIN, rb + B_AF + 8 * st);
            if (w == FW0) named_arrive(N_FW, 64);
            if (++st == 3) { st = 0; ph ^= 1; }
        }
        #pragma unroll 1
        for (int k = 0; k < 16; k++) {
            const uint32_t s = k & 3, fb = B_OF + 8 * s, sa = SB + o_stage(s);
            mbar_wait(k < 2 ? rb + B_AE + 8 + 8 * k : k == 2 ? rb + B_AE : k == 3 ? B_QAF : B_OE + 8 * s, k < 2 ? 0 : k == 2 ? 1 : k == 3 ? L : ((k >> 2) - 1) & 1);
            mbar_expect_tx(fb, 32768);
            tma_load5(sa + 16384, &mp.wo, 0, 0, k >> 3, (k & 7) * 2, nt & 14, fb);
            if ((k & 7) == 0) { ctr_wait(&g_oc[L][mt * 2 + (nt & 1)][k >> 3], 16); fence_async_global(); }
            bulk_load(sa, g_o + (size_t)((mt * 2 + (nt & 1)) * 16 + k) * 16384, 16384, fb);
        }
        if (c < NFC) {
            mbar_expect_tx(B_FL, 5 * 16384);
            mbar_expect_tx(B_FD, 4 * 16384);
            #pragma unroll 1
            for (int i = 3; i < 12; i++) {
                mbar_wait(B_OE + (i < 5 ? 0 : i == 5 ? 8 : i < 9 ? 16 : 24), 1);
                if (i == 10 && L == 1) mbar_wait(B_XRD, 0);
                ffn_load(mp, i, SB + (i < 8 ? gu_piece(i) : OFF_FD + (i - 8) * 16384), i < 8 ? B_FL : B_FD);
            }
        }
    }
}

__global__ void __launch_bounds__(384, 1) k_all(const __grid_constant__ Maps mp, const bf16* __restrict__ x0, const bf16* __restrict__ wo,
                                                const bf16* __restrict__ w_r, bf16* __restrict__ out) {
    extern __shared__ __align__(1024) char smem[];
    if (smem_u32(smem) != SB) __trap();
    const int warp = warp_uniform(threadIdx.x >> 5), wg = warp >> 2;
    TL(0, 0);
    {
        const int grp = warp >= 8 ? warp - 8 : warp + 4;
        #pragma unroll
        for (int i = 0; i < 4; i++) mbar_init(BB + grp * 32 + i * 8, grp < 7 ? 1 : grp < 10 ? 2 : 8);
        fence_mbar_init();
    }
    if (warp == 8) {
        #pragma unroll 1
        for (int s = 0; s < 3; s++) qkv_fill(&mp.xa0, &mp.wqkv, B_QF + 8 * s, s, s);
    }
    __syncthreads();
    if (wg == 2) {
        reg_dec<40>();
        if (warp == 8) producer_role(mp);
        else side_role(mp, x0, wo, w_r, out);
    } else {
        reg_inc<232>();
        #pragma unroll 1
        for (int L = 0; L < 2; L++) {
            qkv_phase(L, wg);
            attention_phase(L, wg);
            oproj_phase(L, wg);
        }
    }
}

typedef CUresult (*EncodeFn)(CUtensorMap*, CUtensorMapDataType, cuuint32_t, void*, const cuuint64_t*, const cuuint64_t*, const cuuint32_t*,
                             const cuuint32_t*, CUtensorMapInterleave, CUtensorMapSwizzle, CUtensorMapL2promotion, CUtensorMapFloatOOBfill);

void make_map(EncodeFn enc, CUtensorMap* tm, const void* ptr, int rank, const cuuint64_t* dims, const cuuint64_t* strides, const cuuint32_t* box, CUtensorMapSwizzle sw) {
    const cuuint32_t es[5] = {1, 1, 1, 1, 1};
    enc(tm, CU_TENSOR_MAP_DATA_TYPE_BFLOAT16, rank, const_cast<void*>(ptr), dims, strides, box, es, CU_TENSOR_MAP_INTERLEAVE_NONE, sw,
        box[0] == 64 ? CU_TENSOR_MAP_L2_PROMOTION_L2_128B : CU_TENSOR_MAP_L2_PROMOTION_NONE, CU_TENSOR_MAP_FLOAT_OOB_FILL_NONE);
}
void make_map2(EncodeFn enc, CUtensorMap* tm, const void* ptr, uint64_t cols, uint64_t rows, uint32_t bc, uint32_t br, CUtensorMapSwizzle sw) {
    const cuuint64_t dims[2] = {cols, rows}, strides[1] = {cols * 2};
    const cuuint32_t box[2] = {bc, br};
    make_map(enc, tm, ptr, 2, dims, strides, box, sw);
}

}

extern "C" void kernel_launch(void* const* d_in, const int* in_sizes, int n_in, void* d_out, int out_size) {
    const bf16* x0 = (const bf16*)d_in[0];
    const bf16* wqkv = (const bf16*)d_in[1];
    const bf16* wo = (const bf16*)d_in[2];
    const bf16* w_r = (const bf16*)d_in[4];
    const bf16* w_gate = (const bf16*)d_in[5];
    const bf16* w_up = (const bf16*)d_in[6];
    const bf16* w_down = (const bf16*)d_in[7];

    EncodeFn enc = nullptr;
    cudaDriverEntryPointQueryResult qr;
    cudaGetDriverEntryPoint("cuTensorMapEncodeTiled", (void**)&enc, cudaEnableDefault, &qr);
    void* p_x;
    cudaGetSymbolAddress(&p_x, g_x);
    Maps mp;
    const CUtensorMapSwizzle S128 = CU_TENSOR_MAP_SWIZZLE_128B;
    make_map2(enc, &mp.x0, x0, D_, S_, 64, 64, S128);
    make_map2(enc, &mp.x, p_x, D_, S_, 64, 64, S128);
    make_map2(enc, &mp.out, d_out, D_, S_, 64, 64, S128);
    make_map2(enc, &mp.xa0, x0, D_, S_, 64, 256, S128);
    make_map2(enc, &mp.xa, p_x, D_, S_, 64, 256, S128);
    make_map2(enc, &mp.w64, wqkv, 3 * D_, D_, 64, 64, S128);
    {
        const cuuint64_t dims[3] = {D_, D_, 3}, strides[2] = {3 * D_ * 2, D_ * 2};
        const cuuint32_t box[3] = {64, 64, 3};
        make_map(enc, &mp.wqkv, wqkv, 3, dims, strides, box, S128);
    }
    make_map2(enc, &mp.r, wqkv, 3 * D_, D_, 24, 256, CU_TENSOR_MAP_SWIZZLE_NONE);
    make_map2(enc, &mp.g, w_gate, FF, D_, 32, 256, CU_TENSOR_MAP_SWIZZLE_64B);
    make_map2(enc, &mp.u, w_up, FF, D_, 32, 256, CU_TENSOR_MAP_SWIZZLE_64B);
    {
        const cuuint64_t dims[5] = {64, 32, 2, 16, 16}, strides[4] = {D_ * 2, 32 * D_ * 2, 64 * D_ * 2, 128};
        const cuuint32_t box[5] = {64, 32, 1, 2, 2};
        make_map(enc, &mp.wo, wo, 5, dims, strides, box, S128);
    }
    {
        const cuuint64_t dims[3] = {64, FF, 16}, strides[2] = {D_ * 2, 128};
        const cuuint32_t box[3] = {64, 32, 4};
        make_map(enc, &mp.d, w_down, 3, dims, strides, box, S128);
    }
    cudaFuncSetAttribute(k_all, cudaFuncAttributeMaxDynamicSharedMemorySize, K_SMEM);
    k_all<<<128, 384, K_SMEM, cudaStreamPerThread>>>(mp, x0, wo, w_r, (bf16*)d_out);
}
```

```cpp
#include <cuda_runtime.h>
#include <cuda_bf16.h>
#include <cuda_fp16.h>
#include <cuda.h>
#include <cudaTypedefs.h>
#include <stdint.h>

namespace {

typedef __nv_bfloat16 bf16;

constexpr int S_ = 2048, D_ = 1024, NH = 32, FF = 3584, NFC = FF / 32;
constexpr float LN_EPS = 1e-5f;
constexpr float QSCALE = 0.17677669529663687f * 1.4426950408889634f;
constexpr uint32_t SENT = 0xFFFFFFFFu;

constexpr int KV_WIN = 32768;
__device__ __align__(1024) char g_kv[NH * 8 * KV_WIN];
__device__ __align__(1024) char g_o[32 * 2 * 16 * 4096];
__device__ __align__(1024) bf16 g_x[S_ * D_];
__device__ float g_csum[8 * 3 * D_];
__device__ float g_wsq[8 * 96];
__device__ float2 g_rs0[S_];
__device__ __align__(128) float4 g_sums[2][S_];
__device__ __align__(128) uint32_t g_ypart[2][NFC][D_];
__device__ __align__(128) uint32_t g_xrow[2][D_ / 2];
__device__ __align__(128) uint32_t g_x2row[D_];
__device__ __align__(128) uint32_t g_fix[3 * D_];
__device__ uint32_t g_c0;
__device__ __align__(128) uint32_t g_kvc[2][NH][8];
__device__ __align__(128) uint32_t g_oc[2][16][2];
__device__ __align__(128) uint32_t g_xc[2][8];
struct RouteOut { int idx; float r; float mean; float rstd; };

constexpr uint32_t SB = 1024;

__device__ __forceinline__ uint32_t smem_u32(const void* p) { return (uint32_t)__cvta_generic_to_shared(p); }
__device__ __forceinline__ void mbar_arrive(uint32_t bar) { asm volatile("mbarrier.arrive.shared::cta.b64 _, [%0];" :: "r"(bar) : "memory"); }
__device__ __forceinline__ void mbar_wait(uint32_t bar, uint32_t parity) {
    asm volatile("{\n.reg .pred p;\n.reg .u32 n;\nmov.u32 n, 0;\n"
                 "LAB_WAIT:\nmbarrier.try_wait.parity.shared::cta.b64 p, [%0], %1, 2000;\n@p bra LAB_DONE;\n"
                 "add.u32 n, n, 1;\nsetp.lt.u32 p, n, 0x200000;\n@p bra LAB_WAIT;\ntrap;\nLAB_DONE:\n}" :: "r"(bar), "r"(parity) : "memory");
}
__device__ __forceinline__ void mbar_arrive_elect(uint32_t bar) {
    asm volatile("{\n.reg .pred p;\nelect.sync _|p, 0xffffffff;\n@p mbarrier.arrive.shared::cta.b64 _, [%0];\n}" :: "r"(bar) : "memory");
}
__device__ __forceinline__ int tid_now() { int v; asm volatile("mov.u32 %0, %%tid.x;" : "=r"(v)); return v; }
__device__ __forceinline__ int cta_now() { int v; asm volatile("mov.u32 %0, %%ctaid.x;" : "=r"(v)); return v; }
__device__ __forceinline__ int warp_uniform(int v) { return __shfl_sync(0xffffffffu, v, 0); }
__device__ __forceinline__ void fence_mbar_init() { asm volatile("fence.mbarrier_init.release.cluster;" ::: "memory"); }
__device__ __forceinline__ void fence_async_smem() { asm volatile("fence.proxy.async.shared::cta;" ::: "memory"); }
__device__ __forceinline__ void fence_async_global() { asm volatile("fence.proxy.async.global;" ::: "memory"); }
__device__ __forceinline__ void named_sync(int id, int n) { asm volatile("bar.sync %0, %1;" :: "r"(id), "r"(n) : "memory"); }
__device__ __forceinline__ void named_arrive(int id, int n) { asm volatile("bar.arrive %0, %1;" :: "r"(id), "r"(n) : "memory"); }
__device__ __forceinline__ bool named_any(bool p, int id) {
    uint32_t r;
    asm volatile("{\n.reg .pred a, b;\nsetp.ne.u32 a, %1, 0;\nbarrier.cta.red.or.pred b, %2, 128, a;\nselp.u32 %0, 1, 0, b;\n}" : "=r"(r) : "r"((uint32_t)p), "r"(id) : "memory");
    return r != 0;
}
#define ELECT(op) "{\n.reg .pred e;\nelect.sync _|e, 0xffffffff;\n@e " op "\n}"
__device__ __forceinline__ void mbar_init(uint32_t bar, int cnt) { asm volatile(ELECT("mbarrier.init.shared::cta.b64 [%0], %1;") :: "r"(bar), "r"(cnt) : "memory"); }
__device__ __forceinline__ void mbar_expect_tx(uint32_t bar, uint32_t bytes) { asm volatile(ELECT("mbarrier.arrive.expect_tx.shared::cta.b64 _, [%0], %1;") :: "r"(bar), "r"(bytes) : "memory"); }
__device__ __forceinline__ void bulk_load(uint32_t dst, const void* src, uint32_t bytes, uint32_t bar) {
    asm volatile(ELECT("cp.async.bulk.shared::cluster.global.mbarrier::complete_tx::bytes [%0], [%1], %2, [%3];") :: "r"(dst), "l"(src), "r"(bytes), "r"(bar) : "memory");
}
__device__ __forceinline__ void bulk_store(void* dst, uint32_t src, uint32_t bytes) {
    asm volatile(ELECT("cp.async.bulk.global.shared::cta.bulk_group [%0], [%1], %2;") :: "l"(dst), "r"(src), "r"(bytes) : "memory");
}
__device__ __forceinline__ void bulk_commit() { asm volatile("cp.async.bulk.commit_group;" ::: "memory"); }
__device__ __forceinline__ void bulk_wait() { asm volatile("cp.async.bulk.wait_group 0;" ::: "memory"); }
template <int N> __device__ __forceinline__ void bulk_wait_n() { asm volatile("cp.async.bulk.wait_group %0;" :: "n"(N) : "memory"); }
__device__ __forceinline__ void bulk_wait_read() { asm volatile("cp.async.bulk.wait_group.read 0;" ::: "memory"); }
__device__ __forceinline__ void l2_prefetch(const void* src, uint32_t bytes) {
    asm volatile(ELECT("cp.async.bulk.prefetch.L2.global [%0], %1;") :: "l"(src), "r"(bytes) : "memory");
}
__device__ __forceinline__ void tma_load(uint32_t dst, const CUtensorMap* tm, int c0, int c1, uint32_t bar) {
    asm volatile(ELECT("cp.async.bulk.tensor.2d.shared::cluster.global.mbarrier::complete_tx::bytes [%0], [%1, {%3, %4}], [%2];")
                 :: "r"(dst), "l"(tm), "r"(bar), "r"(c0), "r"(c1) : "memory");
}
__device__ __forceinline__ void tma_load3(uint32_t dst, const CUtensorMap* tm, int c0, int c1, int c2, uint32_t bar) {
    asm volatile(ELECT("cp.async.bulk.tensor.3d.shared::cluster.global.mbarrier::complete_tx::bytes [%0], [%1, {%3, %4, %5}], [%2];")
                 :: "r"(dst), "l"(tm), "r"(bar), "r"(c0), "r"(c1), "r"(c2) : "memory");
}
__device__ __forceinline__ void tma_load5(uint32_t dst, const CUtensorMap* tm, int c0, int c1, int c2, int c3, int c4, uint32_t bar) {
    asm volatile(ELECT("cp.async.bulk.tensor.5d.shared::cluster.global.mbarrier::complete_tx::bytes [%0], [%1, {%3, %4, %5, %6, %7}], [%2];")
                 :: "r"(dst), "l"(tm), "r"(bar), "r"(c0), "r"(c1), "r"(c2), "r"(c3), "r"(c4) : "memory");
}
__device__ __forceinline__ void tma_store(const CUtensorMap* tm, uint32_t src, int c0, int c1) {
    asm volatile(ELECT("cp.async.bulk.tensor.2d.global.shared::cta.bulk_group [%0, {%2, %3}], [%1];") :: "l"(tm), "r"(src), "r"(c0), "r"(c1) : "memory");
}
__device__ __forceinline__ void tm_prefetch(const CUtensorMap* tm) { asm volatile(ELECT("prefetch.tensormap [%0];") :: "l"(tm) : "memory"); }
__device__ __forceinline__ uint32_t lds32(uint32_t a) { uint32_t v; asm volatile("ld.shared.b32 %0, [%1];" : "=r"(v) : "r"(a) : "memory"); return v; }
__device__ __forceinline__ float ldsf(uint32_t a) { return __uint_as_float(lds32(a)); }
__device__ __forceinline__ float2 lds64f(uint32_t a) { float2 v; asm volatile("ld.shared.v2.f32 {%0, %1}, [%2];" : "=f"(v.x), "=f"(v.y) : "r"(a) : "memory"); return v; }
__device__ __forceinline__ uint4 lds128(uint32_t a) { uint4 v; asm volatile("ld.shared.v4.b32 {%0, %1, %2, %3}, [%4];" : "=r"(v.x), "=r"(v.y), "=r"(v.z), "=r"(v.w) : "r"(a) : "memory"); return v; }
__device__ __forceinline__ void sts32(uint32_t a, uint32_t v) { asm volatile("st.shared.b32 [%0], %1;" :: "r"(a), "r"(v) : "memory"); }
__device__ __forceinline__ void stsf(uint32_t a, float v) { sts32(a, __float_as_uint(v)); }
__device__ __forceinline__ void sts64f(uint32_t a, float x, float y) { asm volatile("st.shared.v2.f32 [%0], {%1, %2};" :: "r"(a), "f"(x), "f"(y) : "memory"); }
__device__ __forceinline__ void sts128(uint32_t a, const uint4& v) { asm volatile("st.shared.v4.b32 [%0], {%1, %2, %3, %4};" :: "r"(a), "r"(v.x), "r"(v.y), "r"(v.z), "r"(v.w) : "memory"); }
__device__ __forceinline__ void stsm4(uint32_t a, uint32_t x, uint32_t y, uint32_t z, uint32_t w) {
    asm volatile("stmatrix.sync.aligned.m8n8.x4.shared.b16 [%0], {%1, %2, %3, %4};" :: "r"(a), "r"(x), "r"(y), "r"(z), "r"(w) : "memory");
}
__device__ __forceinline__ void ldsm4(uint32_t& a0, uint32_t& a1, uint32_t& a2, uint32_t& a3, uint32_t addr) {
    asm volatile("ldmatrix.sync.aligned.m8n8.x4.shared.b16 {%0,%1,%2,%3}, [%4];" : "=r"(a0), "=r"(a1), "=r"(a2), "=r"(a3) : "r"(addr) : "memory");
}
__device__ __forceinline__ void ldsm4t(uint32_t& a0, uint32_t& a1, uint32_t& a2, uint32_t& a3, uint32_t addr) {
    asm volatile("ldmatrix.sync.aligned.m8n8.x4.trans.shared.b16 {%0,%1,%2,%3}, [%4];" : "=r"(a0), "=r"(a1), "=r"(a2), "=r"(a3) : "r"(addr) : "memory");
}
__device__ __forceinline__ void mma_bf16(float (&c)[4], uint32_t a0, uint32_t a1, uint32_t a2, uint32_t a3, uint32_t b0, uint32_t b1) {
    asm("mma.sync.aligned.m16n8k16.row.col.f32.bf16.bf16.f32 {%0,%1,%2,%3}, {%4,%5,%6,%7}, {%8,%9}, {%0,%1,%2,%3};"
        : "+f"(c[0]), "+f"(c[1]), "+f"(c[2]), "+f"(c[3]) : "r"(a0), "r"(a1), "r"(a2), "r"(a3), "r"(b0), "r"(b1));
}
__device__ __forceinline__ uint32_t ld_relaxed(const void* p) { uint32_t v; asm volatile("ld.relaxed.gpu.global.u32 %0, [%1];" : "=r"(v) : "l"(p) : "memory"); return v; }
__device__ __forceinline__ uint4 ld_relaxed4(const void* p) {
    uint4 v; asm volatile("ld.relaxed.gpu.global.v4.b32 {%0, %1, %2, %3}, [%4];" : "=r"(v.x), "=r"(v.y), "=r"(v.z), "=r"(v.w) : "l"(p) : "memory"); return v;
}
__device__ __forceinline__ void ld_relaxed4_unless(uint4& v, const void* p, uint32_t full) {
    asm volatile("{\n.reg .pred q;\nsetp.ne.u32 q, %3, %5;\n@q ld.relaxed.gpu.global.v4.b32 {%0, %1, %2, %3}, [%4];\n}"
                 : "+r"(v.x), "+r"(v.y), "+r"(v.z), "+r"(v.w) : "l"(p), "r"(full) : "memory");
}
__device__ __forceinline__ uint2 ld_relaxed2(const void* p) { uint2 v; asm volatile("ld.relaxed.gpu.global.v2.b32 {%0, %1}, [%2];" : "=r"(v.x), "=r"(v.y) : "l"(p) : "memory"); return v; }
__device__ __forceinline__ void st_relaxed(void* p, uint32_t v) { asm volatile("st.relaxed.gpu.global.u32 [%0], %1;" :: "l"(p), "r"(v) : "memory"); }
__device__ __forceinline__ void st_relaxed4_if(void* p, const uint4& v, bool on) {
    asm volatile("{\n.reg .pred q;\nsetp.ne.u32 q, %5, 0;\n@q st.relaxed.gpu.global.v4.b32 [%0], {%1, %2, %3, %4};\n}"
                 :: "l"(p), "r"(v.x), "r"(v.y), "r"(v.z), "r"(v.w), "r"((uint32_t)on) : "memory");
}
__device__ __forceinline__ uint32_t not_sent(float v) { const uint32_t u = __float_as_uint(v); return u == SENT ? 0x7FFFFFFFu : u; }
__device__ __forceinline__ bool has_sent(const uint4& v) { return max(max(v.x, v.y), max(v.z, v.w)) == SENT; }
constexpr uint32_t SPIN_MAX = 1u << 22;
__device__ __forceinline__ void spin_check(uint32_t n) { asm volatile("{\n.reg .pred p;\nsetp.ge.u32 p, %0, %1;\n@p st.global.u32 [%2], %0;\n}" :: "r"(n), "n"(SPIN_MAX), "l"(0ull) : "memory"); }
__device__ __forceinline__ void ctr_arrive(uint32_t* c) { asm volatile(ELECT("red.release.gpu.global.add.u32 [%0], 1;") :: "l"(c) : "memory"); }
__device__ __forceinline__ void ctr_wait(const uint32_t* c, uint32_t target) {
    asm volatile("{\n.reg .pred p;\n.reg .u32 n, v;\nmov.u32 n, 0;\n"
                 "LAB_WAIT:\nld.acquire.gpu.global.u32 v, [%0];\nsetp.ge.u32 p, v, %1;\n@p bra LAB_DONE;\n"
                 "add.u32 n, n, 1;\nsetp.lt.u32 p, n, 0x400000;\n@p bra LAB_WAIT;\ntrap;\nLAB_DONE:\n}" :: "l"(c), "r"(target) : "memory");
}
__device__ __forceinline__ void publish(uint32_t* c) { bulk_wait(); fence_async_global(); ctr_arrive(c); }

__device__ __forceinline__ void wg_fence() { asm volatile("wgmma.fence.sync.aligned;" ::: "memory"); }
__device__ __forceinline__ void wg_commit() { asm volatile("wgmma.commit_group.sync.aligned;" ::: "memory"); }
template <int N> __device__ __forceinline__ void wg_wait() { asm volatile("wgmma.wait_group.sync.aligned %0;" :: "n"(N) : "memory"); }
template <int N> __device__ __forceinline__ void reg_inc() { asm volatile("setmaxnreg.inc.sync.aligned.u32 %0;" :: "n"(N)); }
template <int N> __device__ __forceinline__ void reg_dec() { asm volatile("setmaxnreg.dec.sync.aligned.u32 %0;" :: "n"(N)); }
__host__ __device__ constexpr uint64_t desc_plain(uint32_t addr, uint32_t lbo, uint32_t sbo) {
    return (uint64_t)((addr & 0x3FFFF) >> 4) | ((uint64_t)(lbo >> 4) << 16) | ((uint64_t)(sbo >> 4) << 32);
}
__host__ __device__ constexpr uint64_t desc_sw128(uint32_t addr, uint32_t lbo, uint32_t sbo) { return desc_plain(addr, lbo, sbo) | (1ull << 62); }

__device__ __forceinline__ float ex2(float x) { float y; asm("ex2.approx.ftz.f32 %0, %1;" : "=f"(y) : "f"(x)); return y; }
__device__ __forceinline__ float rsq(float x) { float y; asm("rsqrt.approx.ftz.f32 %0, %1;" : "=f"(y) : "f"(x)); return y; }
__device__ __forceinline__ uint32_t pack_bf16(float lo, float hi) { uint32_t r; asm("cvt.rn.bf16x2.f32 %0, %1, %2;" : "=r"(r) : "f"(hi), "f"(lo)); return r; }
__device__ __forceinline__ uint32_t pack_f16(float lo, float hi) { uint32_t r; asm("cvt.rn.f16x2.f32 %0, %1, %2;" : "=r"(r) : "f"(hi), "f"(lo)); return r; }
__device__ __forceinline__ float bf_lo(uint32_t v) { return __uint_as_float(v << 16); }
__device__ __forceinline__ float bf_hi(uint32_t v) { return __uint_as_float(v & 0xFFFF0000u); }
__device__ __forceinline__ float bf_round(float x) { return __uint_as_float(pack_bf16(0.f, x)); }
__device__ __forceinline__ uint32_t badd2(uint32_t a, uint32_t b) { uint32_t r; asm("add.rn.bf16x2 %0, %1, %2;" : "=r"(r) : "r"(a), "r"(b)); return r; }
__device__ __forceinline__ void h2_unpack(uint32_t v, float& lo, float& hi) {
    asm("{.reg .f16 l, h; mov.b32 {l, h}, %2; cvt.f32.f16 %0, l; cvt.f32.f16 %1, h;}" : "=f"(lo), "=f"(hi) : "r"(v));
}
__device__ __forceinline__ uint32_t add_ln2(uint32_t x, float rstd, float nb) { return badd2(x, pack_bf16(fmaf(bf_lo(x), rstd, nb), fmaf(bf_hi(x), rstd, nb))); }
__device__ __forceinline__ float sel4(int t, float a0, float a1, float a2, float a3) {
    float r;
    asm("{\n.reg .pred p, q;\n.reg .f32 x, y;\nsetp.ne.u32 p, %1, 0;\nsetp.ne.u32 q, %2, 0;\nselp.f32 x, %4, %3, p;\nselp.f32 y, %6, %5, p;\nselp.f32 %0, y, x, q;\n}"
        : "=f"(r) : "r"(t & 1), "r"(t & 2), "f"(a0), "f"(a1), "f"(a2), "f"(a3));
    return r;
}
__device__ __forceinline__ float warp_sum(float v) {
    #pragma unroll
    for (int o = 16; o > 0; o >>= 1) v += __shfl_xor_sync(0xffffffffu, v, o);
    return v;
}
__device__ __forceinline__ float warp_max(float v) {
    #pragma unroll
    for (int o = 16; o > 0; o >>= 1) v = fmaxf(v, __shfl_xor_sync(0xffffffffu, v, o));
    return v;
}
__device__ __forceinline__ uint32_t redux_max(uint32_t v) { uint32_t r; asm volatile("redux.sync.max.u32 %0, %1, 0xffffffff;" : "=r"(r) : "r"(v)); return r; }
__device__ __forceinline__ uint32_t redux_min(uint32_t v) { uint32_t r; asm volatile("redux.sync.min.u32 %0, %1, 0xffffffff;" : "=r"(r) : "r"(v)); return r; }

#define TL(T, L, i)

__device__ __forceinline__ void wg_gemm_n128(float (&d)[64], uint64_t desca, uint64_t desc) {
    asm volatile("{\n.reg .pred p;\nsetp.ne.b32 p, 1, 0;\n"
        "wgmma.mma_async.sync.aligned.m64n128k16.f32.bf16.bf16 "
        "{%0,%1,%2,%3,%4,%5,%6,%7,%8,%9,%10,%11,%12,%13,%14,%15,%16,%17,%18,%19,%20,%21,%22,%23,%24,%25,%26,%27,%28,%29,%30,%31,%32,%33,%34,%35,%36,%37,%38,%39,%40,%41,%42,%43,%44,%45,%46,%47,%48,%49,%50,%51,%52,%53,%54,%55,%56,%57,%58,%59,%60,%61,%62,%63}, "
        "%64, %65, p, 1, 1, 0, 1;\n}\n"
        : "+f"(d[0]), "+f"(d[1]), "+f"(d[2]), "+f"(d[3]), "+f"(d[4]), "+f"(d[5]), "+f"(d[6]), "+f"(d[7]),
          "+f"(d[8]), "+f"(d[9]), "+f"(d[10]), "+f"(d[11]), "+f"(d[12]), "+f"(d[13]), "+f"(d[14]), "+f"(d[15]),
          "+f"(d[16]), "+f"(d[17]), "+f"(d[18]), "+f"(d[19]), "+f"(d[20]), "+f"(d[21]), "+f"(d[22]), "+f"(d[23]),
          "+f"(d[24]), "+f"(d[25]), "+f"(d[26]), "+f"(d[27]), "+f"(d[28]), "+f"(d[29]), "+f"(d[30]), "+f"(d[31]),
          "+f"(d[32]), "+f"(d[33]), "+f"(d[34]), "+f"(d[35]), "+f"(d[36]), "+f"(d[37]), "+f"(d[38]), "+f"(d[39]),
          "+f"(d[40]), "+f"(d[41]), "+f"(d[42]), "+f"(d[43]), "+f"(d[44]), "+f"(d[45]), "+f"(d[46]), "+f"(d[47]),
          "+f"(d[48]), "+f"(d[49]), "+f"(d[50]), "+f"(d[51]), "+f"(d[52]), "+f"(d[53]), "+f"(d[54]), "+f"(d[55]),
          "+f"(d[56]), "+f"(d[57]), "+f"(d[58]), "+f"(d[59]), "+f"(d[60]), "+f"(d[61]), "+f"(d[62]), "+f"(d[63])
        : "l"(desca), "l"(desc));
}
__device__ __forceinline__ void wg_gemm_n192(float (&d)[96], uint64_t desca, uint64_t desc) {
    asm volatile("{\n.reg .pred p;\nsetp.ne.b32 p, 1, 0;\n"
        "wgmma.mma_async.sync.aligned.m64n192k16.f32.bf16.bf16 "
        "{%0,%1,%2,%3,%4,%5,%6,%7,%8,%9,%10,%11,%12,%13,%14,%15,%16,%17,%18,%19,%20,%21,%22,%23,%24,%25,%26,%27,%28,%29,%30,%31,%32,%33,%34,%35,%36,%37,%38,%39,%40,%41,%42,%43,%44,%45,%46,%47,%48,%49,%50,%51,%52,%53,%54,%55,%56,%57,%58,%59,%60,%61,%62,%63,%64,%65,%66,%67,%68,%69,%70,%71,%72,%73,%74,%75,%76,%77,%78,%79,%80,%81,%82,%83,%84,%85,%86,%87,%88,%89,%90,%91,%92,%93,%94,%95}, "
        "%96, %97, p, 1, 1, 0, 1;\n}\n"
        : "+f"(d[0]), "+f"(d[1]), "+f"(d[2]), "+f"(d[3]), "+f"(d[4]), "+f"(d[5]), "+f"(d[6]), "+f"(d[7]),
          "+f"(d[8]), "+f"(d[9]), "+f"(d[10]), "+f"(d[11]), "+f"(d[12]), "+f"(d[13]), "+f"(d[14]), "+f"(d[15]),
          "+f"(d[16]), "+f"(d[17]), "+f"(d[18]), "+f"(d[19]), "+f"(d[20]), "+f"(d[21]), "+f"(d[22]), "+f"(d[23]),
          "+f"(d[24]), "+f"(d[25]), "+f"(d[26]), "+f"(d[27]), "+f"(d[28]), "+f"(d[29]), "+f"(d[30]), "+f"(d[31]),
          "+f"(d[32]), "+f"(d[33]), "+f"(d[34]), "+f"(d[35]), "+f"(d[36]), "+f"(d[37]), "+f"(d[38]), "+f"(d[39]),
          "+f"(d[40]), "+f"(d[41]), "+f"(d[42]), "+f"(d[43]), "+f"(d[44]), "+f"(d[45]), "+f"(d[46]), "+f"(d[47]),
          "+f"(d[48]), "+f"(d[49]), "+f"(d[50]), "+f"(d[51]), "+f"(d[52]), "+f"(d[53]), "+f"(d[54]), "+f"(d[55]),
          "+f"(d[56]), "+f"(d[57]), "+f"(d[58]), "+f"(d[59]), "+f"(d[60]), "+f"(d[61]), "+f"(d[62]), "+f"(d[63]),
          "+f"(d[64]), "+f"(d[65]), "+f"(d[66]), "+f"(d[67]), "+f"(d[68]), "+f"(d[69]), "+f"(d[70]), "+f"(d[71]),
          "+f"(d[72]), "+f"(d[73]), "+f"(d[74]), "+f"(d[75]), "+f"(d[76]), "+f"(d[77]), "+f"(d[78]), "+f"(d[79]),
          "+f"(d[80]), "+f"(d[81]), "+f"(d[82]), "+f"(d[83]), "+f"(d[84]), "+f"(d[85]), "+f"(d[86]), "+f"(d[87]),
          "+f"(d[88]), "+f"(d[89]), "+f"(d[90]), "+f"(d[91]), "+f"(d[92]), "+f"(d[93]), "+f"(d[94]), "+f"(d[95])
        : "l"(desca), "l"(desc));
}
__device__ __forceinline__ void wg_qk_init(uint32_t (&d)[32], uint64_t desca, uint64_t desc) {
    asm volatile("{\n.reg .pred p;\nsetp.ne.b32 p, 0, 0;\n"
        "wgmma.mma_async.sync.aligned.m64n128k16.f16.f16.f16 "
        "{%0,%1,%2,%3,%4,%5,%6,%7,%8,%9,%10,%11,%12,%13,%14,%15,%16,%17,%18,%19,%20,%21,%22,%23,%24,%25,%26,%27,%28,%29,%30,%31}, "
        "%32, %33, p, 1, 1, 0, 0;\n}\n"
        : "=r"(d[0]), "=r"(d[1]), "=r"(d[2]), "=r"(d[3]), "=r"(d[4]), "=r"(d[5]), "=r"(d[6]), "=r"(d[7]),
          "=r"(d[8]), "=r"(d[9]), "=r"(d[10]), "=r"(d[11]), "=r"(d[12]), "=r"(d[13]), "=r"(d[14]), "=r"(d[15]),
          "=r"(d[16]), "=r"(d[17]), "=r"(d[18]), "=r"(d[19]), "=r"(d[20]), "=r"(d[21]), "=r"(d[22]), "=r"(d[23]),
          "=r"(d[24]), "=r"(d[25]), "=r"(d[26]), "=r"(d[27]), "=r"(d[28]), "=r"(d[29]), "=r"(d[30]), "=r"(d[31])
        : "l"(desca), "l"(desc));
}
__device__ __forceinline__ void wg_qk_acc(uint32_t (&d)[32], uint64_t desca, uint64_t desc) {
    asm volatile("{\n.reg .pred p;\nsetp.ne.b32 p, 1, 0;\n"
        "wgmma.mma_async.sync.aligned.m64n128k16.f16.f16.f16 "
        "{%0,%1,%2,%3,%4,%5,%6,%7,%8,%9,%10,%11,%12,%13,%14,%15,%16,%17,%18,%19,%20,%21,%22,%23,%24,%25,%26,%27,%28,%29,%30,%31}, "
        "%32, %33, p, 1, 1, 0, 0;\n}\n"
        : "+r"(d[0]), "+r"(d[1]), "+r"(d[2]), "+r"(d[3]), "+r"(d[4]), "+r"(d[5]), "+r"(d[6]), "+r"(d[7]),
          "+r"(d[8]), "+r"(d[9]), "+r"(d[10]), "+r"(d[11]), "+r"(d[12]), "+r"(d[13]), "+r"(d[14]), "+r"(d[15]),
          "+r"(d[16]), "+r"(d[17]), "+r"(d[18]), "+r"(d[19]), "+r"(d[20]), "+r"(d[21]), "+r"(d[22]), "+r"(d[23]),
          "+r"(d[24]), "+r"(d[25]), "+r"(d[26]), "+r"(d[27]), "+r"(d[28]), "+r"(d[29]), "+r"(d[30]), "+r"(d[31])
        : "l"(desca), "l"(desc));
}
__device__ __forceinline__ void wg_pv_init(uint32_t (&d)[10], uint32_t a0, uint32_t a1, uint32_t a2, uint32_t a3, uint64_t desc) {
    asm volatile("{\n.reg .pred p;\nsetp.ne.b32 p, 0, 0;\n"
        "wgmma.mma_async.sync.aligned.m64n40k16.f16.f16.f16 "
        "{%0,%1,%2,%3,%4,%5,%6,%7,%8,%9}, "
        "{%10,%11,%12,%13}, %14, p, 1, 1, 1;\n}\n"
        : "=r"(d[0]), "=r"(d[1]), "=r"(d[2]), "=r"(d[3]), "=r"(d[4]), "=r"(d[5]), "=r"(d[6]), "=r"(d[7]),
          "=r"(d[8]), "=r"(d[9])
        : "r"(a0), "r"(a1), "r"(a2), "r"(a3), "l"(desc));
}
__device__ __forceinline__ void wg_pv_acc(uint32_t (&d)[10], uint32_t a0, uint32_t a1, uint32_t a2, uint32_t a3, uint64_t desc) {
    asm volatile("{\n.reg .pred p;\nsetp.ne.b32 p, 1, 0;\n"
        "wgmma.mma_async.sync.aligned.m64n40k16.f16.f16.f16 "
        "{%0,%1,%2,%3,%4,%5,%6,%7,%8,%9}, "
        "{%10,%11,%12,%13}, %14, p, 1, 1, 1;\n}\n"
        : "+r"(d[0]), "+r"(d[1]), "+r"(d[2]), "+r"(d[3]), "+r"(d[4]), "+r"(d[5]), "+r"(d[6]), "+r"(d[7]),
          "+r"(d[8]), "+r"(d[9])
        : "r"(a0), "r"(a1), "r"(a2), "r"(a3), "l"(desc));
}

constexpr int Q_ABYTES = 256 * 64 * 2, Q_STB = Q_ABYTES + 192 * 64 * 2;
constexpr int OFF_SIDE = 3 * Q_STB;
constexpr int OFF_XS = OFF_SIDE + 49152;
constexpr int OFF_CS = OFF_XS + 4096;
constexpr int OFF_RC = OFF_CS + 768;
constexpr int OFF_FIX = OFF_RC + 2048;
constexpr int A_WIN = KV_WIN + 4096;
constexpr int OFF_QA = 3 * A_WIN;
constexpr int OFF_FE = 147456;
constexpr int OFF_XT = 196608;
__host__ __device__ constexpr uint32_t o_stage(uint32_t s) { return s == 3 ? OFF_QA : s == 2 ? 0 : (s + 1) * A_WIN; }
__host__ __device__ constexpr uint32_t gu_piece(uint32_t i) { return i < 3 ? OFF_FE + i * 16384 : i < 6 ? (i - 1) * 16384 : (i - 6) * 16384; }
constexpr int OFF_FD = 5 * 16384;
constexpr int OFF_BAR = OFF_XT + 32768;
constexpr int OFF_PART = OFF_BAR + 384;
constexpr int OFF_RED = OFF_PART + 2048;
constexpr int OFF_RT = OFF_RED + 96;
constexpr int OFF_M = OFF_RT + 128;
constexpr int OFF_WR = OFF_M + 64;
constexpr int K_SMEM = OFF_WR + 264;
static_assert(K_SMEM <= 232448 && OFF_FIX + 768 <= OFF_BAR && OFF_QA + 32768 <= OFF_FE, "smem");
constexpr int M_SC = 0,
              M_IVS = 24,
              M_ISC = 32,
              M_OK = 40,
              M_WS = 48,
              M_RIDX = 60;
constexpr uint32_t BB = SB + OFF_BAR;
constexpr uint32_t B_QF = BB, B_EPI = BB + 24, B_RES2 = BB + 56, B_AF = BB + 64, B_RES = BB + 120, B_OF = BB + 128,
                   B_FE = BB + 160, B_FL = BB + 168, B_FD = BB + 184, B_PR = BB + 192, B_FW = B_PR, B_SW = BB + 216,
                   B_QE = BB + 224, B_QAF = BB + 248, B_OE = BB + 288, B_AE = BB + 320, B_KV0 = BB + 376;

constexpr int N_OST = 5, N_XST = 9, N_RT = 11, N_KV1 = 12, N_FW = 13, N_GD = 14, N_DD = 15;

struct Maps { CUtensorMap xa0, wqkv, xa, x0, x, out, w64, wo, r, g, u, d, xs; };

__device__ __forceinline__ float2 ln_coef(const uint4& s) {
    const float mean = __uint_as_float(s.x) * (1.f / D_);
    return make_float2(rsq(fmaxf(fmaf(-mean, mean, fmaf(__uint_as_float(s.y), 1.f / D_, LN_EPS)), LN_EPS)), mean);
}
__device__ __forceinline__ uint32_t order_bits(float r) { const uint32_t u = __float_as_uint(r); return (u & 0x80000000u) ? ~u : (u | 0x80000000u); }
__device__ __forceinline__ RouteOut route_result(int lane) {
    const float2 e = lds64f(SB + OFF_RT + (lane & 7) * 8);
    const uint32_t m = redux_max(__float_as_uint(e.x));
    RouteOut rt;
    rt.idx = redux_min(__float_as_uint(e.x) == m ? __float_as_uint(e.y) : 0x7FFFFFFFu);
    rt.r = __uint_as_float((m & 0x80000000u) ? m & 0x7FFFFFFFu : ~m);
    return rt;
}
__device__ __forceinline__ void route_stats(RouteOut& rt, const uint4& s) { const float2 r = ln_coef(s); rt.rstd = r.x; rt.mean = r.y; }

__device__ __forceinline__ void prep_work(const bf16* __restrict__ x0, const CUtensorMap* tmW, int t) {
    const int c = blockIdx.x, lane = t & 31, warp = warp_uniform(t >> 5);
    const int ki = c >> 4, n = c & 15;
    constexpr uint32_t red = SB + OFF_SIDE, xs = red + 4096;
    if (warp == 0) {
        mbar_expect_tx(B_PR, 32768);
        bulk_load(xs, x0 + (size_t)c * 16 * D_, 32768, B_PR);
        mbar_expect_tx(B_PR + 8, 16384);
        tma_load(xs + 32768, tmW, 2 * D_ + n * 64, ki * 128, B_PR + 8);
        tma_load(xs + 32768 + 8192, tmW, 2 * D_ + n * 64, ki * 128 + 64, B_PR + 8);
    }
    if (t < 32) g_sums[t >> 4][c * 16 + (t & 15)] = make_float4(0.f, 0.f, 0.f, 0.f);
    const uint4 sent = make_uint4(SENT, SENT, SENT, SENT);
    for (int i = t; i < 2 * NFC * 2; i += 96) reinterpret_cast<uint4*>(&g_ypart[0][0][0])[c * (2 * NFC * 2) + i] = sent;
    if (t < 2) reinterpret_cast<uint4*>(g_x2row)[c * 2 + t] = sent;
    else if (t < 8) reinterpret_cast<uint4*>(g_fix)[c * 6 + t - 2] = sent;
    else if (t < 12) (&g_kvc[0][0][0])[c * 4 + t - 8] = 0u;
    else if (t == 12 && c < 64) (&g_oc[0][0][0])[c] = 0u;
    else if (t == 13 && c < 16) (&g_xc[0][0])[c] = 0u;
    else if (t >= 14 && t < 16) reinterpret_cast<uint4*>(&g_xrow[0][0])[c * 2 + t - 14] = sent;
    mbar_wait(B_PR, 0);
    #pragma unroll 1
    for (int r = warp; r < 16; r += 3) {
        float s = 0.f, q = 0.f;
        #pragma unroll
        for (int i = 0; i < 4; i++) {
            const uint4 u = lds128(xs + r * 2048 + (lane + 32 * i) * 16);
            const float f[8] = {bf_lo(u.x), bf_hi(u.x), bf_lo(u.y), bf_hi(u.y), bf_lo(u.z), bf_hi(u.z), bf_lo(u.w), bf_hi(u.w)};
            #pragma unroll
            for (int e = 0; e < 8; e++) { s += f[e]; q = fmaf(f[e], f[e], q); }
        }
        #pragma unroll
        for (int o = 16; o > 0; o >>= 1) { s += __shfl_xor_sync(0xffffffffu, s, o); q += __shfl_xor_sync(0xffffffffu, q, o); }
        const float mean = s * (1.f / D_);
        const float var = fmaxf(q * (1.f / D_) - mean * mean, 0.f);
        if (lane == 0) g_rs0[c * 16 + r] = make_float2(rsqrtf(var + LN_EPS), mean);
    }
    named_sync(2, 96);
    if (warp == 0) {
        mbar_expect_tx(B_PR + 16, 32768);
        #pragma unroll
        for (int b = 0; b < 4; b++) tma_load(xs + b * 8192, tmW, (b >> 1) * D_ + n * 64, ki * 128 + (b & 1) * 64, B_PR + 16);
    }
    const int j = t & 7, rg = t >> 3;
    #pragma unroll 1
    for (int blk = 0; blk < 3; blk++) {
        const int type = blk == 0 ? 2 : blk - 1;
        const uint32_t wb = xs + type * 16384;
        if (blk < 2) mbar_wait(B_PR + 8 + 8 * blk, 0);
        float cs[8];
        uint32_t z2[4] = {0u, 0u, 0u, 0u};
        #pragma unroll
        for (int i = 0; i < 8; i++) cs[i] = 0.f;
        #pragma unroll 4
        for (int r = rg; r < 128; r += 12) {
            const uint4 u = lds128(wb + r * 128 + ((j ^ (r & 7)) << 4));
            cs[0] += bf_lo(u.x); cs[1] += bf_hi(u.x); cs[2] += bf_lo(u.y); cs[3] += bf_hi(u.y);
            cs[4] += bf_lo(u.z); cs[5] += bf_hi(u.z); cs[6] += bf_lo(u.w); cs[7] += bf_hi(u.w);
            asm("fma.rn.bf16x2 %0, %1, %1, %0;" : "+r"(z2[0]) : "r"(u.x));
            asm("fma.rn.bf16x2 %0, %1, %1, %0;" : "+r"(z2[1]) : "r"(u.y));
            asm("fma.rn.bf16x2 %0, %1, %1, %0;" : "+r"(z2[2]) : "r"(u.z));
            asm("fma.rn.bf16x2 %0, %1, %1, %0;" : "+r"(z2[3]) : "r"(u.w));
        }
        #pragma unroll
        for (int i = 0; i < 8; i++) { cs[i] += __shfl_xor_sync(0xffffffffu, cs[i], 8); cs[i] += __shfl_xor_sync(0xffffffffu, cs[i], 16); }
        float z = ((bf_lo(z2[0]) + bf_hi(z2[0])) + (bf_lo(z2[1]) + bf_hi(z2[1]))) + ((bf_lo(z2[2]) + bf_hi(z2[2])) + (bf_lo(z2[3]) + bf_hi(z2[3])));
        z += __shfl_xor_sync(0xffffffffu, z, 1); z += __shfl_xor_sync(0xffffffffu, z, 2);
        z += __shfl_xor_sync(0xffffffffu, z, 8); z += __shfl_xor_sync(0xffffffffu, z, 16);
        if (lane < 8) {
            #pragma unroll
            for (int i = 0; i < 8; i++) stsf(red + (warp * 200 + type * 64 + j * 8 + i) * 4, cs[i]);
            if ((lane & 3) == 0) stsf(red + (warp * 200 + 192 + type * 2 + (lane >> 2)) * 4, z);
        }
    }
    named_sync(2, 96);
    for (int i = t; i < 198; i += 96) {
        const float v = ldsf(red + i * 4) + ldsf(red + (200 + i) * 4) + ldsf(red + (400 + i) * 4);
        if (i < 192) g_csum[ki * (3 * D_) + (i >> 6) * D_ + n * 64 + (i & 63)] = v;
        else g_wsq[ki * 96 + ((i - 192) >> 1) * 32 + n * 2 + (i & 1)] = v;
    }
    named_sync(2, 96);
    if (warp == 0) { ctr_arrive(&g_c0); ctr_wait(&g_c0, 128); }
    named_sync(2, 96);
}

__device__ __forceinline__ float pow2_inv(float b) {
    const int e = min(max((int)(__float_as_uint(b) >> 23) + 1, 20), 234);
    return __uint_as_float((uint32_t)(254 - e) << 23);
}
__device__ __forceinline__ void epi_inputs(int L) {
    const int t = tid_now() - 288, mt = cta_now() >> 4, nt = cta_now() & 15;
    float p[2][8], r0[3], r1[3];
    #pragma unroll
    for (int k = 0; k < 2; k++)
        #pragma unroll
        for (int q = 0; q < 8; q++) p[k][q] = __ldcg(g_csum + q * (3 * D_) + ((t + 96 * k) >> 6) * D_ + nt * 64 + ((t + 96 * k) & 63));
    #pragma unroll
    for (int k = 0; k < 3; k++) {
        const int row = mt * 256 + min(t + 96 * k, 255);
        const float2 s = __ldcg(L == 0 ? &g_rs0[row] : reinterpret_cast<const float2*>(&g_sums[0][row]));
        r0[k] = s.x; r1[k] = s.y;
    }
    #pragma unroll
    for (int k = 0; k < 2; k++) stsf(SB + OFF_CS + (t + 96 * k) * 4, ((p[k][0] + p[k][1]) + (p[k][2] + p[k][3])) + ((p[k][4] + p[k][5]) + (p[k][6] + p[k][7])));
    #pragma unroll
    for (int k = 0; k < 3; k++) {
        if (L != 0) {
            const float mean = r0[k] * (1.f / D_);
            const float var = fmaxf(r1[k] * (1.f / D_) - mean * mean, 0.f);
            const float a = 1.f + rsqrtf(var + LN_EPS);
            r0[k] = a * rsqrtf(a * a * var + LN_EPS); r1[k] = mean;
        }
        if (t + 96 * k < 256) sts64f(SB + OFF_RC + (t + 96 * k) * 8, r0[k], r1[k]);
    }
    if (L == 0 && t < 32) {
        float z = 0.f;
        if (t < 6) {
            #pragma unroll
            for (int q = 0; q < 8; q++) z += __ldcg(g_wsq + q * 96 + (t >> 1) * 32 + nt * 2 + (t & 1));
        }
        const float b = sqrtf(z) * (t < 2 ? 34.f * QSCALE : 34.f);
        const float sc = t < 4 ? fminf(pow2_inv(b) * 32768.f, 1.f) : pow2_inv(b);
        const float bk = __shfl_down_sync(0xffffffffu, b, 2), sk = __shfl_down_sync(0xffffffffu, sc, 2);
        if (t < 6) stsf(SB + OFF_M + M_SC + t * 4, t < 2 ? sc * QSCALE : sc);
        if (t < 2) { stsf(SB + OFF_M + M_ISC + t * 4, 1.f / (sc * sk)); sts32(SB + OFF_M + M_OK + t * 4, sc == 1.f && sk == 1.f && b * bk < 60000.f); }
        if (t == 4 || t == 5) stsf(SB + OFF_M + M_IVS + (t - 4) * 4, 1.f / sc);
    }
}

__device__ __forceinline__ int ypos_col(int p) { return (p >> 7) * 128 + ((p >> 1) & 7) * 16 + (p & 1) * 8 + ((p >> 4) & 7); }

#define YD 200
template <int NT>
__device__ __forceinline__ float ffn_finish(int L, const RouteOut& rt, int t, uint32_t red, int bid) {
    constexpr int NL = (2 * NFC + NT - 1) / NT;
    const int c = cta_now(), col = ypos_col(c * 8 + (t & 7));
    const uint32_t* src = &g_ypart[L][t >> 1][c * 8 + (t & 1) * 4];
    uint32_t n = 0, xp;
    uint4 v[NL];
    bool wait;
    if (NT == 256 && YD) __nanosleep(YD);
    do {
        wait = false;
        xp = ld_relaxed(&g_xrow[L][(col >> 5) * 16 + (col & 6) * 2 + ((col >> 3) & 3)]);
        #pragma unroll
        for (int i = 0; i < NL; i++) v[i] = t + NT * i < 2 * NFC ? ld_relaxed4(src + i * (NT / 2) * D_) : make_uint4(0u, 0u, 0u, 0u);
        #pragma unroll
        for (int i = 0; i < NL; i++) wait = wait || has_sent(v[i]);
    } while ((wait || xp == SENT) && ++n < SPIN_MAX);
    spin_check(n);
    __syncwarp();
    float a[4] = {0.f, 0.f, 0.f, 0.f};
    #pragma unroll
    for (int i = 0; i < NL; i++) { a[0] += __uint_as_float(v[i].x); a[1] += __uint_as_float(v[i].y); a[2] += __uint_as_float(v[i].z); a[3] += __uint_as_float(v[i].w); }
    const bool b1 = t & 2, b2 = t & 4;
    a[0] = (b1 ? a[1] : a[0]) + __shfl_xor_sync(0xffffffffu, b1 ? a[0] : a[1], 2);
    a[2] = (b1 ? a[3] : a[2]) + __shfl_xor_sync(0xffffffffu, b1 ? a[2] : a[3], 2);
    a[0] = (b2 ? a[2] : a[0]) + __shfl_xor_sync(0xffffffffu, b2 ? a[0] : a[2], 4);
    a[0] += __shfl_xor_sync(0xffffffffu, a[0], 8); a[0] += __shfl_xor_sync(0xffffffffu, a[0], 16);
    if ((t & 31) < 8) stsf(red + (t >> 5) * 32 + (t & 1) * 16 + (t & 6) * 2, a[0]);
    const float xv = (col & 1) ? bf_hi(xp) : bf_lo(xp);
    const float rsel = bf_round(__fdividef(1.f, 1.f + __expf(-bf_round(rt.r)))), xn = bf_round((xv - rt.mean) * rt.rstd);
    named_sync(bid, NT);
    float y = 0.f;
    #pragma unroll
    for (int i = 0; i < NT / 32; i++) y += ldsf(red + i * 32 + (t & 7) * 4);
    return bf_round(xv + bf_round(xn + bf_round(bf_round(y) * rsel)));
}

__device__ __forceinline__ void routed_qkv(int ridx) {
    const int t = tid_now() - 288, c = cta_now(), lane = t & 31, warp = t >> 5;
    constexpr uint32_t red = SB + OFF_RED;
    {
        uint4 v[3];
        uint32_t n = 0;
        do {
            v[0] = ld_relaxed4(g_x2row + t * 4); v[1] = ld_relaxed4(g_x2row + (t + 96) * 4);
            v[2] = t < 64 ? ld_relaxed4(g_x2row + (t + 192) * 4) : make_uint4(0u, 0u, 0u, 0u);
        } while ((has_sent(v[0]) || has_sent(v[1]) || has_sent(v[2])) && ++n < SPIN_MAX);
        spin_check(n);
        __syncwarp();
        TL(288, 0, 21);
        float f[12];
        float s = 0.f;
        #pragma unroll
        for (int i = 0; i < 3; i++) { f[4*i] = __uint_as_float(v[i].x); f[4*i+1] = __uint_as_float(v[i].y); f[4*i+2] = __uint_as_float(v[i].z); f[4*i+3] = __uint_as_float(v[i].w); }
        #pragma unroll
        for (int i = 0; i < 12; i++) s += f[i];
        s = warp_sum(s);
        if (lane == 0) stsf(red + warp * 4, s);
        named_sync(2, 96);
        const float mean = (ldsf(red) + ldsf(red + 4) + ldsf(red + 8)) * (1.f / D_);
        float q = 0.f;
        #pragma unroll
        for (int i = 0; i < 12; i++) { f[i] -= mean; if (i < 8 || t < 64) q = fmaf(f[i], f[i], q); }
        q = warp_sum(q);
        if (lane == 0) stsf(red + 16 + warp * 4, q);
        named_sync(2, 96);
        const float rstd = rsqrtf((ldsf(red + 16) + ldsf(red + 20) + ldsf(red + 24)) * (1.f / D_) + LN_EPS);
        #pragma unroll
        for (int i = 0; i < 3; i++)
            if (i < 2 || t < 64) sts128(SB + OFF_XS + (t + 96 * i) * 16, make_uint4(pack_bf16(0.f, f[4*i] * rstd), pack_bf16(0.f, f[4*i+1] * rstd), pack_bf16(0.f, f[4*i+2] * rstd), pack_bf16(0.f, f[4*i+3] * rstd)));
    }
    named_sync(2, 96);
    TL(288, 0, 22);
    mbar_wait(B_SW, 0);
    TL(288, 0, 23);
    float a[8];
    #pragma unroll
    for (int i = 0; i < 8; i++) a[i] = 0.f;
    const uint32_t wa = SB + OFF_SIDE + t * 16, xa = SB + OFF_XS + (t / 3) * 4;
    #pragma unroll 4
    for (int i = 0; i < 32; i++) {
        const uint4 u = lds128(wa + i * 1536);
        const float xv = ldsf(xa + i * 128);
        a[0] = fmaf(xv, bf_lo(u.x), a[0]); a[1] = fmaf(xv, bf_hi(u.x), a[1]); a[2] = fmaf(xv, bf_lo(u.y), a[2]); a[3] = fmaf(xv, bf_hi(u.y), a[3]);
        a[4] = fmaf(xv, bf_lo(u.z), a[4]); a[5] = fmaf(xv, bf_hi(u.z), a[5]); a[6] = fmaf(xv, bf_lo(u.w), a[6]); a[7] = fmaf(xv, bf_hi(u.w), a[7]);
    }
    named_sync(2, 96);
    TL(288, 0, 41);
    sts128(SB + OFF_SIDE + t * 32, make_uint4(__float_as_uint(a[0]), __float_as_uint(a[1]), __float_as_uint(a[2]), __float_as_uint(a[3])));
    sts128(SB + OFF_SIDE + t * 32 + 16, make_uint4(__float_as_uint(a[4]), __float_as_uint(a[5]), __float_as_uint(a[6]), __float_as_uint(a[7])));
    named_sync(2, 96);
    {
        float y = 0.f;
        #pragma unroll
        for (int i = 0; i < 8; i++) y += ldsf(SB + OFF_SIDE + ((t & 3) * 8 + i) * 96 + (t >> 2) * 4);
        y += __shfl_xor_sync(0xffffffffu, y, 1); y += __shfl_xor_sync(0xffffffffu, y, 2);
        if ((t & 3) == 0) st_relaxed(g_fix + c * 24 + (t >> 2), not_sent(y));
    }
    if ((ridx >> 8) == (c >> 4) && t < 24) {
        const uint32_t* src = g_fix + (t >> 3) * D_ + (c & 15) * 64 + (t & 7) * 8;
        uint4 a, b;
        uint32_t n = 0;
        do { a = ld_relaxed4(src); b = ld_relaxed4(src + 4); } while ((has_sent(a) || has_sent(b)) && ++n < SPIN_MAX);
        spin_check(n);
        const int hh = t >> 2, ch = t & 3, lr = ridx & 255;
        const float hs = ldsf(SB + OFF_M + M_SC + hh * 4);
        sts128(SB + OFF_FIX + t * 16, make_uint4(pack_f16(__uint_as_float(a.x) * hs, __uint_as_float(a.y) * hs), pack_f16(__uint_as_float(a.z) * hs, __uint_as_float(a.w) * hs),
                                                 pack_f16(__uint_as_float(b.x) * hs, __uint_as_float(b.y) * hs), pack_f16(__uint_as_float(b.z) * hs, __uint_as_float(b.w) * hs)));
        sts32(SB + OFF_FIX + 512 + t * 4, SB + (hh < 2 ? OFF_QA + hh * 16384 + (lr >> 6) * 4096 + ch * 1024 + (lr & 63) * 16
                                                        : (hh & 1) * OFF_FE + (hh >> 2) * 16384 + ch * 4096 + lr * 16));
    }
    __syncwarp();
}

__device__ __forceinline__ void residual_prep() {
    const int t = tid_now() - 288, c = cta_now(), row0 = (c >> 4) * 256 + (c & 1) * 128, col0 = ((c & 15) >> 1) * 128;
    for (int i = t; i < 128; i += 96) {
        const float2 s = __ldcg(reinterpret_cast<const float2*>(&g_sums[0][row0 + i]));
        const float mean = s.x * (1.f / D_);
        const float rstd = rsqrtf(fmaxf(s.y * (1.f / D_) - mean * mean, 0.f) + LN_EPS);
        sts64f(SB + OFF_PART + i * 8, rstd, -mean * rstd);
    }
    named_sync(2, 96);
    #pragma unroll 2
    for (int i = t; i < 2048; i += 96) {
        const uint4 u = lds128(SB + OFF_XT + i * 16);
        const float2 r = lds64f(SB + OFF_PART + ((i >> 3) & 127) * 8);
        sts128(SB + OFF_XT + i * 16, make_uint4(add_ln2(u.x, r.x, r.y), add_ln2(u.y, r.x, r.y), add_ln2(u.z, r.x, r.y), add_ln2(u.w, r.x, r.y)));
    }
    const uint32_t lr = lds32(SB + OFF_M + M_RIDX) - row0;
    if (lr < 128u) {
        named_sync(2, 96);
        if (t < 16) {
            const uint4 a = ld_relaxed4(g_x2row + col0 + t * 8), b = ld_relaxed4(g_x2row + col0 + t * 8 + 4);
            sts128(SB + OFF_XT + (t >> 3) * 16384 + lr * 128 + (((t & 7) ^ (lr & 7)) << 4),
                   make_uint4(__byte_perm(a.x, a.y, 0x7632), __byte_perm(a.z, a.w, 0x7632), __byte_perm(b.x, b.y, 0x7632), __byte_perm(b.z, b.w, 0x7632)));
        }
    }
    __syncwarp();
}

#define XPF 1
#define XP0 2
#define XP1 7
#define FW_NS 1000
__device__ __forceinline__ void ffn_load(const Maps& mp, int i, uint32_t dst, uint32_t bar) {
    if (i < 8) tma_load(dst, (i & 1) ? &mp.u : &mp.g, blockIdx.x * 32, (i >> 1) * 256, bar);
    else tma_load3(dst, &mp.d, 0, blockIdx.x * 32, (i - 8) * 4, bar);
}
__device__ __forceinline__ void side_role(const Maps& mp, const bf16* __restrict__ x0, const bf16* __restrict__ wo, const bf16* __restrict__ w_r) {
    prep_work(x0, &mp.w64, threadIdx.x - 288);
    epi_inputs(0);
    #pragma unroll 1
    for (int L = 0; L < 2; L++) {
        const int t = tid_now() - 288, lane = t & 31, sw = warp_uniform(t >> 5);
        const int c = blockIdx.x, mt = c >> 4, nt = c & 15;
        named_sync(2, 96);
        if (t == 0) mbar_arrive(B_EPI);
        TL(288, L, 5);
        if (L == 0) {
            float ws = 0.f;
            for (int i = t; i < D_ / 8; i += 96) {
                const uint4 v = reinterpret_cast<const uint4*>(w_r)[i];
                ws += ((bf_lo(v.x) + bf_hi(v.x)) + (bf_lo(v.y) + bf_hi(v.y))) + ((bf_lo(v.z) + bf_hi(v.z)) + (bf_lo(v.w) + bf_hi(v.w)));
            }
            ws = warp_sum(ws);
            if (lane == 0) stsf(SB + OFF_M + M_WS + sw * 4, ws);
            if (t < 66) sts32(SB + OFF_WR + t * 4, t < 64 ? reinterpret_cast<const uint32_t*>(w_r)[(nt >> 1) * 64 + (t >> 3) * 8 + (t & 1) * 4 + ((t >> 1) & 3)] : 0x3F803F80u);
        }
        __syncwarp();
        if (sw == 0) {
            char* kv = g_kv + (size_t)(nt * 16 + mt) * KV_WIN;
            mbar_wait(B_KV0, L);
            bulk_store(kv, SB, KV_WIN);
            bulk_commit();
            publish(&g_kvc[L][nt * 2][mt]);
            TL(288, L, 6);
            named_sync(N_KV1, 64);
            bulk_store(kv + 8 * KV_WIN, SB + OFF_FE, KV_WIN);
            bulk_commit();
            publish(&g_kvc[L][nt * 2 + 1][mt]);
        }
        if (sw < 2) {
            #pragma unroll 1
            for (int p = 0; p < 2; p++) {
                named_sync(N_OST + 2 * p + sw, 160);
                bulk_store(g_o + (size_t)(((mt * 2 + sw) * 2 + p) * 16 + nt) * 8192, SB + OFF_QA + p * 16384 + sw * 8192, 8192);
                bulk_commit();
                TL(p ? -1 : 288, L, 30); TL(p ? 288 : -1, L, 31);
                if (p == 1) { bulk_wait_read(); mbar_arrive_elect(B_QAF); }
                publish(&g_oc[L][mt * 2 + sw][p]);
            }
        } else {
            named_sync(N_FW, 64);
            mbar_expect_tx(B_RES, 32768);
            #pragma unroll
            for (int i = 0; i < 4; i++) tma_load(SB + OFF_XT + i * 8192, L == 0 ? &mp.x0 : &mp.x, (nt >> 1) * 128 + (i >> 1) * 64, mt * 256 + (nt & 1) * 128 + (i & 1) * 64, B_RES);
            l2_prefetch(reinterpret_cast<const char*>(wo) + (size_t)c * 16384, 16384);
            if (c < NFC) {
                #pragma unroll 1
                for (int r = 0; r < 4; r++) {
                    __nanosleep(FW_NS);
                    if (r > 0) mbar_wait(B_FW, (r + L) & 1);
                    const uint32_t bar = r < 3 ? B_FW : B_FE;
                    mbar_expect_tx(bar, 3 * 16384);
                    #pragma unroll 1
                    for (int b = 0; b < 3; b++) ffn_load(mp, 9 - 3 * r + b, SB + OFF_FE + b * 16384, bar);
                }
            }
        }
        named_sync(2, 96);
        if (sw == 2) {
            l2_prefetch(&g_ypart[L][0][0] + c * (NFC * 8), NFC * 32);
            l2_prefetch(&g_sums[L][c * 16], 256);
            l2_prefetch(c < 16 ? &g_xrow[L][c * 32] : c < 48 ? &g_x2row[(c - 16) * 32] : c < 56 ? &g_kvc[1][(c - 48) * 4][0] : c == 56 ? &g_oc[1][0][0] : &g_xc[0][0], c < 57 ? 128 : 64);
            l2_prefetch(&g_fix[c * 24], 96);
        }
        mbar_wait(B_RES, L);
        if (L == 1) { residual_prep(); named_sync(2, 96); }
        if (t == 0) mbar_arrive(B_RES2);
        __syncwarp();
        if (sw < 2) {
            named_sync(N_XST + sw, 160);
            const int row0 = mt * 256 + (nt & 1) * 128 + sw * 64, col0 = (nt >> 1) * 128;
            #pragma unroll 1
            for (int h = 0; h < 8; h++) {
                if (L == 0) bulk_wait_n<XP0>(); else bulk_wait_n<XP1>();
                tma_store(L == 0 ? &mp.xs : &mp.out, SB + OFF_XT + (h & 1) * 16384 + sw * 8192 + (h >> 1) * 2048, col0 + (h & 1) * 64, row0 + (h >> 1) * 16);
                bulk_commit();
            }
            publish(&g_xc[L][mt]);
            TL(288, L, 14);
        }
        if (L == 0) {
            __syncwarp();
            named_sync(N_RT, 128);
            RouteOut rt = route_result(lane);
            route_stats(rt, ld_relaxed4(&g_sums[0][rt.idx]));
            if (t == 0) { sts32(SB + OFF_M + M_RIDX, rt.idx); if (c == 0) g_c0 = 0u; }
            epi_inputs(1);
            const float v = ffn_finish<96>(0, rt, t, SB + OFF_RED, 2);
            TL(288, L, 20);
            if (t < 8) st_relaxed(g_x2row + ypos_col(c * 8 + t), not_sent(v));
            routed_qkv(rt.idx);
        }
    }
}

template <int HH>
__device__ __forceinline__ void qkv_epi_head(const float (&acc0)[96], const float (&acc1)[96], const float (&cf)[4], const float (&nm)[4], uint32_t dst, int t) {
    float2 c2[4];
    #pragma unroll
    for (int jj = 0; jj < 4; jj++) c2[jj] = lds64f(SB + OFF_CS + (HH * 32 + jj * 8) * 4 + t * 8);
    const float hs = ldsf(SB + OFF_M + M_SC + HH * 4);
    #pragma unroll
    for (int i = 0; i < 4; i++) {
        const float* a = (i >> 1) ? acc1 : acc0;
        const float sc = cf[i] * hs;
        uint32_t pk[4];
        #pragma unroll
        for (int jj = 0; jj < 4; jj++)
            pk[jj] = pack_f16(fmaf(nm[i], c2[jj].x, a[4 * (4 * HH + jj) + 2 * (i & 1)]) * sc, fmaf(nm[i], c2[jj].y, a[4 * (4 * HH + jj) + 2 * (i & 1) + 1]) * sc);
        stsm4(dst + (i >> 1) * (HH < 2 ? 4096 : 1024) + (i & 1) * 128, pk[0], pk[1], pk[2], pk[3]);
    }
}
__device__ __forceinline__ void qkv_patch(int lane, uint32_t mask) {
    const uint4 v = lds128(SB + OFF_FIX + lane * 16);
    const uint32_t dst = lds32(SB + OFF_FIX + 512 + lane * 4);
    __syncwarp();
    asm volatile("{\n.reg .pred q;\nsetp.ne.u32 q, %5, 0;\n@q st.shared.v4.b32 [%0], {%1, %2, %3, %4};\n}"
                 :: "r"(dst), "r"(v.x), "r"(v.y), "r"(v.z), "r"(v.w), "r"((mask >> lane) & 1) : "memory");
}

__device__ __forceinline__ void qkv_phase(int L, int wg) {
    const uint32_t rb = L * 32;
    float acc0[96], acc1[96];
    #pragma unroll
    for (int i = 0; i < 96; i++) { acc0[i] = 0.f; acc1[i] = 0.f; }
    const bool leader = (tid_now() & 127) == 0;
    uint32_t st = 0, ph = 0;
    #pragma unroll 1
    for (int k = 0; k < 16; k++) {
        mbar_wait(rb + B_QF + 8 * st, ph);
        TL(k == 0 ? 0 : -1, L, 1);
        const uint64_t da = desc_sw128(SB, 16, 1024) + ((st * Q_STB + wg * 16384) >> 4);
        const uint64_t db = desc_sw128(SB + Q_ABYTES, 8192, 1024) + ((st * Q_STB) >> 4);
        wg_fence();
        #pragma unroll
        for (int kk = 0; kk < 4; kk++) {
            wg_gemm_n192(acc0, da + kk * 2, db + kk * 128);
            wg_gemm_n192(acc1, da + (8192 >> 4) + kk * 2, db + kk * 128);
        }
        wg_commit();
        if (k > 0) {
            wg_wait<1>();
            if (leader) mbar_arrive(rb + B_QE + 8 * (st == 0 ? 2 : st - 1));
        }
        if (++st == 3) { st = 0; ph ^= 1; }
    }
    const int tid = tid_now(), lane = tid & 31, w = (tid >> 5) & 3, g = lane >> 2, t = lane & 3;
    mbar_wait(B_EPI, L);
    float cf[4], nm[4];
    #pragma unroll
    for (int i = 0; i < 4; i++) { const float2 r = lds64f(SB + OFF_RC + (wg * 128 + w * 16 + g + (i >> 1) * 64 + (i & 1) * 8) * 8); cf[i] = r.x; nm[i] = -r.y; }
    const int d = (int)lds32(SB + OFF_M + M_RIDX) - (cta_now() >> 4) * 256;
    const uint32_t own = L == 1 && (d >> 7) == wg && ((d >> 4) & 3) == w ? 0xFFFFFFu : 0u;
    wg_wait<0>();
    TL(0, L, 2);
    TL(128, L, 40);
    named_sync(1, 256);
    const uint32_t dk = SB + wg * 2048 + (lane >> 3) * 4096 + (w * 16 + (lane & 7)) * 16;
    const uint32_t dq = SB + OFF_QA + wg * 8192 + (lane >> 3) * 1024 + (w * 16 + (lane & 7)) * 16;
    qkv_epi_head<2>(acc0, acc1, cf, nm, dk, t);
    qkv_epi_head<4>(acc0, acc1, cf, nm, dk + 16384, t);
    qkv_patch(lane, own & 0x0F0F00u);
    fence_async_smem();
    __syncwarp();
    mbar_arrive_elect(B_KV0);
    TL(0, L, 4);
    qkv_epi_head<3>(acc0, acc1, cf, nm, dk + OFF_FE, t);
    qkv_epi_head<5>(acc0, acc1, cf, nm, dk + OFF_FE + 16384, t);
    qkv_epi_head<0>(acc0, acc1, cf, nm, dq, t);
    qkv_epi_head<1>(acc0, acc1, cf, nm, dq + 16384, t);
    qkv_patch(lane, own & 0xF0F0FFu);
    #pragma unroll
    for (int s = 0; s < 3; s++) sts128(SB + s * A_WIN + KV_WIN + tid * 16, make_uint4(0x3C003C00u, 0x3C003C00u, 0x3C003C00u, 0x3C003C00u));
    fence_async_smem();
    named_sync(1, 256);
    if (tid == 0) mbar_arrive(rb + B_AF);
    TL(0, L, 3);
}

#define TIE 0
struct Unit {
    uint32_t o[10];
    uint32_t bz[2];
    uint32_t sc[2];
    uint32_t ch[2];
};
constexpr uint32_t CH_OK = 0x38003800u;
__device__ __forceinline__ uint32_t hmax2(uint32_t a, uint32_t b) { uint32_t r; asm("max.f16x2 %0, %1, %2;" : "=r"(r) : "r"(a), "r"(b)); return r; }
__device__ __forceinline__ uint32_t hadd2(uint32_t a, uint32_t b) { uint32_t r; asm("add.rn.f16x2 %0, %1, %2;" : "=r"(r) : "r"(a), "r"(b)); return r; }
__device__ __forceinline__ uint32_t hsub2(uint32_t a, uint32_t b) { uint32_t r; asm("sub.rn.f16x2 %0, %1, %2;" : "=r"(r) : "r"(a), "r"(b)); return r; }
__device__ __forceinline__ uint32_t hfma2(uint32_t a, uint32_t b, uint32_t c) { uint32_t r; asm("fma.rn.f16x2 %0, %1, %2, %3;" : "=r"(r) : "r"(a), "r"(b), "r"(c)); return r; }
__device__ __forceinline__ uint32_t exp2_h2(uint32_t s, uint32_t bz, uint32_t& ch) {
    uint32_t z, w, d;
    asm("fma.rn.relu.f16x2 %0, %1, %2, %3;" : "=r"(z) : "r"(s), "r"(0x00400040u), "r"(bz));
    asm("lop3.b32 %0, %1, 0x003F003F, %0, 0xC2;" : "+r"(ch) : "r"(z));
    asm("fma.rn.f16x2 %0, %1, %2, %3;" : "=r"(w) : "r"(ch), "r"(0x30A630A6u), "r"(0xACCCACCCu));
    asm("{.reg .b32 n; neg.f16x2 n, %1; fma.rn.relu.f16x2 %0, n, %1, %2;}" : "=r"(d) : "r"(w), "r"(0x00580058u));
    return (z << 4) - d;
}
__device__ __forceinline__ void exp_tile(uint32_t (&p)[32], const uint32_t (&s)[32], Unit& u) {
    #pragma unroll
    for (int i = 0; i < 32; i++) p[i] = exp2_h2(s[i], u.bz[i & 1], u.ch[i & 1]);
}
__device__ __forceinline__ void issue_qk(uint32_t (&s)[32], uint64_t dq, uint64_t dk) {
    wg_qk_init(s, dq, dk); wg_qk_acc(s, dq + (2048 >> 4), dk + (8192 >> 4));
    wg_commit();
}
template <bool INIT>
__device__ __forceinline__ void issue_pv(uint32_t (&h)[10], const uint32_t (&p)[32], uint64_t dv) {
    #pragma unroll
    for (int k = 0; k < 8; k++) {
        if (INIT && k == 0) wg_pv_init(h, p[0], p[1], p[2], p[3], dv);
        else wg_pv_acc(h, p[4*k], p[4*k+1], p[4*k+2], p[4*k+3], dv + k * 16);
    }
    wg_commit();
}
__device__ __forceinline__ void unit_init(Unit& u, const uint32_t (&s)[32]) {
    uint32_t m0 = s[0], m1 = s[1];
    #pragma unroll
    for (int i = 1; i < 16; i++) { m0 = hmax2(m0, s[2 * i]); m1 = hmax2(m1, s[2 * i + 1]); }
    uint32_t m = hmax2(__byte_perm(m0, m1, 0x5410), __byte_perm(m0, m1, 0x7632));
    m = hmax2(m, __shfl_xor_sync(0xffffffffu, m, 1)); m = hmax2(m, __shfl_xor_sync(0xffffffffu, m, 2));
    float f0, f1; h2_unpack(m, f0, f1);
    u.ch[0] = fabsf(f0) < 1000.f ? CH_OK : 0u; u.ch[1] = fabsf(f1) < 1000.f ? CH_OK : 0u;
    f0 = (18.f - ceilf(f0)) * 3.814697265625e-06f; f1 = (18.f - ceilf(f1)) * 3.814697265625e-06f;
    u.bz[0] = pack_f16(f0, f0); u.bz[1] = pack_f16(f1, f1);
    u.sc[0] = u.sc[1] = 0x3C003C00u;
    #pragma unroll
    for (int i = 0; i < 10; i++) u.o[i] = 0u;
}
template <bool MORE>
__device__ __forceinline__ void unit_flush(Unit& u, const uint32_t (&h)[10]) {
    #pragma unroll
    for (int i = 0; i < 10; i++) u.o[i] = hfma2(u.o[i], u.sc[i & 1], h[i]);
    if (MORE) {
        #pragma unroll
        for (int r = 0; r < 2; r++) {
            const uint32_t ex = u.o[8 + r] & 0x7C007C00u;
            u.sc[r] = 0x84008400u - ex;
            u.bz[r] = hsub2(hadd2(u.bz[r], 0x04800480u), ex >> 4);
        }
    }
}
__device__ __forceinline__ uint32_t unit_store(const Unit& u, uint32_t dst, float ivs, bool head_ok, int lane) {
    uint32_t bad = 0;
    #pragma unroll
    for (int h = 0; h < 2; h++) {
        const uint32_t l = u.o[8 + h] & 0xFFFFu;
        uint32_t b = __ballot_sync(0xffffffffu, !head_ok || (u.ch[h] & CH_OK) != CH_OK || l >= 0x7C00u || l < 0x4000u);
        b |= b >> 1; b |= b >> 2;
        float lf, unused; h2_unpack(l, lf, unused);
        const float inv = __fdividef(ivs, lf);
        uint32_t pk[4];
        #pragma unroll
        for (int j = 0; j < 4; j++) { float x, y; h2_unpack(u.o[2 * j + h], x, y); pk[j] = pack_bf16(x * inv, y * inv); }
        const bool mine = (b >> (4 * (lane & 7))) & 1;
        stsm4(mine ? SB + OFF_RT : dst + h * 128, pk[0], pk[1], pk[2], pk[3]);
        bad |= (__ballot_sync(0xffffffffu, mine) & 0xFFu) << (8 * h);
    }
    return bad;
}
__device__ __noinline__ void exact_rows(int L, int pass, int wg, uint32_t bad) {
    const int tid = tid_now() & 127, lane = tid & 31, w = tid >> 5;
    const int head = (cta_now() & 15) * 2 + pass;
    const uint32_t scr = SB + OFF_PART + wg * 1024;
    if (lane == 0) sts32(scr + w * 4, bad);
    if (tid < 8) ctr_wait(&g_kvc[L][head][tid], 1);
    named_sync(3 + wg, 128);
    const float isc = ldsf(SB + OFF_M + M_ISC + pass * 4), ivs = ldsf(SB + OFF_M + M_IVS + pass * 4);
    const char* kv = g_kv + (size_t)head * 8 * KV_WIN + tid * 16;
    #pragma unroll 1
    for (int ww = 0; ww < 4; ww++) {
        uint32_t m = lds32(scr + ww * 4);
        #pragma unroll 1
        while (m) {
            const int bit = __ffs(m) - 1;
            m &= m - 1;
            const uint32_t qa = SB + OFF_QA + pass * 16384 + (wg * 2 + (bit >> 4)) * 4096 + (ww * 16 + (bit & 15)) * 16;
            float q[32], a[32], mx = -INFINITY, l = 0.f;
            #pragma unroll
            for (int ch = 0; ch < 4; ch++) {
                const uint4 u = lds128(qa + ch * 1024);
                h2_unpack(u.x, q[8*ch], q[8*ch+1]); h2_unpack(u.y, q[8*ch+2], q[8*ch+3]); h2_unpack(u.z, q[8*ch+4], q[8*ch+5]); h2_unpack(u.w, q[8*ch+6], q[8*ch+7]);
            }
            #pragma unroll
            for (int i = 0; i < 32; i++) a[i] = 0.f;
            #pragma unroll 1
            for (int it = 0; it < 16; it += 4) {
                uint4 u[4][8];
                #pragma unroll
                for (int i = 0; i < 4; i++)
                    #pragma unroll
                    for (int ch = 0; ch < 8; ch++) u[i][ch] = __ldcg(reinterpret_cast<const uint4*>(kv + ((it + i) >> 1) * KV_WIN + (i & 1) * 2048 + ch * 4096));
                float s[4], mn = mx;
                #pragma unroll
                for (int i = 0; i < 4; i++) {
                    s[i] = 0.f;
                    #pragma unroll
                    for (int ch = 0; ch < 4; ch++) {
                        const uint32_t v[4] = {u[i][ch].x, u[i][ch].y, u[i][ch].z, u[i][ch].w};
                        #pragma unroll
                        for (int e = 0; e < 4; e++) { float x, y; h2_unpack(v[e], x, y); s[i] = fmaf(x, q[8*ch + 2*e], fmaf(y, q[8*ch + 2*e + 1], s[i])); }
                    }
                    mn = fmaxf(mn, s[i]);
                }
                const float al = ex2((mx - mn) * isc);
                mx = mn; l *= al;
                #pragma unroll
                for (int i = 0; i < 32; i++) a[i] *= al;
                #pragma unroll
                for (int i = 0; i < 4; i++) {
                    const float p = ex2((s[i] - mx) * isc);
                    l += p;
                    #pragma unroll
                    for (int ch = 0; ch < 4; ch++) {
                        const uint32_t v[4] = {u[i][4 + ch].x, u[i][4 + ch].y, u[i][4 + ch].z, u[i][4 + ch].w};
                        #pragma unroll
                        for (int e = 0; e < 4; e++) { float x, y; h2_unpack(v[e], x, y); a[8*ch + 2*e] = fmaf(p, x, a[8*ch + 2*e]); a[8*ch + 2*e + 1] = fmaf(p, y, a[8*ch + 2*e + 1]); }
                    }
                }
            }
            const float mw = warp_max(mx);
            if (lane == 0) stsf(scr + 16 + w * 4, mw);
            named_sync(3 + wg, 128);
            const float al = ex2((mx - fmaxf(fmaxf(ldsf(scr + 16), ldsf(scr + 20)), fmaxf(ldsf(scr + 24), ldsf(scr + 28)))) * isc);
            l *= al;
            #pragma unroll
            for (int i = 0; i < 32; i++) a[i] *= al;
            l = warp_sum(l);
            #pragma unroll
            for (int j = 0; j < 31; j++) {
                const int o = j < 16 ? 16 : j < 24 ? 8 : j < 28 ? 4 : j < 30 ? 2 : 1, i = j - (32 - 2 * o);
                const bool up = lane & o;
                const float lo = a[i], hi = a[i + o];
                a[i] = (up ? hi : lo) + __shfl_xor_sync(0xffffffffu, up ? lo : hi, o);
            }
            stsf(scr + 32 + (w * 33 + lane) * 4, a[0]);
            if (lane == 0) stsf(scr + 32 + (w * 33 + 32) * 4, l);
            named_sync(3 + wg, 128);
            if (w == 0) {
                float o = 0.f, ls = 0.f;
                #pragma unroll
                for (int i = 0; i < 4; i++) { o += ldsf(scr + 32 + (i * 33 + lane) * 4); ls += ldsf(scr + 32 + (i * 33 + 32) * 4); }
                asm volatile("st.shared.u16 [%0], %1;" :: "r"(qa + (lane >> 3) * 1024 + (lane & 7) * 2), "h"((unsigned short)(pack_bf16(o * ivs / ls, 0.f))) : "memory");
            }
        }
    }
    named_sync(3 + wg, 128);
}

__device__ __forceinline__ void attention_phase(int L, int wg) {
    const uint32_t rb = L * 32;
    constexpr uint64_t dk0 = desc_plain(SB, 4096, 128), dv0 = desc_plain(SB + 16384, 128, 4096);
    constexpr int T1 = 2048 >> 4;
    uint32_t st = 0, ph = 0;
    #pragma unroll 1
    for (int pass = 0; pass < 2; pass++) {
        const uint64_t dqa = desc_plain(SB + OFF_QA, 1024, 128) + (pass * 4 + wg * 2) * (4096 >> 4), dqc = dqa + (4096 >> 4);
        Unit a, c;
        st = warp_uniform(st); ph = warp_uniform(ph);
        uint32_t SA[32], SC[32], PA[32], PC[32], ha[10], hc[10], pst = 0;
        #pragma unroll
        for (int i = 0; i < 10; i++) hc[i] = 0u;
        #pragma unroll
        for (int i = 0; i < 32; i++) PC[i] = 0u;
        mbar_wait(rb + B_AF + 8 * st, ph);
        wg_fence();
        issue_qk(SA, dqa, dk0 + st * (A_WIN >> 4));
        issue_qk(SC, dqc, dk0 + st * (A_WIN >> 4));
        wg_wait<1>();
        unit_init(a, SA);
        exp_tile(PA, SA, a);
        wg_wait<0>();
        unit_init(c, SC);
        #pragma unroll 1
        for (int s = 0;; s++) {
            const uint64_t dkb = dk0 + st * (A_WIN >> 4), dvb = dv0 + st * (A_WIN >> 4);
            uint32_t nst = st + 1, nph = ph;
            if (nst == 3) { nst = 0; nph ^= 1; }
            const uint64_t dkn = dk0 + nst * (A_WIN >> 4);
            wg_fence();
            issue_pv<true>(ha, PA, dvb); issue_qk(SA, dqa, dkb + T1);
            wg_wait<2>();
            if (s > 0) { mbar_arrive_elect(rb + B_AE + 8 * pst); unit_flush<true>(c, hc); }
            else {
                #pragma unroll
                for (int i = 0; i < 32; i++) c.o[i & 7] |= PC[i];
            }
            exp_tile(PC, SC, c);
            wg_fence();
            issue_pv<true>(hc, PC, dvb); issue_qk(SC, dqc, dkb + T1);
            wg_wait<2>();
            exp_tile(PA, SA, a);
            if (s == 7) {
                wg_fence(); issue_pv<false>(ha, PA, dvb + T1);
                wg_wait<1>();
                exp_tile(PC, SC, c);
                wg_fence(); issue_pv<false>(hc, PC, dvb + T1);
                wg_wait<1>();
                unit_flush<false>(a, ha);
                wg_wait<0>();
                unit_flush<false>(c, hc);
                mbar_arrive_elect(rb + B_AE + 8 * st);
                st = nst; ph = nph;
                break;
            }
            mbar_wait(rb + B_AF + 8 * nst, nph);
            wg_fence();
            issue_pv<false>(ha, PA, dvb + T1); issue_qk(SA, dqa, dkn);
            wg_wait<2>();
            exp_tile(PC, SC, c);
            wg_fence();
            issue_pv<false>(hc, PC, dvb + T1); issue_qk(SC, dqc, dkn);
            wg_wait<2>();
            unit_flush<true>(a, ha);
            exp_tile(PA, SA, a);
            pst = st; st = nst; ph = nph;
        }
        const int tid = tid_now(), lane = tid & 31;
        const float ivs = ldsf(SB + OFF_M + M_IVS + pass * 4);
        const bool head_ok = lds32(SB + OFF_M + M_OK + pass * 4) != 0;
        const uint32_t dst = SB + OFF_QA + pass * 16384 + wg * 8192 + (lane >> 3) * 1024 + (((tid >> 5) & 3) * 16 + (lane & 7)) * 16;
        const uint32_t bad = unit_store(a, dst, ivs, head_ok, lane) | unit_store(c, dst + 4096, ivs, head_ok, lane) << 16;
        if (__builtin_expect(named_any(bad != 0, 3 + wg), 0)) {
            exact_rows(L, pass, wg, bad);
        }
        fence_async_smem();
        named_arrive(N_OST + 2 * pass + wg, 160);
        TL(pass ? -1 : 0, L, 8); TL(pass ? 0 : -1, L, 9);
    }
}

#define FLP 1
#define GDP 1
#define DDP 2
constexpr uint32_t STAT_FULL = 0x41000000u;

__device__ __forceinline__ void oproj_phase(int L, int wg, bf16* __restrict__ out) {
    const int c = cta_now(), tid = tid_now(), lane = tid & 31, W = tid >> 5, g = lane >> 2, t = lane & 3;
    const int row0 = (c >> 4) * 256 + (c & 1) * 128, col0 = ((c & 15) >> 1) * 128;
    float acc[64];
    #pragma unroll
    for (int i = 0; i < 64; i++) acc[i] = 0.f;
    #pragma unroll 1
    for (int k = 0; k < 16; k++) {
        const uint32_t s = k & 3;
        mbar_wait(B_OF + 8 * s, (k >> 2) & 1);
        TL(k == 0 ? 0 : -1, L, 10); TL(k == 8 ? 0 : -1, L, 11);
        const uint64_t da = desc_plain(SB, 1024, 128) + ((o_stage(s) + wg * 4096) >> 4);
        const uint64_t db = desc_sw128(SB + 16384, 8192, 1024) + (o_stage(s) >> 4);
        wg_fence();
        #pragma unroll
        for (int kk = 0; kk < 4; kk++) wg_gemm_n128(acc, da + (kk >> 1) * 512 + (kk & 1) * 128, db + kk * 128);
        wg_commit();
        if (k > 0) {
            wg_wait<1>();
            if ((tid & 127) == 0) mbar_arrive(B_OE + 8 * ((k - 1) & 3));
        }
    }
    mbar_wait(B_RES2, L);
    const uint32_t xa = SB + OFF_XT + (W * 16 + ((lane >> 3) & 1) * 8 + (lane & 7)) * 128, xs = (lane >> 4) ^ (lane & 7);
    uint32_t x[32];
    const uint32_t wra = SB + OFF_WR + (g == 0 ? t * 8 : 256), wrs = g == 0 ? 32 : 0;
    wg_wait<0>();
    if ((tid & 127) == 0) mbar_arrive(B_OE + 24);
    TL(0, L, 12);
    {
        float sd[4] = {0.f, 0.f, 0.f, 0.f}, q0[4] = {0.f, 0.f, 0.f, 0.f}, q1[4] = {0.f, 0.f, 0.f, 0.f};
        #pragma unroll
        for (int ks = 0; ks < 8; ks++) {
            ldsm4(x[4*ks], x[4*ks+1], x[4*ks+2], x[4*ks+3], xa + (ks >> 2) * 16384 + ((xs ^ ((ks & 3) * 2)) << 4));
            const float2 wb = lds64f(wra + ks * wrs);
            #pragma unroll
            for (int i = 0; i < 4; i++) x[4*ks + i] = badd2(x[4*ks + i], pack_bf16(acc[8*ks + 2*i], acc[8*ks + 2*i + 1]));
            mma_bf16(sd, x[4*ks], x[4*ks+1], x[4*ks+2], x[4*ks+3], __float_as_uint(wb.x), __float_as_uint(wb.y));
            mma_bf16(q0, x[4*ks], x[4*ks+1], x[4*ks+2], x[4*ks+3], x[4*ks], x[4*ks+2]);
            mma_bf16(q1, x[4*ks], x[4*ks+1], x[4*ks+2], x[4*ks+3], x[4*ks+1], x[4*ks+3]);
        }
        const float s0 = __shfl_sync(0xffffffffu, (g & 1) ? q0[1] : q0[0], 4 * g + (g >> 1));
        const float s1 = __shfl_sync(0xffffffffu, (g & 1) ? q1[3] : q1[2], 4 * g + (g >> 1));
        if (t == 0) {
            float4* p = &g_sums[L][row0 + W * 16 + g];
            asm volatile("red.relaxed.gpu.global.add.v4.f32 [%0], {%1, %2, %3, %4};" :: "l"(p), "f"(sd[1]), "f"(s0), "f"(sd[0]), "f"(1.f) : "memory");
            asm volatile("red.relaxed.gpu.global.add.v4.f32 [%0], {%1, %2, %3, %4};" :: "l"(p + 8), "f"(sd[3]), "f"(s1), "f"(sd[2]), "f"(1.f) : "memory");
        }
    }
    TL(0, L, 13);
    if (L == 0) {
        #pragma unroll
        for (int ks = 0; ks < 8; ks++) stsm4(xa + (ks >> 2) * 16384 + ((xs ^ ((ks & 3) * 2)) << 4), x[4*ks], x[4*ks+1], x[4*ks+2], x[4*ks+3]);
        fence_async_smem();
        named_arrive(N_XST + wg, 160);
    }
    const bool ffn = c < NFC;
    uint4 fa[32], fd[16];
    const uint32_t ga = SB + W * 2048 + ((lane >> 4) * 8 + (lane & 7)) * 64 + ((((lane >> 3) & 1) ^ ((lane >> 1) & 3)) << 4);
    if (ffn) mbar_wait(B_FE, L);
    #pragma unroll
    for (int i = 0; i < 12; i++) ldsm4t(fa[i].x, fa[i].y, fa[i].z, fa[i].w, (ga ^ ((i & 1) * 32)) + gu_piece(i >> 2) + (i & 2) * 512);
    {
        uint4 s0 = make_uint4(0u, 0u, 0u, 0u), s1 = s0, sv[8];
        uint32_t n = 0;
        do {
            ld_relaxed4_unless(s0, &g_sums[L][row0 + W * 16 + g], STAT_FULL); ld_relaxed4_unless(s1, &g_sums[L][row0 + W * 16 + g + 8], STAT_FULL);
        } while ((s0.w != STAT_FULL || s1.w != STAT_FULL) && ++n < SPIN_MAX);
        __syncwarp();
        TL(0, L, 46);
        #pragma unroll
        for (int i = 0; i < 8; i++) sv[i] = ld_relaxed4(&g_sums[L][tid + 256 * i]);
        if (L == 1) {
            const float2 r0 = ln_coef(s0), r1 = ln_coef(s1);
            const float b0 = -r0.x * r0.y, b1 = -r1.x * r1.y;
            #pragma unroll
            for (int ks = 0; ks < 8; ks++)
                stsm4(xa + (ks >> 2) * 16384 + ((xs ^ ((ks & 3) * 2)) << 4), add_ln2(x[4*ks], r0.x, b0), add_ln2(x[4*ks+1], r1.x, b1),
                      add_ln2(x[4*ks+2], r0.x, b0), add_ln2(x[4*ks+3], r1.x, b1));
            fence_async_smem();
            named_arrive(N_XST + wg, 160);
        }
        if (FLP == 0) {
            if (ffn) mbar_wait(B_FL, L);
            #pragma unroll
            for (int i = 12; i < 32; i++) ldsm4t(fa[i].x, fa[i].y, fa[i].z, fa[i].w, (ga ^ ((i & 1) * 32)) + gu_piece(i >> 2) + (i & 2) * 512);
        }
        TL(0, L, 45);
        const float ws = ldsf(SB + OFF_M + M_WS) + ldsf(SB + OFF_M + M_WS + 4) + ldsf(SB + OFF_M + M_WS + 8);
        const uint32_t full = STAT_FULL | (lds32(SB + OFF_WR + 256) & 1);
        while (true) {
            bool done = true;
            #pragma unroll
            for (int i = 0; i < 8; i++) done = done && sv[i].w == full;
            if (done || ++n >= SPIN_MAX) break;
            #pragma unroll
            for (int i = 0; i < 8; i++) ld_relaxed4_unless(sv[i], &g_sums[L][tid + 256 * i], STAT_FULL);
        }
        spin_check(n);
        __syncwarp();
        TL(0, L, 15);
        float best;
        uint32_t brow = tid;
        #pragma unroll
        for (int i = 0; i < 8; i++) {
            const float2 r = ln_coef(sv[i]);
            const float v = r.x * fmaf(-r.y, ws, __uint_as_float(sv[i].z));
            if (i == 0) best = v;
            else if (v > best) { best = v; brow = tid + 256 * i; }
        }
        const uint32_t k = order_bits(best), m = redux_max(k), mrow = redux_min(k == m ? brow : 0x7FFFFFFFu);
        if (lane == 0) sts64f(SB + OFF_RT + W * 8, __uint_as_float(m), __uint_as_float(mrow));
    }
    named_sync(1, 256);
    if (W == 7 && L == 0) named_arrive(N_RT, 128);
    RouteOut rt = route_result(lane);
    const int lrt = rt.idx - row0;
    {
        if ((lrt >> 4) == W) {
            const bool hi = lrt & 8;
            #pragma unroll
            for (int i = 0; i < 4; i++)
                st_relaxed4_if(&g_xrow[L][col0 / 2 + i * 16 + t * 4], make_uint4(min(hi ? x[8*i+1] : x[8*i], SENT - 1), min(hi ? x[8*i+3] : x[8*i+2], SENT - 1),
                               min(hi ? x[8*i+5] : x[8*i+4], SENT - 1), min(hi ? x[8*i+7] : x[8*i+6], SENT - 1)), g == (lrt & 7));
        }
        __syncwarp();
    }
    TL(0, L, 16);
    uint2 xrow;
    {
        const uint4 rs = ld_relaxed4(&g_sums[L][rt.idx]);
        const uint32_t* xp = &g_xrow[L][((g >> 1) * 2 + (W >> 2)) * 64 + (W & 3) * 16 + t * 4 + (g & 1) * 2];
        if (FLP == 1) {
            if (ffn) mbar_wait(B_FL, L);
            #pragma unroll
            for (int i = 12; i < 32; i++) ldsm4t(fa[i].x, fa[i].y, fa[i].z, fa[i].w, (ga ^ ((i & 1) * 32)) + gu_piece(i >> 2) + (i & 2) * 512);
        }
        xrow = ld_relaxed2(xp);
        if (ffn) mbar_wait(B_FD, L);
        const uint32_t wa = SB + OFF_FD + W * 8192 + ((lane >> 4) * 8 + (lane & 7)) * 128 + ((((lane >> 3) & 1) ^ (lane & 7)) << 4);
        #pragma unroll
        for (int i = 0; i < 16; i++) ldsm4t(fd[i].x, fd[i].y, fd[i].z, fd[i].w, (wa ^ (((i >> 1) & 3) * 32)) + (i >> 3) * 4096 + (i & 1) * 2048);
        if (L == 0 && GDP == 1) named_arrive(N_GD, 288);
        if (L == 0 && DDP == 1) named_arrive(N_DD, 288);
        uint32_t n = 0;
        while ((xrow.x == SENT || xrow.y == SENT) && ++n < SPIN_MAX) xrow = ld_relaxed2(xp);
        spin_check(n);
        __syncwarp();
        route_stats(rt, rs);
    }
    if (L == 0 && GDP == 2) named_arrive(N_GD, 288);
    if (L == 0 && DDP == 2) named_arrive(N_DD, 288);
    TL(0, L, 17);
    {
        const float nb = -rt.mean * rt.rstd;
        const uint32_t n0 = pack_bf16(fmaf(bf_lo(xrow.x), rt.rstd, nb), fmaf(bf_hi(xrow.x), rt.rstd, nb));
        const uint32_t n1 = pack_bf16(fmaf(bf_lo(xrow.y), rt.rstd, nb), fmaf(bf_hi(xrow.y), rt.rstd, nb));
        float gu[4][4];
        #pragma unroll
        for (int i = 0; i < 4; i++) { gu[i][0] = 0.f; gu[i][1] = 0.f; gu[i][2] = 0.f; gu[i][3] = 0.f; }
        #pragma unroll
        for (int ks = 0; ks < 8; ks++) {
            const uint32_t b0 = __shfl_sync(0xffffffffu, n0, 4 * ks + t), b1 = __shfl_sync(0xffffffffu, n1, 4 * ks + t);
            #pragma unroll
            for (int i = 0; i < 4; i++) {
                const uint4& a = fa[(ks >> 1) * 8 + (i >> 1) * 4 + (ks & 1) * 2 + (i & 1)];
                mma_bf16(gu[i], a.x, a.y, a.z, a.w, b0, b1);
            }
        }
        stsf(SB + OFF_PART + (W * 64 + t * 16 + g) * 4, sel4(t, gu[0][0], gu[1][0], gu[2][0], gu[3][0]));
        stsf(SB + OFF_PART + (W * 64 + t * 16 + g + 8) * 4, sel4(t, gu[0][2], gu[1][2], gu[2][2], gu[3][2]));
    }
    named_sync(1, 256);
    TL(0, L, 18);
    {
        float gsum = 0.f, usum = 0.f;
        #pragma unroll
        for (int i = 0; i < 8; i++) { gsum += ldsf(SB + OFF_PART + (i * 64 + lane) * 4); usum += ldsf(SB + OFF_PART + (i * 64 + 32 + lane) * 4); }
        const float gv = bf_round(gsum), uv = bf_round(usum);
        const float hv = bf_round(__fdividef(gv, 1.f + __expf(-gv))) * uv;
        const uint32_t hp = pack_bf16(hv, __shfl_down_sync(0xffffffffu, hv, 1));
        uint32_t hb[4];
        #pragma unroll
        for (int i = 0; i < 4; i++) hb[i] = __shfl_sync(0xffffffffu, hp, 8 * i + 2 * t);
        float y[8][4];
        #pragma unroll
        for (int mb = 0; mb < 8; mb++) {
            y[mb][0] = 0.f; y[mb][1] = 0.f; y[mb][2] = 0.f; y[mb][3] = 0.f;
            #pragma unroll
            for (int ks = 0; ks < 2; ks++) mma_bf16(y[mb], fd[2*mb + ks].x, fd[2*mb + ks].y, fd[2*mb + ks].z, fd[2*mb + ks].w, hb[2 * ks], hb[2 * ks + 1]);
        }
        st_relaxed4_if(&g_ypart[L][min(c, NFC - 1)][tid * 4], make_uint4(not_sent(sel4(t, y[0][0], y[2][0], y[4][0], y[6][0])), not_sent(sel4(t, y[0][2], y[2][2], y[4][2], y[6][2])),
                       not_sent(sel4(t, y[1][0], y[3][0], y[5][0], y[7][0])), not_sent(sel4(t, y[1][2], y[3][2], y[5][2], y[7][2]))), ffn);
    }
    if (L == 0 && DDP == 3) named_arrive(N_DD, 288);
    TL(0, L, 19);
    if (L == 1) {
        if (W == 7) ctr_wait(&g_xc[1][rt.idx >> 8], 32);
        const float v = ffn_finish<256>(1, rt, tid, SB + OFF_FE, 1);
        if (tid < 8) reinterpret_cast<unsigned short*>(out)[(size_t)rt.idx * D_ + ypos_col(c * 8 + tid)] = (unsigned short)(__float_as_uint(v) >> 16);
        TL(0, L, 20);
    }
}

#define FW0 9
#define KW1 4
static_assert(FW0 >= 8 && KW1 >= 3 && KW1 < 7, "buffer reuse");
__device__ __forceinline__ void qkv_fill(const CUtensorMap* tx, const CUtensorMap* tw, uint32_t bar, int st, int k) {
    const uint32_t sa = SB + st * Q_STB;
    mbar_expect_tx(bar, Q_STB);
    tma_load(sa, tx, k * 64, (blockIdx.x >> 4) * 256, bar);
    tma_load3(sa + Q_ABYTES, tw, (blockIdx.x & 15) * 64, k * 64, 0, bar);
}
__device__ __forceinline__ void producer_role(const Maps& mp) {
    const int c = blockIdx.x, mt = c >> 4, nt = c & 15, lane = threadIdx.x & 31;
    #pragma unroll 1
    for (int i = 2; i < 13; i++) tm_prefetch(&mp.xa0 + i);
    #pragma unroll 1
    for (int L = 0; L < 2; L++) {
        const uint32_t rb = L * 32;
        uint32_t st = 0, ph = L;
        #pragma unroll 1
        for (int k = L == 0 ? 3 : 0; k < 16; k++) {
            if (k == 0) { ctr_wait(&g_xc[0][mt], 32); fence_async_global(); named_sync(N_GD, 288); }
            if (k == 1) named_sync(N_DD, 288);
            mbar_wait(rb + B_QE + 8 * st, ph);
            TL(k == 3 ? 256 : -1, L, 28);
            qkv_fill(L == 0 ? &mp.xa0 : &mp.xa, &mp.wqkv, rb + B_QF + 8 * st, st, k);
            if (L == 1 && k >= 3 && k < 7) {
                if (k == 3) mbar_expect_tx(B_SW, 4 * 12288);
                tma_load(SB + OFF_SIDE + (k - 3) * 12288, &mp.r, c * 24, (k - 3) * 256, B_SW);
            }
            if (++st == 3) { st = 0; ph ^= 1; }
        }
        mbar_wait(B_KV0, L);
        TL(256, L, 29);
        st = 1; ph = 1;
        #pragma unroll 1
        for (int w = 1; w < 16; w++) {
            const int win = (nt * 2 + (w >> 3)) * 8 + ((mt + w) & 7);
            if (w <= 3 || w == 8) {
                ctr_wait(&g_kvc[L][0][0] + (w < 3 ? win : (win & ~7) + (lane & 7)), 1);
                __syncwarp();
                fence_async_global();
            }
            TL(w == 1 ? 256 : -1, L, 7);
            mbar_wait(rb + B_AE + 8 * st, ph);
            mbar_expect_tx(rb + B_AF + 8 * st, KV_WIN);
            bulk_load(SB + st * A_WIN, g_kv + (size_t)win * KV_WIN, KV_WIN, rb + B_AF + 8 * st);
            if (w == KW1 || w == FW0) named_arrive(w == FW0 ? N_FW : N_KV1, 64);
            if (++st == 3) { st = 0; ph ^= 1; }
        }
        #pragma unroll 1
        for (int k = 0; k < 16; k++) {
            const uint32_t s = k & 3, fb = B_OF + 8 * s, sa = SB + o_stage(s);
            mbar_wait(k < 2 ? rb + B_AE + 8 + 8 * k : k == 2 ? rb + B_AE : k == 3 ? B_QAF : B_OE + 8 * s, k < 2 ? 0 : k == 2 ? 1 : k == 3 ? L : ((k >> 2) - 1) & 1);
            mbar_expect_tx(fb, 32768);
            tma_load5(sa + 16384, &mp.wo, 0, 0, k >> 3, (k & 7) * 2, nt & 14, fb);
            if ((k & 7) == 0) { ctr_wait(&g_oc[L][mt * 2 + (nt & 1)][k >> 3], 16); fence_async_global(); }
            bulk_load(sa, g_o + (size_t)((mt * 2 + (nt & 1)) * 16 + k) * 16384, 16384, fb);
        }
        if (c < NFC) {
            mbar_expect_tx(B_FL, 5 * 16384);
            mbar_expect_tx(B_FD, 4 * 16384);
            #pragma unroll 1
            for (int i = 3; i < 12; i++) {
                mbar_wait(B_OE + (i < 5 ? 0 : i == 5 ? 8 : i < 9 ? 16 : 24), 1);
                TL(i == 9 ? 256 : -1, L, 32);
                ffn_load(mp, i, SB + (i < 8 ? gu_piece(i) : OFF_FD + (i - 8) * 16384), i < 8 ? B_FL : B_FD);
            }
        }
    }
}

__global__ void __launch_bounds__(384, 1) k_all(const bf16* __restrict__ x0, const bf16* __restrict__ wo, const bf16* __restrict__ w_r, bf16* __restrict__ out,
                                                const __grid_constant__ Maps mp) {
    extern __shared__ __align__(1024) char smem[];
    if (smem_u32(smem) != SB) __trap();
    const int warp = warp_uniform(threadIdx.x >> 5), wg = warp >> 2;
    TL(0, 0, 0);
    {
        const int grp = warp >= 8 ? warp - 8 : warp + 4;
        #pragma unroll
        for (int i = 0; i < 4; i++) mbar_init(BB + grp * 32 + i * 8, grp < 7 ? 1 : grp < 10 ? 2 : 8);
        fence_mbar_init();
    }
    if (warp == 8) {
        #pragma unroll 1
        for (int s = 0; s < 3; s++) qkv_fill(&mp.xa0, &mp.wqkv, B_QF + 8 * s, s, s);
    }
    __syncthreads();
    if (wg == 2) {
        reg_dec<40>();
        if (warp == 8) producer_role(mp);
        else side_role(mp, x0, wo, w_r);
    } else {
        reg_inc<232>();
        #pragma unroll 1
        for (int L = 0; L < 2; L++) {
            qkv_phase(L, wg);
            attention_phase(L, wg);
            oproj_phase(L, wg, out);
        }
    }
}

typedef CUresult (*EncodeFn)(CUtensorMap*, CUtensorMapDataType, cuuint32_t, void*, const cuuint64_t*, const cuuint64_t*, const cuuint32_t*,
                             const cuuint32_t*, CUtensorMapInterleave, CUtensorMapSwizzle, CUtensorMapL2promotion, CUtensorMapFloatOOBfill);

void make_map(EncodeFn enc, CUtensorMap* tm, const void* ptr, int rank, const cuuint64_t* dims, const cuuint64_t* strides, const cuuint32_t* box, CUtensorMapSwizzle sw) {
    const cuuint32_t es[5] = {1, 1, 1, 1, 1};
    enc(tm, CU_TENSOR_MAP_DATA_TYPE_BFLOAT16, rank, const_cast<void*>(ptr), dims, strides, box, es, CU_TENSOR_MAP_INTERLEAVE_NONE, sw,
        box[0] == 64 ? CU_TENSOR_MAP_L2_PROMOTION_L2_128B : CU_TENSOR_MAP_L2_PROMOTION_NONE, CU_TENSOR_MAP_FLOAT_OOB_FILL_NONE);
}
void make_map2(EncodeFn enc, CUtensorMap* tm, const void* ptr, uint64_t cols, uint64_t rows, uint32_t bc, uint32_t br, CUtensorMapSwizzle sw) {
    const cuuint64_t dims[2] = {cols, rows}, strides[1] = {cols * 2};
    const cuuint32_t box[2] = {bc, br};
    make_map(enc, tm, ptr, 2, dims, strides, box, sw);
}

}

extern "C" void kernel_launch(void* const* d_in, const int* in_sizes, int n_in, void* d_out, int out_size) {
    const bf16* x0 = (const bf16*)d_in[0];
    const bf16* wqkv = (const bf16*)d_in[1];
    const bf16* wo = (const bf16*)d_in[2];
    const bf16* w_r = (const bf16*)d_in[4];
    const bf16* w_gate = (const bf16*)d_in[5];
    const bf16* w_up = (const bf16*)d_in[6];
    const bf16* w_down = (const bf16*)d_in[7];

    EncodeFn enc = nullptr;
    cudaDriverEntryPointQueryResult qr;
    cudaGetDriverEntryPoint("cuTensorMapEncodeTiled", (void**)&enc, cudaEnableDefault, &qr);
    void* p_x;
    cudaGetSymbolAddress(&p_x, g_x);
    Maps mp;
    const CUtensorMapSwizzle S128 = CU_TENSOR_MAP_SWIZZLE_128B;
    make_map2(enc, &mp.x0, x0, D_, S_, 64, 64, S128);
    make_map2(enc, &mp.x, p_x, D_, S_, 64, 64, S128);
    make_map2(enc, &mp.out, d_out, D_, S_, 64, 16, S128);
    make_map2(enc, &mp.xs, p_x, D_, S_, 64, 16, S128);
    make_map2(enc, &mp.xa0, x0, D_, S_, 64, 256, S128);
    make_map2(enc, &mp.xa, p_x, D_, S_, 64, 256, S128);
    make_map2(enc, &mp.w64, wqkv, 3 * D_, D_, 64, 64, S128);
    {
        const cuuint64_t dims[3] = {D_, D_, 3}, strides[2] = {3 * D_ * 2, D_ * 2};
        const cuuint32_t box[3] = {64, 64, 3};
        make_map(enc, &mp.wqkv, wqkv, 3, dims, strides, box, S128);
    }
    make_map2(enc, &mp.r, wqkv, 3 * D_, D_, 24, 256, CU_TENSOR_MAP_SWIZZLE_NONE);
    make_map2(enc, &mp.g, w_gate, FF, D_, 32, 256, CU_TENSOR_MAP_SWIZZLE_64B);
    make_map2(enc, &mp.u, w_up, FF, D_, 32, 256, CU_TENSOR_MAP_SWIZZLE_64B);
    {
        const cuuint64_t dims[5] = {64, 32, 2, 16, 16}, strides[4] = {D_ * 2, 32 * D_ * 2, 64 * D_ * 2, 128};
        const cuuint32_t box[5] = {64, 32, 1, 2, 2};
        make_map(enc, &mp.wo, wo, 5, dims, strides, box, S128);
    }
    {
        const cuuint64_t dims[3] = {64, FF, 16}, strides[2] = {D_ * 2, 128};
        const cuuint32_t box[3] = {64, 32, 4};
        make_map(enc, &mp.d, w_down, 3, dims, strides, box, S128);
    }
    cudaFuncSetAttribute(k_all, cudaFuncAttributeMaxDynamicSharedMemorySize, K_SMEM);
    k_all<<<128, 384, K_SMEM, cudaStreamPerThread>>>(x0, wo, w_r, (bf16*)d_out, mp);
}
```

```cpp
#include <cuda_runtime.h>
#include <cuda_bf16.h>
#include <cuda_fp16.h>
#include <cuda.h>
#include <cudaTypedefs.h>
#include <stdint.h>

namespace {

typedef __nv_bfloat16 bf16;

constexpr int S_ = 2048, D_ = 1024, NH = 32, FF = 3584, NFC = FF / 32;
constexpr float LN_EPS = 1e-5f;
constexpr float QSCALE = 0.17677669529663687f * 1.4426950408889634f;
constexpr uint32_t SENT = 0xFFFFFFFFu;

constexpr uint32_t STAT_FULL = 0x41000000u;

constexpr int KV_WIN = 32768;
__device__ __align__(1024) char g_kv[NH * 8 * KV_WIN];
__device__ __align__(1024) char g_o[32 * 2 * 16 * 4096];
__device__ __align__(1024) bf16 g_x[S_ * D_];
__device__ float g_csum[8 * 3 * D_];
__device__ float g_wsq[8 * 96];
__device__ float2 g_rs0[S_];
__device__ __align__(128) float4 g_sums[2][S_];
__device__ __align__(128) uint32_t g_ypart[2][NFC][D_];
__device__ __align__(128) uint4 g_tab[2][8][16][2];
__device__ __align__(128) uint32_t g_xrow[2][16][D_ / 2];
__device__ __align__(128) uint32_t g_x2row[D_];
__device__ __align__(128) uint32_t g_fix[3 * D_];
__device__ uint32_t g_c0;
__device__ __align__(128) uint32_t g_kvc[2][NH][8];
__device__ __align__(128) uint32_t g_oc[2][16][2];
__device__ __align__(128) uint32_t g_xc[2][8];
struct RouteOut { int idx; float r; float mean; float rstd; };

constexpr uint32_t SB = 1024;

__device__ __forceinline__ uint32_t smem_u32(const void* p) { return (uint32_t)__cvta_generic_to_shared(p); }
__device__ __forceinline__ void mbar_arrive(uint32_t bar) { asm volatile("mbarrier.arrive.shared::cta.b64 _, [%0];" :: "r"(bar) : "memory"); }
__device__ __forceinline__ void mbar_wait(uint32_t bar, uint32_t parity) {
    asm volatile("{\n.reg .pred p;\n.reg .u32 n;\nmov.u32 n, 0;\n"
                 "LAB_WAIT:\nmbarrier.try_wait.parity.shared::cta.b64 p, [%0], %1, 2000;\n@p bra LAB_DONE;\n"
                 "add.u32 n, n, 1;\nsetp.lt.u32 p, n, 0x200000;\n@p bra LAB_WAIT;\ntrap;\nLAB_DONE:\n}" :: "r"(bar), "r"(parity) : "memory");
}
__device__ __forceinline__ void mbar_arrive_elect(uint32_t bar) {
    asm volatile("{\n.reg .pred p;\nelect.sync _|p, 0xffffffff;\n@p mbarrier.arrive.shared::cta.b64 _, [%0];\n}" :: "r"(bar) : "memory");
}
__device__ __forceinline__ int tid_now() { int v; asm volatile("mov.u32 %0, %%tid.x;" : "=r"(v)); return v; }
__device__ __forceinline__ int cta_now() { int v; asm volatile("mov.u32 %0, %%ctaid.x;" : "=r"(v)); return v; }
__device__ __forceinline__ int warp_uniform(int v) { return __shfl_sync(0xffffffffu, v, 0); }
__device__ __forceinline__ void fence_mbar_init() { asm volatile("fence.mbarrier_init.release.cluster;" ::: "memory"); }
__device__ __forceinline__ void fence_async_smem() { asm volatile("fence.proxy.async.shared::cta;" ::: "memory"); }
__device__ __forceinline__ void fence_async_global() { asm volatile("fence.proxy.async.global;" ::: "memory"); }
__device__ __forceinline__ void named_sync(int id, int n) { asm volatile("bar.sync %0, %1;" :: "r"(id), "r"(n) : "memory"); }
__device__ __forceinline__ void named_arrive(int id, int n) { asm volatile("bar.arrive %0, %1;" :: "r"(id), "r"(n) : "memory"); }
__device__ __forceinline__ bool named_any(bool p, int id) {
    uint32_t r;
    asm volatile("{\n.reg .pred a, b;\nsetp.ne.u32 a, %1, 0;\nbarrier.cta.red.or.pred b, %2, 128, a;\nselp.u32 %0, 1, 0, b;\n}" : "=r"(r) : "r"((uint32_t)p), "r"(id) : "memory");
    return r != 0;
}
#define ELECT(op) "{\n.reg .pred e;\nelect.sync _|e, 0xffffffff;\n@e " op "\n}"
__device__ __forceinline__ void mbar_init(uint32_t bar, int cnt) { asm volatile(ELECT("mbarrier.init.shared::cta.b64 [%0], %1;") :: "r"(bar), "r"(cnt) : "memory"); }
__device__ __forceinline__ void mbar_expect_tx(uint32_t bar, uint32_t bytes) { asm volatile(ELECT("mbarrier.arrive.expect_tx.shared::cta.b64 _, [%0], %1;") :: "r"(bar), "r"(bytes) : "memory"); }
__device__ __forceinline__ void bulk_load(uint32_t dst, const void* src, uint32_t bytes, uint32_t bar) {
    asm volatile(ELECT("cp.async.bulk.shared::cluster.global.mbarrier::complete_tx::bytes [%0], [%1], %2, [%3];") :: "r"(dst), "l"(src), "r"(bytes), "r"(bar) : "memory");
}
__device__ __forceinline__ void bulk_store(void* dst, uint32_t src, uint32_t bytes) {
    asm volatile(ELECT("cp.async.bulk.global.shared::cta.bulk_group [%0], [%1], %2;") :: "l"(dst), "r"(src), "r"(bytes) : "memory");
}
__device__ __forceinline__ void bulk_commit() { asm volatile("cp.async.bulk.commit_group;" ::: "memory"); }
__device__ __forceinline__ void bulk_wait() { asm volatile("cp.async.bulk.wait_group 0;" ::: "memory"); }
template <int N> __device__ __forceinline__ void bulk_wait_n() { asm volatile("cp.async.bulk.wait_group %0;" :: "n"(N) : "memory"); }
__device__ __forceinline__ void bulk_wait_read() { asm volatile("cp.async.bulk.wait_group.read 0;" ::: "memory"); }
__device__ __forceinline__ void l2_prefetch(const void* src, uint32_t bytes) {
    asm volatile(ELECT("cp.async.bulk.prefetch.L2.global [%0], %1;") :: "l"(src), "r"(bytes) : "memory");
}
__device__ __forceinline__ void tma_load(uint32_t dst, const CUtensorMap* tm, int c0, int c1, uint32_t bar) {
    asm volatile(ELECT("cp.async.bulk.tensor.2d.shared::cluster.global.mbarrier::complete_tx::bytes [%0], [%1, {%3, %4}], [%2];")
                 :: "r"(dst), "l"(tm), "r"(bar), "r"(c0), "r"(c1) : "memory");
}
__device__ __forceinline__ void tma_load3(uint32_t dst, const CUtensorMap* tm, int c0, int c1, int c2, uint32_t bar) {
    asm volatile(ELECT("cp.async.bulk.tensor.3d.shared::cluster.global.mbarrier::complete_tx::bytes [%0], [%1, {%3, %4, %5}], [%2];")
                 :: "r"(dst), "l"(tm), "r"(bar), "r"(c0), "r"(c1), "r"(c2) : "memory");
}
__device__ __forceinline__ void tma_load5(uint32_t dst, const CUtensorMap* tm, int c0, int c1, int c2, int c3, int c4, uint32_t bar) {
    asm volatile(ELECT("cp.async.bulk.tensor.5d.shared::cluster.global.mbarrier::complete_tx::bytes [%0], [%1, {%3, %4, %5, %6, %7}], [%2];")
                 :: "r"(dst), "l"(tm), "r"(bar), "r"(c0), "r"(c1), "r"(c2), "r"(c3), "r"(c4) : "memory");
}
__device__ __forceinline__ void tma_store(const CUtensorMap* tm, uint32_t src, int c0, int c1) {
    asm volatile(ELECT("cp.async.bulk.tensor.2d.global.shared::cta.bulk_group [%0, {%2, %3}], [%1];") :: "l"(tm), "r"(src), "r"(c0), "r"(c1) : "memory");
}
__device__ __forceinline__ void tm_prefetch(const CUtensorMap* tm) { asm volatile(ELECT("prefetch.tensormap [%0];") :: "l"(tm) : "memory"); }
__device__ __forceinline__ uint32_t lds32(uint32_t a) { uint32_t v; asm volatile("ld.shared.b32 %0, [%1];" : "=r"(v) : "r"(a) : "memory"); return v; }
__device__ __forceinline__ float ldsf(uint32_t a) { return __uint_as_float(lds32(a)); }
__device__ __forceinline__ float2 lds64f(uint32_t a) { float2 v; asm volatile("ld.shared.v2.f32 {%0, %1}, [%2];" : "=f"(v.x), "=f"(v.y) : "r"(a) : "memory"); return v; }
__device__ __forceinline__ uint4 lds128(uint32_t a) { uint4 v; asm volatile("ld.shared.v4.b32 {%0, %1, %2, %3}, [%4];" : "=r"(v.x), "=r"(v.y), "=r"(v.z), "=r"(v.w) : "r"(a) : "memory"); return v; }
__device__ __forceinline__ void sts32(uint32_t a, uint32_t v) { asm volatile("st.shared.b32 [%0], %1;" :: "r"(a), "r"(v) : "memory"); }
__device__ __forceinline__ void stsf(uint32_t a, float v) { sts32(a, __float_as_uint(v)); }
__device__ __forceinline__ void sts64f(uint32_t a, float x, float y) { asm volatile("st.shared.v2.f32 [%0], {%1, %2};" :: "r"(a), "f"(x), "f"(y) : "memory"); }
__device__ __forceinline__ void sts128(uint32_t a, const uint4& v) { asm volatile("st.shared.v4.b32 [%0], {%1, %2, %3, %4};" :: "r"(a), "r"(v.x), "r"(v.y), "r"(v.z), "r"(v.w) : "memory"); }
__device__ __forceinline__ void stsm4(uint32_t a, uint32_t x, uint32_t y, uint32_t z, uint32_t w) {
    asm volatile("stmatrix.sync.aligned.m8n8.x4.shared.b16 [%0], {%1, %2, %3, %4};" :: "r"(a), "r"(x), "r"(y), "r"(z), "r"(w) : "memory");
}
__device__ __forceinline__ void ldsm4(uint32_t& a0, uint32_t& a1, uint32_t& a2, uint32_t& a3, uint32_t addr) {
    asm volatile("ldmatrix.sync.aligned.m8n8.x4.shared.b16 {%0,%1,%2,%3}, [%4];" : "=r"(a0), "=r"(a1), "=r"(a2), "=r"(a3) : "r"(addr) : "memory");
}
__device__ __forceinline__ void ldsm4t(uint32_t& a0, uint32_t& a1, uint32_t& a2, uint32_t& a3, uint32_t addr) {
    asm volatile("ldmatrix.sync.aligned.m8n8.x4.trans.shared.b16 {%0,%1,%2,%3}, [%4];" : "=r"(a0), "=r"(a1), "=r"(a2), "=r"(a3) : "r"(addr) : "memory");
}
__device__ __forceinline__ void mma_bf16(float (&c)[4], uint32_t a0, uint32_t a1, uint32_t a2, uint32_t a3, uint32_t b0, uint32_t b1) {
    asm("mma.sync.aligned.m16n8k16.row.col.f32.bf16.bf16.f32 {%0,%1,%2,%3}, {%4,%5,%6,%7}, {%8,%9}, {%0,%1,%2,%3};"
        : "+f"(c[0]), "+f"(c[1]), "+f"(c[2]), "+f"(c[3]) : "r"(a0), "r"(a1), "r"(a2), "r"(a3), "r"(b0), "r"(b1));
}
__device__ __forceinline__ uint32_t ld_relaxed(const void* p) { uint32_t v; asm volatile("ld.relaxed.gpu.global.u32 %0, [%1];" : "=r"(v) : "l"(p) : "memory"); return v; }
__device__ __forceinline__ uint4 ld_relaxed4(const void* p) {
    uint4 v; asm volatile("ld.relaxed.gpu.global.v4.b32 {%0, %1, %2, %3}, [%4];" : "=r"(v.x), "=r"(v.y), "=r"(v.z), "=r"(v.w) : "l"(p) : "memory"); return v;
}
__device__ __forceinline__ void ld_relaxed4_unless(uint4& v, const void* p, uint32_t full) {
    asm volatile("{\n.reg .pred q;\nsetp.ne.u32 q, %3, %5;\n@q ld.relaxed.gpu.global.v4.b32 {%0, %1, %2, %3}, [%4];\n}"
                 : "+r"(v.x), "+r"(v.y), "+r"(v.z), "+r"(v.w) : "l"(p), "r"(full) : "memory");
}
__device__ __forceinline__ uint2 ld_relaxed2(const void* p) { uint2 v; asm volatile("ld.relaxed.gpu.global.v2.b32 {%0, %1}, [%2];" : "=r"(v.x), "=r"(v.y) : "l"(p) : "memory"); return v; }
__device__ __forceinline__ void st_relaxed(void* p, uint32_t v) { asm volatile("st.relaxed.gpu.global.u32 [%0], %1;" :: "l"(p), "r"(v) : "memory"); }
__device__ __forceinline__ void st_relaxed4_if(void* p, const uint4& v, bool on) {
    asm volatile("{\n.reg .pred q;\nsetp.ne.u32 q, %5, 0;\n@q st.relaxed.gpu.global.v4.b32 [%0], {%1, %2, %3, %4};\n}"
                 :: "l"(p), "r"(v.x), "r"(v.y), "r"(v.z), "r"(v.w), "r"((uint32_t)on) : "memory");
}
__device__ __forceinline__ uint32_t not_sent(float v) { const uint32_t u = __float_as_uint(v); return u == SENT ? 0x7FFFFFFFu : u; }
__device__ __forceinline__ bool has_sent(const uint4& v) { return max(max(v.x, v.y), max(v.z, v.w)) == SENT; }
constexpr uint32_t SPIN_MAX = 1u << 22;
__device__ __forceinline__ void spin_check(uint32_t n) { asm volatile("{\n.reg .pred p;\nsetp.ge.u32 p, %0, %1;\n@p st.global.u32 [%2], %0;\n}" :: "r"(n), "n"(SPIN_MAX), "l"(0ull) : "memory"); }
__device__ __forceinline__ void ctr_arrive(uint32_t* c) { asm volatile(ELECT("red.release.gpu.global.add.u32 [%0], 1;") :: "l"(c) : "memory"); }
__device__ __forceinline__ void ctr_wait(const uint32_t* c, uint32_t target) {
    asm volatile("{\n.reg .pred p;\n.reg .u32 n, v;\nmov.u32 n, 0;\n"
                 "LAB_WAIT:\nld.acquire.gpu.global.u32 v, [%0];\nsetp.ge.u32 p, v, %1;\n@p bra LAB_DONE;\n"
                 "add.u32 n, n, 1;\nsetp.lt.u32 p, n, 0x400000;\n@p bra LAB_WAIT;\ntrap;\nLAB_DONE:\n}" :: "l"(c), "r"(target) : "memory");
}
__device__ __forceinline__ void publish(uint32_t* c) { bulk_wait(); fence_async_global(); ctr_arrive(c); }

__device__ __forceinline__ void wg_fence() { asm volatile("wgmma.fence.sync.aligned;" ::: "memory"); }
__device__ __forceinline__ void wg_commit() { asm volatile("wgmma.commit_group.sync.aligned;" ::: "memory"); }
template <int N> __device__ __forceinline__ void wg_wait() { asm volatile("wgmma.wait_group.sync.aligned %0;" :: "n"(N) : "memory"); }
template <int N> __device__ __forceinline__ void reg_inc() { asm volatile("setmaxnreg.inc.sync.aligned.u32 %0;" :: "n"(N)); }
template <int N> __device__ __forceinline__ void reg_dec() { asm volatile("setmaxnreg.dec.sync.aligned.u32 %0;" :: "n"(N)); }
__host__ __device__ constexpr uint64_t desc_plain(uint32_t addr, uint32_t lbo, uint32_t sbo) {
    return (uint64_t)((addr & 0x3FFFF) >> 4) | ((uint64_t)(lbo >> 4) << 16) | ((uint64_t)(sbo >> 4) << 32);
}
__host__ __device__ constexpr uint64_t desc_sw128(uint32_t addr, uint32_t lbo, uint32_t sbo) { return desc_plain(addr, lbo, sbo) | (1ull << 62); }

__device__ __forceinline__ float ex2(float x) { float y; asm("ex2.approx.ftz.f32 %0, %1;" : "=f"(y) : "f"(x)); return y; }
__device__ __forceinline__ float rcp(float x) { float y; asm("rcp.approx.ftz.f32 %0, %1;" : "=f"(y) : "f"(x)); return y; }
__device__ __forceinline__ float rsq(float x) { float y; asm("rsqrt.approx.ftz.f32 %0, %1;" : "=f"(y) : "f"(x)); return y; }
__device__ __forceinline__ uint32_t pack_bf16(float lo, float hi) { uint32_t r; asm("cvt.rn.bf16x2.f32 %0, %1, %2;" : "=r"(r) : "f"(hi), "f"(lo)); return r; }
__device__ __forceinline__ uint32_t pack_f16(float lo, float hi) { uint32_t r; asm("cvt.rn.f16x2.f32 %0, %1, %2;" : "=r"(r) : "f"(hi), "f"(lo)); return r; }
__device__ __forceinline__ float bf_lo(uint32_t v) { return __uint_as_float(v << 16); }
__device__ __forceinline__ float bf_hi(uint32_t v) { return __uint_as_float(v & 0xFFFF0000u); }
__device__ __forceinline__ float bf_round(float x) { return __uint_as_float(pack_bf16(0.f, x)); }
__device__ __forceinline__ uint32_t badd2(uint32_t a, uint32_t b) { uint32_t r; asm("add.rn.bf16x2 %0, %1, %2;" : "=r"(r) : "r"(a), "r"(b)); return r; }
__device__ __forceinline__ void h2_unpack(uint32_t v, float& lo, float& hi) {
    asm("{.reg .f16 l, h; mov.b32 {l, h}, %2; cvt.f32.f16 %0, l; cvt.f32.f16 %1, h;}" : "=f"(lo), "=f"(hi) : "r"(v));
}
__device__ __forceinline__ uint32_t add_ln2(uint32_t x, float rstd, float nb) { return badd2(x, pack_bf16(fmaf(bf_lo(x), rstd, nb), fmaf(bf_hi(x), rstd, nb))); }
__device__ __forceinline__ float sel4(int t, float a0, float a1, float a2, float a3) {
    float r;
    asm("{\n.reg .pred p, q;\n.reg .f32 x, y;\nsetp.ne.u32 p, %1, 0;\nsetp.ne.u32 q, %2, 0;\nselp.f32 x, %4, %3, p;\nselp.f32 y, %6, %5, p;\nselp.f32 %0, y, x, q;\n}"
        : "=f"(r) : "r"(t & 1), "r"(t & 2), "f"(a0), "f"(a1), "f"(a2), "f"(a3));
    return r;
}
__device__ __forceinline__ float warp_sum(float v) {
    #pragma unroll
    for (int o = 16; o > 0; o >>= 1) v += __shfl_xor_sync(0xffffffffu, v, o);
    return v;
}
__device__ __forceinline__ float warp_max(float v) {
    #pragma unroll
    for (int o = 16; o > 0; o >>= 1) v = fmaxf(v, __shfl_xor_sync(0xffffffffu, v, o));
    return v;
}
__device__ __forceinline__ uint32_t redux_max(uint32_t v) { uint32_t r; asm volatile("redux.sync.max.u32 %0, %1, 0xffffffff;" : "=r"(r) : "r"(v)); return r; }
__device__ __forceinline__ uint32_t redux_min(uint32_t v) { uint32_t r; asm volatile("redux.sync.min.u32 %0, %1, 0xffffffff;" : "=r"(r) : "r"(v)); return r; }

#define TL(T, L, i)

__device__ __forceinline__ void wg_gemm_n128(float (&d)[64], uint64_t desca, uint64_t desc) {
    asm volatile("{\n.reg .pred p;\nsetp.ne.b32 p, 1, 0;\n"
        "wgmma.mma_async.sync.aligned.m64n128k16.f32.bf16.bf16 "
        "{%0,%1,%2,%3,%4,%5,%6,%7,%8,%9,%10,%11,%12,%13,%14,%15,%16,%17,%18,%19,%20,%21,%22,%23,%24,%25,%26,%27,%28,%29,%30,%31,%32,%33,%34,%35,%36,%37,%38,%39,%40,%41,%42,%43,%44,%45,%46,%47,%48,%49,%50,%51,%52,%53,%54,%55,%56,%57,%58,%59,%60,%61,%62,%63}, "
        "%64, %65, p, 1, 1, 0, 1;\n}\n"
        : "+f"(d[0]), "+f"(d[1]), "+f"(d[2]), "+f"(d[3]), "+f"(d[4]), "+f"(d[5]), "+f"(d[6]), "+f"(d[7]),
          "+f"(d[8]), "+f"(d[9]), "+f"(d[10]), "+f"(d[11]), "+f"(d[12]), "+f"(d[13]), "+f"(d[14]), "+f"(d[15]),
          "+f"(d[16]), "+f"(d[17]), "+f"(d[18]), "+f"(d[19]), "+f"(d[20]), "+f"(d[21]), "+f"(d[22]), "+f"(d[23]),
          "+f"(d[24]), "+f"(d[25]), "+f"(d[26]), "+f"(d[27]), "+f"(d[28]), "+f"(d[29]), "+f"(d[30]), "+f"(d[31]),
          "+f"(d[32]), "+f"(d[33]), "+f"(d[34]), "+f"(d[35]), "+f"(d[36]), "+f"(d[37]), "+f"(d[38]), "+f"(d[39]),
          "+f"(d[40]), "+f"(d[41]), "+f"(d[42]), "+f"(d[43]), "+f"(d[44]), "+f"(d[45]), "+f"(d[46]), "+f"(d[47]),
          "+f"(d[48]), "+f"(d[49]), "+f"(d[50]), "+f"(d[51]), "+f"(d[52]), "+f"(d[53]), "+f"(d[54]), "+f"(d[55]),
          "+f"(d[56]), "+f"(d[57]), "+f"(d[58]), "+f"(d[59]), "+f"(d[60]), "+f"(d[61]), "+f"(d[62]), "+f"(d[63])
        : "l"(desca), "l"(desc));
}
__device__ __forceinline__ void wg_gemm_n128_init(float (&d)[64], uint64_t desca, uint64_t desc) {
    asm volatile("{\n.reg .pred p;\nsetp.ne.b32 p, 0, 0;\n"
        "wgmma.mma_async.sync.aligned.m64n128k16.f32.bf16.bf16 "
        "{%0,%1,%2,%3,%4,%5,%6,%7,%8,%9,%10,%11,%12,%13,%14,%15,%16,%17,%18,%19,%20,%21,%22,%23,%24,%25,%26,%27,%28,%29,%30,%31,%32,%33,%34,%35,%36,%37,%38,%39,%40,%41,%42,%43,%44,%45,%46,%47,%48,%49,%50,%51,%52,%53,%54,%55,%56,%57,%58,%59,%60,%61,%62,%63}, "
        "%64, %65, p, 1, 1, 0, 1;\n}\n"
        : "=f"(d[0]), "=f"(d[1]), "=f"(d[2]), "=f"(d[3]), "=f"(d[4]), "=f"(d[5]), "=f"(d[6]), "=f"(d[7]),
          "=f"(d[8]), "=f"(d[9]), "=f"(d[10]), "=f"(d[11]), "=f"(d[12]), "=f"(d[13]), "=f"(d[14]), "=f"(d[15]),
          "=f"(d[16]), "=f"(d[17]), "=f"(d[18]), "=f"(d[19]), "=f"(d[20]), "=f"(d[21]), "=f"(d[22]), "=f"(d[23]),
          "=f"(d[24]), "=f"(d[25]), "=f"(d[26]), "=f"(d[27]), "=f"(d[28]), "=f"(d[29]), "=f"(d[30]), "=f"(d[31]),
          "=f"(d[32]), "=f"(d[33]), "=f"(d[34]), "=f"(d[35]), "=f"(d[36]), "=f"(d[37]), "=f"(d[38]), "=f"(d[39]),
          "=f"(d[40]), "=f"(d[41]), "=f"(d[42]), "=f"(d[43]), "=f"(d[44]), "=f"(d[45]), "=f"(d[46]), "=f"(d[47]),
          "=f"(d[48]), "=f"(d[49]), "=f"(d[50]), "=f"(d[51]), "=f"(d[52]), "=f"(d[53]), "=f"(d[54]), "=f"(d[55]),
          "=f"(d[56]), "=f"(d[57]), "=f"(d[58]), "=f"(d[59]), "=f"(d[60]), "=f"(d[61]), "=f"(d[62]), "=f"(d[63])
        : "l"(desca), "l"(desc));
}
__device__ __forceinline__ void wg_gemm_n192(float (&d)[96], uint64_t desca, uint64_t desc) {
    asm volatile("{\n.reg .pred p;\nsetp.ne.b32 p, 1, 0;\n"
        "wgmma.mma_async.sync.aligned.m64n192k16.f32.bf16.bf16 "
        "{%0,%1,%2,%3,%4,%5,%6,%7,%8,%9,%10,%11,%12,%13,%14,%15,%16,%17,%18,%19,%20,%21,%22,%23,%24,%25,%26,%27,%28,%29,%30,%31,%32,%33,%34,%35,%36,%37,%38,%39,%40,%41,%42,%43,%44,%45,%46,%47,%48,%49,%50,%51,%52,%53,%54,%55,%56,%57,%58,%59,%60,%61,%62,%63,%64,%65,%66,%67,%68,%69,%70,%71,%72,%73,%74,%75,%76,%77,%78,%79,%80,%81,%82,%83,%84,%85,%86,%87,%88,%89,%90,%91,%92,%93,%94,%95}, "
        "%96, %97, p, 1, 1, 0, 1;\n}\n"
        : "+f"(d[0]), "+f"(d[1]), "+f"(d[2]), "+f"(d[3]), "+f"(d[4]), "+f"(d[5]), "+f"(d[6]), "+f"(d[7]),
          "+f"(d[8]), "+f"(d[9]), "+f"(d[10]), "+f"(d[11]), "+f"(d[12]), "+f"(d[13]), "+f"(d[14]), "+f"(d[15]),
          "+f"(d[16]), "+f"(d[17]), "+f"(d[18]), "+f"(d[19]), "+f"(d[20]), "+f"(d[21]), "+f"(d[22]), "+f"(d[23]),
          "+f"(d[24]), "+f"(d[25]), "+f"(d[26]), "+f"(d[27]), "+f"(d[28]), "+f"(d[29]), "+f"(d[30]), "+f"(d[31]),
          "+f"(d[32]), "+f"(d[33]), "+f"(d[34]), "+f"(d[35]), "+f"(d[36]), "+f"(d[37]), "+f"(d[38]), "+f"(d[39]),
          "+f"(d[40]), "+f"(d[41]), "+f"(d[42]), "+f"(d[43]), "+f"(d[44]), "+f"(d[45]), "+f"(d[46]), "+f"(d[47]),
          "+f"(d[48]), "+f"(d[49]), "+f"(d[50]), "+f"(d[51]), "+f"(d[52]), "+f"(d[53]), "+f"(d[54]), "+f"(d[55]),
          "+f"(d[56]), "+f"(d[57]), "+f"(d[58]), "+f"(d[59]), "+f"(d[60]), "+f"(d[61]), "+f"(d[62]), "+f"(d[63]),
          "+f"(d[64]), "+f"(d[65]), "+f"(d[66]), "+f"(d[67]), "+f"(d[68]), "+f"(d[69]), "+f"(d[70]), "+f"(d[71]),
          "+f"(d[72]), "+f"(d[73]), "+f"(d[74]), "+f"(d[75]), "+f"(d[76]), "+f"(d[77]), "+f"(d[78]), "+f"(d[79]),
          "+f"(d[80]), "+f"(d[81]), "+f"(d[82]), "+f"(d[83]), "+f"(d[84]), "+f"(d[85]), "+f"(d[86]), "+f"(d[87]),
          "+f"(d[88]), "+f"(d[89]), "+f"(d[90]), "+f"(d[91]), "+f"(d[92]), "+f"(d[93]), "+f"(d[94]), "+f"(d[95])
        : "l"(desca), "l"(desc));
}
__device__ __forceinline__ void wg_gemm_n192_init(float (&d)[96], uint64_t desca, uint64_t desc) {
    asm volatile("{\n.reg .pred p;\nsetp.ne.b32 p, 0, 0;\n"
        "wgmma.mma_async.sync.aligned.m64n192k16.f32.bf16.bf16 "
        "{%0,%1,%2,%3,%4,%5,%6,%7,%8,%9,%10,%11,%12,%13,%14,%15,%16,%17,%18,%19,%20,%21,%22,%23,%24,%25,%26,%27,%28,%29,%30,%31,%32,%33,%34,%35,%36,%37,%38,%39,%40,%41,%42,%43,%44,%45,%46,%47,%48,%49,%50,%51,%52,%53,%54,%55,%56,%57,%58,%59,%60,%61,%62,%63,%64,%65,%66,%67,%68,%69,%70,%71,%72,%73,%74,%75,%76,%77,%78,%79,%80,%81,%82,%83,%84,%85,%86,%87,%88,%89,%90,%91,%92,%93,%94,%95}, "
        "%96, %97, p, 1, 1, 0, 1;\n}\n"
        : "=f"(d[0]), "=f"(d[1]), "=f"(d[2]), "=f"(d[3]), "=f"(d[4]), "=f"(d[5]), "=f"(d[6]), "=f"(d[7]),
          "=f"(d[8]), "=f"(d[9]), "=f"(d[10]), "=f"(d[11]), "=f"(d[12]), "=f"(d[13]), "=f"(d[14]), "=f"(d[15]),
          "=f"(d[16]), "=f"(d[17]), "=f"(d[18]), "=f"(d[19]), "=f"(d[20]), "=f"(d[21]), "=f"(d[22]), "=f"(d[23]),
          "=f"(d[24]), "=f"(d[25]), "=f"(d[26]), "=f"(d[27]), "=f"(d[28]), "=f"(d[29]), "=f"(d[30]), "=f"(d[31]),
          "=f"(d[32]), "=f"(d[33]), "=f"(d[34]), "=f"(d[35]), "=f"(d[36]), "=f"(d[37]), "=f"(d[38]), "=f"(d[39]),
          "=f"(d[40]), "=f"(d[41]), "=f"(d[42]), "=f"(d[43]), "=f"(d[44]), "=f"(d[45]), "=f"(d[46]), "=f"(d[47]),
          "=f"(d[48]), "=f"(d[49]), "=f"(d[50]), "=f"(d[51]), "=f"(d[52]), "=f"(d[53]), "=f"(d[54]), "=f"(d[55]),
          "=f"(d[56]), "=f"(d[57]), "=f"(d[58]), "=f"(d[59]), "=f"(d[60]), "=f"(d[61]), "=f"(d[62]), "=f"(d[63]),
          "=f"(d[64]), "=f"(d[65]), "=f"(d[66]), "=f"(d[67]), "=f"(d[68]), "=f"(d[69]), "=f"(d[70]), "=f"(d[71]),
          "=f"(d[72]), "=f"(d[73]), "=f"(d[74]), "=f"(d[75]), "=f"(d[76]), "=f"(d[77]), "=f"(d[78]), "=f"(d[79]),
          "=f"(d[80]), "=f"(d[81]), "=f"(d[82]), "=f"(d[83]), "=f"(d[84]), "=f"(d[85]), "=f"(d[86]), "=f"(d[87]),
          "=f"(d[88]), "=f"(d[89]), "=f"(d[90]), "=f"(d[91]), "=f"(d[92]), "=f"(d[93]), "=f"(d[94]), "=f"(d[95])
        : "l"(desca), "l"(desc));
}
__device__ __forceinline__ void wg_qk_init(uint32_t (&d)[32], uint64_t desca, uint64_t desc) {
    asm volatile("{\n.reg .pred p;\nsetp.ne.b32 p, 0, 0;\n"
        "wgmma.mma_async.sync.aligned.m64n128k16.f16.f16.f16 "
        "{%0,%1,%2,%3,%4,%5,%6,%7,%8,%9,%10,%11,%12,%13,%14,%15,%16,%17,%18,%19,%20,%21,%22,%23,%24,%25,%26,%27,%28,%29,%30,%31}, "
        "%32, %33, p, 1, 1, 0, 0;\n}\n"
        : "=r"(d[0]), "=r"(d[1]), "=r"(d[2]), "=r"(d[3]), "=r"(d[4]), "=r"(d[5]), "=r"(d[6]), "=r"(d[7]),
          "=r"(d[8]), "=r"(d[9]), "=r"(d[10]), "=r"(d[11]), "=r"(d[12]), "=r"(d[13]), "=r"(d[14]), "=r"(d[15]),
          "=r"(d[16]), "=r"(d[17]), "=r"(d[18]), "=r"(d[19]), "=r"(d[20]), "=r"(d[21]), "=r"(d[22]), "=r"(d[23]),
          "=r"(d[24]), "=r"(d[25]), "=r"(d[26]), "=r"(d[27]), "=r"(d[28]), "=r"(d[29]), "=r"(d[30]), "=r"(d[31])
        : "l"(desca), "l"(desc));
}
__device__ __forceinline__ void wg_qk_acc(uint32_t (&d)[32], uint64_t desca, uint64_t desc) {
    asm volatile("{\n.reg .pred p;\nsetp.ne.b32 p, 1, 0;\n"
        "wgmma.mma_async.sync.aligned.m64n128k16.f16.f16.f16 "
        "{%0,%1,%2,%3,%4,%5,%6,%7,%8,%9,%10,%11,%12,%13,%14,%15,%16,%17,%18,%19,%20,%21,%22,%23,%24,%25,%26,%27,%28,%29,%30,%31}, "
        "%32, %33, p, 1, 1, 0, 0;\n}\n"
        : "+r"(d[0]), "+r"(d[1]), "+r"(d[2]), "+r"(d[3]), "+r"(d[4]), "+r"(d[5]), "+r"(d[6]), "+r"(d[7]),
          "+r"(d[8]), "+r"(d[9]), "+r"(d[10]), "+r"(d[11]), "+r"(d[12]), "+r"(d[13]), "+r"(d[14]), "+r"(d[15]),
          "+r"(d[16]), "+r"(d[17]), "+r"(d[18]), "+r"(d[19]), "+r"(d[20]), "+r"(d[21]), "+r"(d[22]), "+r"(d[23]),
          "+r"(d[24]), "+r"(d[25]), "+r"(d[26]), "+r"(d[27]), "+r"(d[28]), "+r"(d[29]), "+r"(d[30]), "+r"(d[31])
        : "l"(desca), "l"(desc));
}
__device__ __forceinline__ void wg_pv_init(uint32_t (&d)[10], uint32_t a0, uint32_t a1, uint32_t a2, uint32_t a3, uint64_t desc) {
    asm volatile("{\n.reg .pred p;\nsetp.ne.b32 p, 0, 0;\n"
        "wgmma.mma_async.sync.aligned.m64n40k16.f16.f16.f16 "
        "{%0,%1,%2,%3,%4,%5,%6,%7,%8,%9}, "
        "{%10,%11,%12,%13}, %14, p, 1, 1, 1;\n}\n"
        : "=r"(d[0]), "=r"(d[1]), "=r"(d[2]), "=r"(d[3]), "=r"(d[4]), "=r"(d[5]), "=r"(d[6]), "=r"(d[7]),
          "=r"(d[8]), "=r"(d[9])
        : "r"(a0), "r"(a1), "r"(a2), "r"(a3), "l"(desc));
}
__device__ __forceinline__ void wg_pv_acc(uint32_t (&d)[10], uint32_t a0, uint32_t a1, uint32_t a2, uint32_t a3, uint64_t desc) {
    asm volatile("{\n.reg .pred p;\nsetp.ne.b32 p, 1, 0;\n"
        "wgmma.mma_async.sync.aligned.m64n40k16.f16.f16.f16 "
        "{%0,%1,%2,%3,%4,%5,%6,%7,%8,%9}, "
        "{%10,%11,%12,%13}, %14, p, 1, 1, 1;\n}\n"
        : "+r"(d[0]), "+r"(d[1]), "+r"(d[2]), "+r"(d[3]), "+r"(d[4]), "+r"(d[5]), "+r"(d[6]), "+r"(d[7]),
          "+r"(d[8]), "+r"(d[9])
        : "r"(a0), "r"(a1), "r"(a2), "r"(a3), "l"(desc));
}

constexpr int Q_ABYTES = 256 * 64 * 2, Q_STB = Q_ABYTES + 192 * 64 * 2;
constexpr int OFF_SIDE = 3 * Q_STB;
constexpr int OFF_XS = OFF_SIDE + 49152;
constexpr int OFF_CS = OFF_XS + 4096;
constexpr int OFF_RC = OFF_CS + 768;
constexpr int OFF_FIX = OFF_RC + 2048;
constexpr int A_WIN = KV_WIN + 4096;
constexpr int OFF_QA = 3 * A_WIN;
constexpr int OFF_FE = 147456;
constexpr int OFF_XT = 196608;
__host__ __device__ constexpr uint32_t o_stage(uint32_t s) { return s == 3 ? OFF_QA : s == 2 ? 0 : (s + 1) * A_WIN; }
__host__ __device__ constexpr uint32_t gu_piece(uint32_t i) { return i < 3 ? OFF_FE + i * 16384 : i < 6 ? (i - 1) * 16384 : (i - 6) * 16384; }
constexpr int OFF_FD = 5 * 16384;
constexpr int OFF_BAR = OFF_XT + 32768;
constexpr int OFF_PART = OFF_BAR + 384;
constexpr int OFF_RED = OFF_PART + 2048;
constexpr int OFF_RT = OFF_RED + 96;
constexpr int OFF_M = OFF_RT + 144;
constexpr int OFF_WR = OFF_M + 64;
constexpr int K_SMEM = OFF_WR + 264;
static_assert(K_SMEM <= 232448 && OFF_FIX + 768 <= OFF_BAR && OFF_QA + 32768 <= OFF_FE, "smem");
constexpr uint32_t CH_OK = 0x38003800u;
constexpr int M_SC = 0,
              M_IVS = 24,
              M_ISC = 32,
              M_OK = 40,
              M_WS = 48,
              M_RIDX = 60;
constexpr uint32_t BB = SB + OFF_BAR;
constexpr uint32_t B_QF = BB, B_EPI = BB + 24, B_RES2 = BB + 56, B_AF = BB + 64, B_RES = BB + 120, B_OF = BB + 128,
                   B_FE = BB + 160, B_FL = BB + 168, B_FD = BB + 184, B_PR = BB + 192, B_FW = B_PR, B_SW = BB + 216,
                   B_QE = BB + 224, B_QAF = BB + 248, B_OE = BB + 288, B_AE = BB + 320, B_KV0 = BB + 376;

constexpr int N_OST = 5, N_XST = 9, N_RT = 11, N_KV1 = 12, N_FW = 13, N_GD = 14, N_DD = 15;

struct Maps { CUtensorMap xa0, wqkv, xa, x0, x, out, w64, wo, r, g, u, d, xs; };

__device__ __forceinline__ float2 ln_coef(const uint4& s) {
    const float mean = __uint_as_float(s.x) * (1.f / D_);
    return make_float2(rsq(fmaxf(fmaf(-mean, mean, fmaf(__uint_as_float(s.y), 1.f / D_, LN_EPS)), LN_EPS)), mean);
}
__device__ __forceinline__ uint32_t order_bits(float r) { const uint32_t u = __float_as_uint(r); return (u & 0x80000000u) ? ~u : (u | 0x80000000u); }
__device__ __forceinline__ uint4 warp_best(const uint4& e) {
    const uint32_t m = redux_max(e.x), row = redux_min(e.x == m ? e.y : 0x7FFFFFFFu);
    const int src = __ffs(__ballot_sync(0xffffffffu, e.y == row)) - 1;
    return make_uint4(m, row, __shfl_sync(0xffffffffu, e.z, src), __shfl_sync(0xffffffffu, e.w, src));
}
__device__ __forceinline__ RouteOut route_out(const uint4& e) {
    RouteOut rt;
    rt.idx = e.y; rt.r = __uint_as_float((e.x & 0x80000000u) ? e.x & 0x7FFFFFFFu : ~e.x); rt.mean = __uint_as_float(e.z); rt.rstd = __uint_as_float(e.w);
    return rt;
}

__device__ __forceinline__ void prep_work(const bf16* __restrict__ x0, const CUtensorMap* tmW, int t) {
    const int c = blockIdx.x, lane = t & 31, warp = warp_uniform(t >> 5);
    const int ki = c >> 4, n = c & 15;
    constexpr uint32_t red = SB + OFF_SIDE, xs = red + 4096;
    if (warp == 0) {
        mbar_expect_tx(B_PR, 32768);
        bulk_load(xs, x0 + (size_t)c * 16 * D_, 32768, B_PR);
        mbar_expect_tx(B_PR + 8, 16384);
        tma_load(xs + 32768, tmW, 2 * D_ + n * 64, ki * 128, B_PR + 8);
        tma_load(xs + 32768 + 8192, tmW, 2 * D_ + n * 64, ki * 128 + 64, B_PR + 8);
    }
    if (t < 32) g_sums[t >> 4][c * 16 + (t & 15)] = make_float4(0.f, 0.f, 0.f, 0.f);
    const uint4 sent = make_uint4(SENT, SENT, SENT, SENT);
    for (int i = t; i < 2 * NFC * 2; i += 96) reinterpret_cast<uint4*>(&g_ypart[0][0][0])[c * (2 * NFC * 2) + i] = sent;
    if (t < 2) reinterpret_cast<uint4*>(g_x2row)[c * 2 + t] = sent;
    else if (t < 8) reinterpret_cast<uint4*>(g_fix)[c * 6 + t - 2] = sent;
    else if (t < 12) (&g_kvc[0][0][0])[c * 4 + t - 8] = 0u;
    else if (t == 12 && c < 64) (&g_oc[0][0][0])[c] = 0u;
    else if (t == 13 && c < 16) (&g_xc[0][0])[c] = 0u;
    else if (t >= 16 && t < 20) (&g_tab[0][0][0][0])[c * 4 + t - 16] = sent;
    else if (t >= 32 && t < 64) reinterpret_cast<uint4*>(&g_xrow[0][0][0])[c * 32 + t - 32] = sent;
    mbar_wait(B_PR, 0);
    #pragma unroll 1
    for (int r = warp; r < 16; r += 3) {
        float s = 0.f, q = 0.f;
        #pragma unroll
        for (int i = 0; i < 4; i++) {
            const uint4 u = lds128(xs + r * 2048 + (lane + 32 * i) * 16);
            const float f[8] = {bf_lo(u.x), bf_hi(u.x), bf_lo(u.y), bf_hi(u.y), bf_lo(u.z), bf_hi(u.z), bf_lo(u.w), bf_hi(u.w)};
            #pragma unroll
            for (int e = 0; e < 8; e++) { s += f[e]; q = fmaf(f[e], f[e], q); }
        }
        #pragma unroll
        for (int o = 16; o > 0; o >>= 1) { s += __shfl_xor_sync(0xffffffffu, s, o); q += __shfl_xor_sync(0xffffffffu, q, o); }
        const float mean = s * (1.f / D_);
        const float var = fmaxf(q * (1.f / D_) - mean * mean, 0.f);
        if (lane == 0) g_rs0[c * 16 + r] = make_float2(rsqrtf(var + LN_EPS), mean);
    }
    named_sync(2, 96);
    if (warp == 0) {
        mbar_expect_tx(B_PR + 16, 32768);
        #pragma unroll
        for (int b = 0; b < 4; b++) tma_load(xs + b * 8192, tmW, (b >> 1) * D_ + n * 64, ki * 128 + (b & 1) * 64, B_PR + 16);
    }
    const int j = t & 7, rg = t >> 3;
    #pragma unroll 1
    for (int blk = 0; blk < 3; blk++) {
        const int type = blk == 0 ? 2 : blk - 1;
        const uint32_t wb = xs + type * 16384;
        if (blk < 2) mbar_wait(B_PR + 8 + 8 * blk, 0);
        float cs[8];
        uint32_t z2[4] = {0u, 0u, 0u, 0u};
        #pragma unroll
        for (int i = 0; i < 8; i++) cs[i] = 0.f;
        #pragma unroll 4
        for (int r = rg; r < 128; r += 12) {
            const uint4 u = lds128(wb + r * 128 + ((j ^ (r & 7)) << 4));
            cs[0] += bf_lo(u.x); cs[1] += bf_hi(u.x); cs[2] += bf_lo(u.y); cs[3] += bf_hi(u.y);
            cs[4] += bf_lo(u.z); cs[5] += bf_hi(u.z); cs[6] += bf_lo(u.w); cs[7] += bf_hi(u.w);
            asm("fma.rn.bf16x2 %0, %1, %1, %0;" : "+r"(z2[0]) : "r"(u.x));
            asm("fma.rn.bf16x2 %0, %1, %1, %0;" : "+r"(z2[1]) : "r"(u.y));
            asm("fma.rn.bf16x2 %0, %1, %1, %0;" : "+r"(z2[2]) : "r"(u.z));
            asm("fma.rn.bf16x2 %0, %1, %1, %0;" : "+r"(z2[3]) : "r"(u.w));
        }
        #pragma unroll
        for (int i = 0; i < 8; i++) { cs[i] += __shfl_xor_sync(0xffffffffu, cs[i], 8); cs[i] += __shfl_xor_sync(0xffffffffu, cs[i], 16); }
        float z = ((bf_lo(z2[0]) + bf_hi(z2[0])) + (bf_lo(z2[1]) + bf_hi(z2[1]))) + ((bf_lo(z2[2]) + bf_hi(z2[2])) + (bf_lo(z2[3]) + bf_hi(z2[3])));
        z += __shfl_xor_sync(0xffffffffu, z, 1); z += __shfl_xor_sync(0xffffffffu, z, 2);
        z += __shfl_xor_sync(0xffffffffu, z, 8); z += __shfl_xor_sync(0xffffffffu, z, 16);
        if (lane < 8) {
            #pragma unroll
            for (int i = 0; i < 8; i++) stsf(red + (warp * 200 + type * 64 + j * 8 + i) * 4, cs[i]);
            if ((lane & 3) == 0) stsf(red + (warp * 200 + 192 + type * 2 + (lane >> 2)) * 4, z);
        }
    }
    named_sync(2, 96);
    for (int i = t; i < 198; i += 96) {
        const float v = ldsf(red + i * 4) + ldsf(red + (200 + i) * 4) + ldsf(red + (400 + i) * 4);
        if (i < 192) g_csum[ki * (3 * D_) + (i >> 6) * D_ + n * 64 + (i & 63)] = v;
        else g_wsq[ki * 96 + ((i - 192) >> 1) * 32 + n * 2 + (i & 1)] = v;
    }
    named_sync(2, 96);
    if (warp == 0) { ctr_arrive(&g_c0); ctr_wait(&g_c0, 128); }
    named_sync(2, 96);
}

__device__ __forceinline__ float pow2_inv(float b) {
    const int e = min(max((int)(__float_as_uint(b) >> 23) + 1, 20), 234);
    return __uint_as_float((uint32_t)(254 - e) << 23);
}
__device__ __forceinline__ void epi_inputs(int L) {
    const int t = tid_now() - 288, mt = cta_now() >> 4, nt = cta_now() & 15;
    float p[2][8], r0[3], r1[3];
    #pragma unroll
    for (int k = 0; k < 2; k++)
        #pragma unroll
        for (int q = 0; q < 8; q++) p[k][q] = __ldcg(g_csum + q * (3 * D_) + ((t + 96 * k) >> 6) * D_ + nt * 64 + ((t + 96 * k) & 63));
    #pragma unroll
    for (int k = 0; k < 2; k++) stsf(SB + OFF_CS + (t + 96 * k) * 4, ((p[k][0] + p[k][1]) + (p[k][2] + p[k][3])) + ((p[k][4] + p[k][5]) + (p[k][6] + p[k][7])));
    bool wait;
    uint32_t n = 0;
    do {
        wait = false;
        #pragma unroll
        for (int k = 0; k < 3; k++) {
            const int row = mt * 256 + min(t + 96 * k, 255);
            if (L == 0) { const float2 s = __ldcg(&g_rs0[row]); r0[k] = s.x; r1[k] = s.y; }
            else { const uint4 s = ld_relaxed4(&g_sums[0][row]); r0[k] = __uint_as_float(s.x); r1[k] = __uint_as_float(s.y); wait = wait || s.w != STAT_FULL; }
        }
    } while (wait && ++n < SPIN_MAX);
    #pragma unroll
    for (int k = 0; k < 3; k++) {
        if (L != 0) {
            const float mean = r0[k] * (1.f / D_);
            const float var = fmaxf(r1[k] * (1.f / D_) - mean * mean, 0.f);
            const float a = 1.f + rsqrtf(var + LN_EPS);
            r0[k] = a * rsqrtf(a * a * var + LN_EPS); r1[k] = mean;
        }
        if (t + 96 * k < 256) sts64f(SB + OFF_RC + (t + 96 * k) * 8, r0[k], r1[k]);
    }
    if (L == 0 && t < 32) {
        float z = 0.f;
        if (t < 6) {
            #pragma unroll
            for (int q = 0; q < 8; q++) z += __ldcg(g_wsq + q * 96 + (t >> 1) * 32 + nt * 2 + (t & 1));
        }
        const float b = sqrtf(z) * (t < 2 ? 34.f * QSCALE : 34.f);
        const float sc = t < 4 ? fminf(pow2_inv(b) * 32768.f, 1.f) : pow2_inv(b);
        const float bk = __shfl_down_sync(0xffffffffu, b, 2), sk = __shfl_down_sync(0xffffffffu, sc, 2);
        if (t < 6) stsf(SB + OFF_M + M_SC + t * 4, t < 2 ? sc * QSCALE : sc);
        if (t < 2) { stsf(SB + OFF_M + M_ISC + t * 4, 1.f / (sc * sk)); sts32(SB + OFF_M + M_OK + t * 4, sc == 1.f && sk == 1.f && b * bk < 60000.f ? CH_OK : 0u); }
        if (t == 4 || t == 5) stsf(SB + OFF_M + M_IVS + (t - 4) * 4, 1.f / sc);
    }
}

__device__ __forceinline__ int ypos_col(int p) { return (p >> 7) * 128 + ((p >> 1) & 7) * 16 + (p & 1) * 8 + ((p >> 4) & 7); }

#define YD 200
template <int NT>
__device__ __forceinline__ float ffn_finish(int L, const RouteOut& rt, int t, uint32_t red, int bid) {
    constexpr int NL = (2 * NFC + NT - 1) / NT;
    const int c = cta_now(), col = ypos_col(c * 8 + (t & 7));
    const uint32_t* src = &g_ypart[L][t >> 1][c * 8 + (t & 1) * 4];
    uint32_t n = 0, xp;
    uint4 v[NL];
    bool wait;
    if (NT == 256 && YD) __nanosleep(YD);
    do {
        wait = false;
        xp = ld_relaxed(&g_xrow[L][rt.idx >> 7][((col >> 5) & 7) * 64 + (col >> 8) * 16 + (col & 6) * 2 + ((col >> 3) & 3)]);
        #pragma unroll
        for (int i = 0; i < NL; i++) v[i] = t + NT * i < 2 * NFC ? ld_relaxed4(src + i * (NT / 2) * D_) : make_uint4(0u, 0u, 0u, 0u);
        #pragma unroll
        for (int i = 0; i < NL; i++) wait = wait || has_sent(v[i]);
    } while ((wait || xp == SENT) && ++n < SPIN_MAX);
    spin_check(n);
    __syncwarp();
    float a[4] = {0.f, 0.f, 0.f, 0.f};
    #pragma unroll
    for (int i = 0; i < NL; i++) { a[0] += __uint_as_float(v[i].x); a[1] += __uint_as_float(v[i].y); a[2] += __uint_as_float(v[i].z); a[3] += __uint_as_float(v[i].w); }
    const bool b1 = t & 2, b2 = t & 4;
    a[0] = (b1 ? a[1] : a[0]) + __shfl_xor_sync(0xffffffffu, b1 ? a[0] : a[1], 2);
    a[2] = (b1 ? a[3] : a[2]) + __shfl_xor_sync(0xffffffffu, b1 ? a[2] : a[3], 2);
    a[0] = (b2 ? a[2] : a[0]) + __shfl_xor_sync(0xffffffffu, b2 ? a[0] : a[2], 4);
    a[0] += __shfl_xor_sync(0xffffffffu, a[0], 8); a[0] += __shfl_xor_sync(0xffffffffu, a[0], 16);
    if ((t & 31) < 8) stsf(red + (t >> 5) * 32 + (t & 1) * 16 + (t & 6) * 2, a[0]);
    const float xv = (col & 1) ? bf_hi(xp) : bf_lo(xp);
    const float rsel = bf_round(__fdividef(1.f, 1.f + __expf(-bf_round(rt.r)))), xn = bf_round((xv - rt.mean) * rt.rstd);
    named_sync(bid, NT);
    float y = 0.f;
    #pragma unroll
    for (int i = 0; i < NT / 32; i++) y += ldsf(red + i * 32 + (t & 7) * 4);
    return bf_round(xv + bf_round(xn + bf_round(bf_round(y) * rsel)));
}

__device__ __forceinline__ void routed_qkv(int ridx) {
    const int t = tid_now() - 288, c = cta_now(), lane = t & 31, warp = t >> 5;
    constexpr uint32_t red = SB + OFF_RED;
    {
        uint4 v[3];
        uint32_t n = 0;
        do {
            v[0] = ld_relaxed4(g_x2row + t * 4); v[1] = ld_relaxed4(g_x2row + (t + 96) * 4);
            v[2] = t < 64 ? ld_relaxed4(g_x2row + (t + 192) * 4) : make_uint4(0u, 0u, 0u, 0u);
        } while ((has_sent(v[0]) || has_sent(v[1]) || has_sent(v[2])) && ++n < SPIN_MAX);
        spin_check(n);
        __syncwarp();
        TL(288, 0, 21);
        float f[12];
        float s = 0.f;
        #pragma unroll
        for (int i = 0; i < 3; i++) { f[4*i] = __uint_as_float(v[i].x); f[4*i+1] = __uint_as_float(v[i].y); f[4*i+2] = __uint_as_float(v[i].z); f[4*i+3] = __uint_as_float(v[i].w); }
        #pragma unroll
        for (int i = 0; i < 12; i++) s += f[i];
        s = warp_sum(s);
        if (lane == 0) stsf(red + warp * 4, s);
        named_sync(2, 96);
        const float mean = (ldsf(red) + ldsf(red + 4) + ldsf(red + 8)) * (1.f / D_);
        float q = 0.f;
        #pragma unroll
        for (int i = 0; i < 12; i++) { f[i] -= mean; if (i < 8 || t < 64) q = fmaf(f[i], f[i], q); }
        q = warp_sum(q);
        if (lane == 0) stsf(red + 16 + warp * 4, q);
        named_sync(2, 96);
        const float rstd = rsqrtf((ldsf(red + 16) + ldsf(red + 20) + ldsf(red + 24)) * (1.f / D_) + LN_EPS);
        #pragma unroll
        for (int i = 0; i < 3; i++)
            if (i < 2 || t < 64) sts128(SB + OFF_XS + (t + 96 * i) * 16, make_uint4(pack_bf16(0.f, f[4*i] * rstd), pack_bf16(0.f, f[4*i+1] * rstd), pack_bf16(0.f, f[4*i+2] * rstd), pack_bf16(0.f, f[4*i+3] * rstd)));
    }
    named_sync(2, 96);
    TL(288, 0, 22);
    mbar_wait(B_SW, 0);
    TL(288, 0, 23);
    float a[8];
    #pragma unroll
    for (int i = 0; i < 8; i++) a[i] = 0.f;
    const uint32_t wa = SB + OFF_SIDE + t * 16, xa = SB + OFF_XS + (t / 3) * 4;
    #pragma unroll 4
    for (int i = 0; i < 32; i++) {
        const uint4 u = lds128(wa + i * 1536);
        const float xv = ldsf(xa + i * 128);
        a[0] = fmaf(xv, bf_lo(u.x), a[0]); a[1] = fmaf(xv, bf_hi(u.x), a[1]); a[2] = fmaf(xv, bf_lo(u.y), a[2]); a[3] = fmaf(xv, bf_hi(u.y), a[3]);
        a[4] = fmaf(xv, bf_lo(u.z), a[4]); a[5] = fmaf(xv, bf_hi(u.z), a[5]); a[6] = fmaf(xv, bf_lo(u.w), a[6]); a[7] = fmaf(xv, bf_hi(u.w), a[7]);
    }
    named_sync(2, 96);
    TL(288, 0, 41);
    sts128(SB + OFF_SIDE + t * 32, make_uint4(__float_as_uint(a[0]), __float_as_uint(a[1]), __float_as_uint(a[2]), __float_as_uint(a[3])));
    sts128(SB + OFF_SIDE + t * 32 + 16, make_uint4(__float_as_uint(a[4]), __float_as_uint(a[5]), __float_as_uint(a[6]), __float_as_uint(a[7])));
    named_sync(2, 96);
    {
        float y = 0.f;
        #pragma unroll
        for (int i = 0; i < 8; i++) y += ldsf(SB + OFF_SIDE + ((t & 3) * 8 + i) * 96 + (t >> 2) * 4);
        y += __shfl_xor_sync(0xffffffffu, y, 1); y += __shfl_xor_sync(0xffffffffu, y, 2);
        if ((t & 3) == 0) st_relaxed(g_fix + c * 24 + (t >> 2), not_sent(y));
    }
    if ((ridx >> 8) == (c >> 4) && t < 24) {
        const uint32_t* src = g_fix + (t >> 3) * D_ + (c & 15) * 64 + (t & 7) * 8;
        uint4 a, b;
        uint32_t n = 0;
        do { a = ld_relaxed4(src); b = ld_relaxed4(src + 4); } while ((has_sent(a) || has_sent(b)) && ++n < SPIN_MAX);
        spin_check(n);
        const int hh = t >> 2, ch = t & 3, lr = ridx & 255;
        const float hs = ldsf(SB + OFF_M + M_SC + hh * 4);
        sts128(SB + OFF_FIX + t * 16, make_uint4(pack_f16(__uint_as_float(a.x) * hs, __uint_as_float(a.y) * hs), pack_f16(__uint_as_float(a.z) * hs, __uint_as_float(a.w) * hs),
                                                 pack_f16(__uint_as_float(b.x) * hs, __uint_as_float(b.y) * hs), pack_f16(__uint_as_float(b.z) * hs, __uint_as_float(b.w) * hs)));
        sts32(SB + OFF_FIX + 512 + t * 4, SB + (hh < 2 ? OFF_QA + hh * 16384 + (lr >> 6) * 4096 + ch * 1024 + (lr & 63) * 16
                                                        : (hh & 1) * OFF_FE + (hh >> 2) * 16384 + ch * 4096 + lr * 16));
    }
    __syncwarp();
}

__device__ __forceinline__ void residual_prep() {
    const int t = tid_now() - 288, c = cta_now(), row0 = (c >> 4) * 256 + (c & 1) * 128, col0 = ((c & 15) >> 1) * 128;
    for (int i = t; i < 128; i += 96) {
        const float2 s = __ldcg(reinterpret_cast<const float2*>(&g_sums[0][row0 + i]));
        const float mean = s.x * (1.f / D_);
        const float rstd = rsqrtf(fmaxf(s.y * (1.f / D_) - mean * mean, 0.f) + LN_EPS);
        sts64f(SB + OFF_PART + i * 8, rstd, -mean * rstd);
    }
    named_sync(2, 96);
    #pragma unroll 2
    for (int i = t; i < 2048; i += 96) {
        const uint4 u = lds128(SB + OFF_XT + i * 16);
        const float2 r = lds64f(SB + OFF_PART + ((i >> 3) & 127) * 8);
        sts128(SB + OFF_XT + i * 16, make_uint4(add_ln2(u.x, r.x, r.y), add_ln2(u.y, r.x, r.y), add_ln2(u.z, r.x, r.y), add_ln2(u.w, r.x, r.y)));
    }
    const uint32_t lr = lds32(SB + OFF_M + M_RIDX) - row0;
    if (lr < 128u) {
        named_sync(2, 96);
        if (t < 16) {
            const uint4 a = ld_relaxed4(g_x2row + col0 + t * 8), b = ld_relaxed4(g_x2row + col0 + t * 8 + 4);
            sts128(SB + OFF_XT + (t >> 3) * 16384 + lr * 128 + (((t & 7) ^ (lr & 7)) << 4),
                   make_uint4(__byte_perm(a.x, a.y, 0x7632), __byte_perm(a.z, a.w, 0x7632), __byte_perm(b.x, b.y, 0x7632), __byte_perm(b.z, b.w, 0x7632)));
        }
    }
    __syncwarp();
}

#define XPF 1
#define XP0 2
#define XP1 7
#define FW_NS 1000
__device__ __forceinline__ void ffn_load(const Maps& mp, int i, uint32_t dst, uint32_t bar) {
    if (i < 8) tma_load(dst, (i & 1) ? &mp.u : &mp.g, blockIdx.x * 32, (i >> 1) * 256, bar);
    else tma_load3(dst, &mp.d, 0, blockIdx.x * 32, (i - 8) * 4, bar);
}
__device__ __forceinline__ void side_role(const Maps& mp, const bf16* __restrict__ x0, const bf16* __restrict__ wo, const bf16* __restrict__ w_r) {
    prep_work(x0, &mp.w64, threadIdx.x - 288);
    epi_inputs(0);
    #pragma unroll 1
    for (int L = 0; L < 2; L++) {
        const int t = tid_now() - 288, lane = t & 31, sw = warp_uniform(t >> 5);
        const int c = blockIdx.x, mt = c >> 4, nt = c & 15;
        named_sync(2, 96);
        if (t == 0) mbar_arrive(B_EPI);
        TL(288, L, 5);
        if (L == 0) {
            float ws = 0.f;
            for (int i = t; i < D_ / 8; i += 96) {
                const uint4 v = reinterpret_cast<const uint4*>(w_r)[i];
                ws += ((bf_lo(v.x) + bf_hi(v.x)) + (bf_lo(v.y) + bf_hi(v.y))) + ((bf_lo(v.z) + bf_hi(v.z)) + (bf_lo(v.w) + bf_hi(v.w)));
            }
            ws = warp_sum(ws);
            if (lane == 0) stsf(SB + OFF_M + M_WS + sw * 4, ws);
            if (t < 66) sts32(SB + OFF_WR + t * 4, t < 64 ? reinterpret_cast<const uint32_t*>(w_r)[(nt >> 1) * 64 + (t >> 3) * 8 + (t & 1) * 4 + ((t >> 1) & 3)] : 0x3F803F80u);
        }
        __syncwarp();
        if (sw == 0) {
            char* kv = g_kv + (size_t)(nt * 16 + mt) * KV_WIN;
            mbar_wait(B_KV0, L);
            bulk_store(kv, SB, KV_WIN);
            bulk_commit();
            publish(&g_kvc[L][nt * 2][mt]);
            TL(288, L, 6);
            named_sync(N_KV1, 64);
            bulk_store(kv + 8 * KV_WIN, SB + OFF_FE, KV_WIN);
            bulk_commit();
            publish(&g_kvc[L][nt * 2 + 1][mt]);
        }
        if (sw < 2) {
            #pragma unroll 1
            for (int p = 0; p < 2; p++) {
                named_sync(N_OST + 2 * p + sw, 160);
                bulk_store(g_o + (size_t)(((mt * 2 + sw) * 2 + p) * 16 + nt) * 8192, SB + OFF_QA + p * 16384 + sw * 8192, 8192);
                bulk_commit();
                TL(p ? -1 : 288, L, 30); TL(p ? 288 : -1, L, 31);
                if (p == 1) { bulk_wait_read(); mbar_arrive_elect(B_QAF); }
                publish(&g_oc[L][mt * 2 + sw][p]);
            }
        } else {
            named_sync(N_FW, 64);
            mbar_expect_tx(B_RES, 32768);
            #pragma unroll
            for (int i = 0; i < 4; i++) tma_load(SB + OFF_XT + i * 8192, L == 0 ? &mp.x0 : &mp.x, (nt >> 1) * 128 + (i >> 1) * 64, mt * 256 + (nt & 1) * 128 + (i & 1) * 64, B_RES);
            l2_prefetch(reinterpret_cast<const char*>(wo) + (size_t)c * 16384, 16384);
            if (c < NFC) {
                #pragma unroll 1
                for (int r = 0; r < 4; r++) {
                    __nanosleep(FW_NS);
                    if (r > 0) mbar_wait(B_FW, (r + L) & 1);
                    const uint32_t bar = r < 3 ? B_FW : B_FE;
                    mbar_expect_tx(bar, 3 * 16384);
                    #pragma unroll 1
                    for (int b = 0; b < 3; b++) ffn_load(mp, 9 - 3 * r + b, SB + OFF_FE + b * 16384, bar);
                }
            }
        }
        named_sync(2, 96);
        if (sw == 2) {
            l2_prefetch(&g_ypart[L][0][0] + c * (NFC * 8), NFC * 32);
            l2_prefetch(&g_sums[L][c * 16], 256);
            l2_prefetch(&g_xrow[L][0][0] + c * 64, 256);
            l2_prefetch(&g_tab[L][0][0][0] + c * 2, 32);
            l2_prefetch(c < 32 ? &g_x2row[c * 32] : c < 40 ? &g_kvc[1][(c - 32) * 4][0] : c == 40 ? &g_oc[1][0][0] : &g_xc[0][0], c <= 40 ? 128 : 64);
            l2_prefetch(&g_fix[c * 24], 96);
        }
        mbar_wait(B_RES, L);
        if (L == 1) { residual_prep(); named_sync(2, 96); }
        if (t == 0) mbar_arrive(B_RES2);
        __syncwarp();
        if (sw < 2) {
            named_sync(N_XST + sw, 160);
            const int row0 = mt * 256 + (nt & 1) * 128 + sw * 64, col0 = (nt >> 1) * 128;
            #pragma unroll 1
            for (int h = 0; h < 8; h++) {
                if (L == 0) bulk_wait_n<XP0>(); else bulk_wait_n<XP1>();
                tma_store(L == 0 ? &mp.xs : &mp.out, SB + OFF_XT + (h & 1) * 16384 + sw * 8192 + (h >> 1) * 2048, col0 + (h & 1) * 64, row0 + (h >> 1) * 16);
                bulk_commit();
            }
            publish(&g_xc[L][mt]);
            TL(288, L, 14);
        }
        if (L == 0) {
            __syncwarp();
            named_sync(N_RT, 128);
            const RouteOut rt = route_out(lds128(SB + OFF_RT + 128));
            if (t == 0) { sts32(SB + OFF_M + M_RIDX, rt.idx); if (c == 0) g_c0 = 0u; }
            epi_inputs(1);
            const float v = ffn_finish<96>(0, rt, t, SB + OFF_RED, 2);
            TL(288, L, 20);
            if (t < 8) st_relaxed(g_x2row + ypos_col(c * 8 + t), not_sent(v));
            routed_qkv(rt.idx);
        }
    }
}

struct EpiIn { float2 c2[4]; float hs; };
template <int HH>
__device__ __forceinline__ EpiIn qkv_epi_in(int t) {
    EpiIn e;
    #pragma unroll
    for (int jj = 0; jj < 4; jj++) e.c2[jj] = lds64f(SB + OFF_CS + (HH * 32 + jj * 8) * 4 + t * 8);
    e.hs = ldsf(SB + OFF_M + M_SC + HH * 4);
    return e;
}
template <int HH, int NEXT>
__device__ __forceinline__ void qkv_epi_head(const float (&acc0)[96], const float (&acc1)[96], const float (&cf)[4], const float (&nm)[4], EpiIn& in, uint32_t dst, int t) {
    const EpiIn e = in;
    #pragma unroll
    for (int i = 0; i < 4; i++) {
        const float* a = (i >> 1) ? acc1 : acc0;
        const float sc = cf[i] * e.hs;
        uint32_t pk[4];
        #pragma unroll
        for (int jj = 0; jj < 4; jj++)
            pk[jj] = pack_f16(fmaf(nm[i], e.c2[jj].x, a[4 * (4 * HH + jj) + 2 * (i & 1)]) * sc, fmaf(nm[i], e.c2[jj].y, a[4 * (4 * HH + jj) + 2 * (i & 1) + 1]) * sc);
        stsm4(dst + (i >> 1) * (HH < 2 ? 4096 : 1024) + (i & 1) * 128, pk[0], pk[1], pk[2], pk[3]);
        if (i == 1 && NEXT >= 0) in = qkv_epi_in<NEXT < 0 ? 0 : NEXT>(t);
    }
}
__device__ __forceinline__ void qkv_patch(int lane, uint32_t mask) {
    const uint4 v = lds128(SB + OFF_FIX + lane * 16);
    const uint32_t dst = lds32(SB + OFF_FIX + 512 + lane * 4);
    __syncwarp();
    asm volatile("{\n.reg .pred q;\nsetp.ne.u32 q, %5, 0;\n@q st.shared.v4.b32 [%0], {%1, %2, %3, %4};\n}"
                 :: "r"(dst), "r"(v.x), "r"(v.y), "r"(v.z), "r"(v.w), "r"((mask >> lane) & 1) : "memory");
}

template <bool INIT>
__device__ __forceinline__ void qkv_step(float (&acc0)[96], float (&acc1)[96], uint32_t st, int wg) {
    const uint64_t da = desc_sw128(SB, 16, 1024) + ((st * Q_STB + wg * 16384) >> 4);
    const uint64_t db = desc_sw128(SB + Q_ABYTES, 8192, 1024) + ((st * Q_STB) >> 4);
    wg_fence();
    if (INIT) { wg_gemm_n192_init(acc0, da, db); wg_gemm_n192_init(acc1, da + (8192 >> 4), db); }
    #pragma unroll
    for (int kk = INIT ? 1 : 0; kk < 4; kk++) {
        wg_gemm_n192(acc0, da + kk * 2, db + kk * 128);
        wg_gemm_n192(acc1, da + (8192 >> 4) + kk * 2, db + kk * 128);
    }
    wg_commit();
}
__device__ __forceinline__ void qkv_phase(int L, int wg) {
    const uint32_t rb = L * 32;
    float acc0[96], acc1[96];
    const bool leader = (tid_now() & 127) == 0;
    mbar_wait(rb + B_QF, 0);
    TL(0, L, 1);
    qkv_step<true>(acc0, acc1, 0, wg);
    uint32_t st = 1, ph = 0;
    #pragma unroll 1
    for (int k = 1; k < 16; k++) {
        mbar_wait(rb + B_QF + 8 * st, ph);
        qkv_step<false>(acc0, acc1, st, wg);
        wg_wait<1>();
        if (leader) mbar_arrive(rb + B_QE + 8 * (st == 0 ? 2 : st - 1));
        if (++st == 3) { st = 0; ph ^= 1; }
    }
    const int tid = tid_now(), lane = tid & 31, w = (tid >> 5) & 3, g = lane >> 2, t = lane & 3;
    mbar_wait(B_EPI, L);
    float cf[4], nm[4];
    #pragma unroll
    for (int i = 0; i < 4; i++) { const float2 r = lds64f(SB + OFF_RC + (wg * 128 + w * 16 + g + (i >> 1) * 64 + (i & 1) * 8) * 8); cf[i] = r.x; nm[i] = -r.y; }
    const int d = (int)lds32(SB + OFF_M + M_RIDX) - (cta_now() >> 4) * 256;
    const bool own = L == 1 && (d >> 7) == wg && ((d >> 4) & 3) == w;
    EpiIn in = qkv_epi_in<2>(t);
    wg_wait<0>();
    TL(0, L, 2);
    TL(128, L, 40);
    named_sync(1, 256);
    const uint32_t dk = SB + wg * 2048 + (lane >> 3) * 4096 + (w * 16 + (lane & 7)) * 16;
    const uint32_t dq = SB + OFF_QA + wg * 8192 + (lane >> 3) * 1024 + (w * 16 + (lane & 7)) * 16;
    qkv_epi_head<2, 4>(acc0, acc1, cf, nm, in, dk, t);
    qkv_epi_head<4, 0>(acc0, acc1, cf, nm, in, dk + 16384, t);
    if (own) qkv_patch(lane, 0x0F0F00u);
    #pragma unroll
    for (int s = 0; s < 3; s++) sts128(SB + s * A_WIN + KV_WIN + tid * 16, make_uint4(0x3C003C00u, 0x3C003C00u, 0x3C003C00u, 0x3C003C00u));
    fence_async_smem();
    __syncwarp();
    mbar_arrive_elect(B_KV0);
    TL(0, L, 4);
    qkv_epi_head<0, 1>(acc0, acc1, cf, nm, in, dq, t);
    qkv_epi_head<1, 3>(acc0, acc1, cf, nm, in, dq + 16384, t);
    qkv_epi_head<3, 5>(acc0, acc1, cf, nm, in, dk + OFF_FE, t);
    qkv_epi_head<5, -1>(acc0, acc1, cf, nm, in, dk + OFF_FE + 16384, t);
    if (own) qkv_patch(lane, 0xF0F0FFu);
    fence_async_smem();
    named_sync(3 + wg, 128);
    TL(0, L, 3);
}

struct Unit {
    uint32_t o[10];
    uint32_t bz[2];
    uint32_t sc[2];
    uint32_t ch[2];
};
__device__ __forceinline__ uint32_t hmax2(uint32_t a, uint32_t b) { uint32_t r; asm("max.f16x2 %0, %1, %2;" : "=r"(r) : "r"(a), "r"(b)); return r; }
__device__ __forceinline__ uint32_t hadd2(uint32_t a, uint32_t b) { uint32_t r; asm("add.rn.f16x2 %0, %1, %2;" : "=r"(r) : "r"(a), "r"(b)); return r; }
__device__ __forceinline__ uint32_t hsub2(uint32_t a, uint32_t b) { uint32_t r; asm("sub.rn.f16x2 %0, %1, %2;" : "=r"(r) : "r"(a), "r"(b)); return r; }
__device__ __forceinline__ uint32_t hfma2(uint32_t a, uint32_t b, uint32_t c) { uint32_t r; asm("fma.rn.f16x2 %0, %1, %2, %3;" : "=r"(r) : "r"(a), "r"(b), "r"(c)); return r; }
__device__ __forceinline__ uint32_t exp2_h2(uint32_t s, uint32_t bz, uint32_t& ch) {
    uint32_t z, w, d;
    asm("fma.rn.relu.f16x2 %0, %1, %2, %3;" : "=r"(z) : "r"(s), "r"(0x00400040u), "r"(bz));
    asm("lop3.b32 %0, %1, 0x003F003F, %0, 0xC2;" : "+r"(ch) : "r"(z));
    asm("fma.rn.f16x2 %0, %1, %2, %3;" : "=r"(w) : "r"(ch), "r"(0x30A630A6u), "r"(0xACCCACCCu));
    asm("{.reg .b32 n; neg.f16x2 n, %1; fma.rn.relu.f16x2 %0, n, %1, %2;}" : "=r"(d) : "r"(w), "r"(0x00580058u));
    return (z << 4) - d;
}
__device__ __forceinline__ void exp_tile(uint32_t (&p)[32], const uint32_t (&s)[32], Unit& u) {
    #pragma unroll
    for (int i = 0; i < 32; i++) p[i] = exp2_h2(s[i], u.bz[i & 1], u.ch[i & 1]);
}
__device__ __forceinline__ void issue_qk(uint32_t (&s)[32], uint64_t dq, uint64_t dk) {
    wg_qk_init(s, dq, dk); wg_qk_acc(s, dq + (2048 >> 4), dk + (8192 >> 4));
    wg_commit();
}
template <bool INIT>
__device__ __forceinline__ void issue_pv(uint32_t (&h)[10], const uint32_t (&p)[32], uint64_t dv) {
    #pragma unroll
    for (int k = 0; k < 8; k++) {
        if (INIT && k == 0) wg_pv_init(h, p[0], p[1], p[2], p[3], dv);
        else wg_pv_acc(h, p[4*k], p[4*k+1], p[4*k+2], p[4*k+3], dv + k * 16);
    }
    wg_commit();
}
__device__ __forceinline__ void unit_init(Unit& u, const uint32_t (&s)[32], uint32_t ok) {
    uint32_t m0 = s[0], m1 = s[1];
    #pragma unroll
    for (int i = 1; i < 16; i++) { m0 = hmax2(m0, s[2 * i]); m1 = hmax2(m1, s[2 * i + 1]); }
    uint32_t m = hmax2(__byte_perm(m0, m1, 0x5410), __byte_perm(m0, m1, 0x7632));
    m = hmax2(m, __shfl_xor_sync(0xffffffffu, m, 1)); m = hmax2(m, __shfl_xor_sync(0xffffffffu, m, 2));
    float f0, f1; h2_unpack(m, f0, f1);
    u.ch[0] = fabsf(f0) < 1000.f ? ok : 0u; u.ch[1] = fabsf(f1) < 1000.f ? ok : 0u;
    f0 = (18.f - ceilf(f0)) * 3.814697265625e-06f; f1 = (18.f - ceilf(f1)) * 3.814697265625e-06f;
    u.bz[0] = pack_f16(f0, f0); u.bz[1] = pack_f16(f1, f1);
    u.sc[0] = u.sc[1] = 0x3C003C00u;
    #pragma unroll
    for (int i = 0; i < 10; i++) u.o[i] = 0u;
}
template <bool MORE>
__device__ __forceinline__ void unit_flush(Unit& u, const uint32_t (&h)[10]) {
    #pragma unroll
    for (int i = 0; i < 10; i++) u.o[i] = hfma2(u.o[i], u.sc[i & 1], h[i]);
    if (MORE) {
        #pragma unroll
        for (int r = 0; r < 2; r++) {
            const uint32_t ex = u.o[8 + r] & 0x7C007C00u;
            u.sc[r] = 0x84008400u - ex;
            u.bz[r] = hsub2(hadd2(u.bz[r], 0x04800480u), ex >> 4);
        }
    }
}
__device__ __forceinline__ uint32_t unit_store(const Unit& u, uint32_t dst, float ivs, int lane) {
    uint32_t bad = 0;
    #pragma unroll
    for (int h = 0; h < 2; h++) {
        uint32_t b = __ballot_sync(0xffffffffu, (~u.ch[h] & CH_OK) != 0 || u.o[8 + h] - 0x40000000u >= 0x3C000000u);
        b |= b >> 1; b = (b | b >> 2) & 0x11111111u;
        float lf, unused; h2_unpack(u.o[8 + h], lf, unused);
        const float inv = ivs * rcp(lf);
        uint32_t pk[4];
        #pragma unroll
        for (int j = 0; j < 4; j++) { float x, y; h2_unpack(u.o[2 * j + h], x, y); pk[j] = pack_bf16(x * inv, y * inv); }
        stsm4((b >> (4 * (lane & 7))) & 1 ? SB + OFF_RT : dst + h * 128, pk[0], pk[1], pk[2], pk[3]);
        bad |= b << h;
    }
    return bad;
}
__device__ __noinline__ void exact_rows(int L, int pass, int wg, uint32_t bad) {
    const int tid = tid_now() & 127, lane = tid & 31, w = tid >> 5;
    const int head = (cta_now() & 15) * 2 + pass;
    const uint32_t scr = SB + OFF_PART + wg * 1024;
    if (lane == 0) sts32(scr + w * 4, bad);
    if (tid < 8) ctr_wait(&g_kvc[L][head][tid], 1);
    named_sync(3 + wg, 128);
    const float isc = ldsf(SB + OFF_M + M_ISC + pass * 4), ivs = ldsf(SB + OFF_M + M_IVS + pass * 4);
    const char* kv = g_kv + (size_t)head * 8 * KV_WIN + tid * 16;
    #pragma unroll 1
    for (int ww = 0; ww < 4; ww++) {
        uint32_t m = lds32(scr + ww * 4);
        #pragma unroll 1
        while (m) {
            const int bit = __ffs(m) - 1;
            m &= m - 1;
            const uint32_t qa = SB + OFF_QA + pass * 16384 + (wg * 2 + ((bit >> 1) & 1)) * 4096 + (ww * 16 + (bit & 1) * 8 + (bit >> 2)) * 16;
            float q[32], a[32], mx = -INFINITY, l = 0.f;
            #pragma unroll
            for (int ch = 0; ch < 4; ch++) {
                const uint4 u = lds128(qa + ch * 1024);
                h2_unpack(u.x, q[8*ch], q[8*ch+1]); h2_unpack(u.y, q[8*ch+2], q[8*ch+3]); h2_unpack(u.z, q[8*ch+4], q[8*ch+5]); h2_unpack(u.w, q[8*ch+6], q[8*ch+7]);
            }
            #pragma unroll
            for (int i = 0; i < 32; i++) a[i] = 0.f;
            #pragma unroll 1
            for (int it = 0; it < 16; it += 4) {
                uint4 u[4][8];
                #pragma unroll
                for (int i = 0; i < 4; i++)
                    #pragma unroll
                    for (int ch = 0; ch < 8; ch++) u[i][ch] = __ldcg(reinterpret_cast<const uint4*>(kv + ((it + i) >> 1) * KV_WIN + (i & 1) * 2048 + ch * 4096));
                float s[4], mn = mx;
                #pragma unroll
                for (int i = 0; i < 4; i++) {
                    s[i] = 0.f;
                    #pragma unroll
                    for (int ch = 0; ch < 4; ch++) {
                        const uint32_t v[4] = {u[i][ch].x, u[i][ch].y, u[i][ch].z, u[i][ch].w};
                        #pragma unroll
                        for (int e = 0; e < 4; e++) { float x, y; h2_unpack(v[e], x, y); s[i] = fmaf(x, q[8*ch + 2*e], fmaf(y, q[8*ch + 2*e + 1], s[i])); }
                    }
                    mn = fmaxf(mn, s[i]);
                }
                const float al = ex2((mx - mn) * isc);
                mx = mn; l *= al;
                #pragma unroll
                for (int i = 0; i < 32; i++) a[i] *= al;
                #pragma unroll
                for (int i = 0; i < 4; i++) {
                    const float p = ex2((s[i] - mx) * isc);
                    l += p;
                    #pragma unroll
                    for (int ch = 0; ch < 4; ch++) {
                        const uint32_t v[4] = {u[i][4 + ch].x, u[i][4 + ch].y, u[i][4 + ch].z, u[i][4 + ch].w};
                        #pragma unroll
                        for (int e = 0; e < 4; e++) { float x, y; h2_unpack(v[e], x, y); a[8*ch + 2*e] = fmaf(p, x, a[8*ch + 2*e]); a[8*ch + 2*e + 1] = fmaf(p, y, a[8*ch + 2*e + 1]); }
                    }
                }
            }
            const float mw = warp_max(mx);
            if (lane == 0) stsf(scr + 16 + w * 4, mw);
            named_sync(3 + wg, 128);
            const float al = ex2((mx - fmaxf(fmaxf(ldsf(scr + 16), ldsf(scr + 20)), fmaxf(ldsf(scr + 24), ldsf(scr + 28)))) * isc);
            l *= al;
            #pragma unroll
            for (int i = 0; i < 32; i++) a[i] *= al;
            l = warp_sum(l);
            #pragma unroll
            for (int j = 0; j < 31; j++) {
                const int o = j < 16 ? 16 : j < 24 ? 8 : j < 28 ? 4 : j < 30 ? 2 : 1, i = j - (32 - 2 * o);
                const bool up = lane & o;
                const float lo = a[i], hi = a[i + o];
                a[i] = (up ? hi : lo) + __shfl_xor_sync(0xffffffffu, up ? lo : hi, o);
            }
            stsf(scr + 32 + (w * 33 + lane) * 4, a[0]);
            if (lane == 0) stsf(scr + 32 + (w * 33 + 32) * 4, l);
            named_sync(3 + wg, 128);
            if (w == 0) {
                float o = 0.f, ls = 0.f;
                #pragma unroll
                for (int i = 0; i < 4; i++) { o += ldsf(scr + 32 + (i * 33 + lane) * 4); ls += ldsf(scr + 32 + (i * 33 + 32) * 4); }
                asm volatile("st.shared.u16 [%0], %1;" :: "r"(qa + (lane >> 3) * 1024 + (lane & 7) * 2), "h"((unsigned short)(pack_bf16(o * ivs / ls, 0.f))) : "memory");
            }
        }
    }
    named_sync(3 + wg, 128);
}

__device__ __forceinline__ void attention_phase(int L, int wg) {
    const uint32_t rb = L * 32;
    constexpr uint64_t dk0 = desc_plain(SB, 4096, 128), dv0 = desc_plain(SB + 16384, 128, 4096);
    constexpr int T1 = 2048 >> 4;
    uint32_t st = 0, ph = 0;
    #pragma unroll 1
    for (int pass = 0; pass < 2; pass++) {
        const uint64_t dqa = desc_plain(SB + OFF_QA, 1024, 128) + (pass * 4 + wg * 2) * (4096 >> 4), dqc = dqa + (4096 >> 4);
        Unit a, c;
        st = warp_uniform(st); ph = warp_uniform(ph);
        uint32_t SA[32], SC[32], PA[32], PC[32], ha[10], hc[10], bad;
        #pragma unroll
        for (int i = 0; i < 10; i++) hc[i] = 0u;
        #pragma unroll
        for (int i = 0; i < 32; i++) PC[i] = 0u;
        const uint32_t ok = lds32(SB + OFF_M + M_OK + pass * 4);
        mbar_wait(rb + B_AF + 8 * st, ph);
        wg_fence();
        issue_qk(SA, dqa, dk0 + st * (A_WIN >> 4));
        issue_qk(SC, dqc, dk0 + st * (A_WIN >> 4));
        wg_wait<1>();
        unit_init(a, SA, ok);
        exp_tile(PA, SA, a);
        wg_wait<0>();
        unit_init(c, SC, ok);
        uint32_t eb = 0;
        #pragma unroll 1
        for (int s = 0;; s++) {
            const uint64_t dkb = dk0 + st * (A_WIN >> 4), dvb = dv0 + st * (A_WIN >> 4);
            if (__builtin_expect(s == 8 * gridDim.y, 0)) {
                wg_wait<0>();
                bad = 0;
                #pragma unroll
                for (int i = 0; i < 32; i++) bad |= PC[i];
                break;
            }
            wg_fence();
            issue_pv<true>(ha, PA, dvb); issue_qk(SA, dqa, dkb + T1);
            wg_wait<2>();
            if (s > 0) { mbar_arrive_elect(eb); unit_flush<true>(c, hc); }
            exp_tile(PC, SC, c);
            wg_fence();
            issue_pv<true>(hc, PC, dvb); issue_qk(SC, dqc, dkb + T1);
            wg_wait<2>();
            exp_tile(PA, SA, a);
            eb = rb + B_AE + 8 * st;
            if (++st == 3) { st = 0; ph ^= 1; }
            if (s == 7) {
                wg_fence(); issue_pv<false>(ha, PA, dvb + T1);
                wg_wait<1>();
                exp_tile(PC, SC, c);
                wg_fence(); issue_pv<false>(hc, PC, dvb + T1);
                wg_wait<1>();
                const int tid = tid_now(), lane = tid & 31;
                const float ivs = ldsf(SB + OFF_M + M_IVS + pass * 4);
                const uint32_t dst = SB + OFF_QA + pass * 16384 + wg * 8192 + (lane >> 3) * 1024 + (((tid >> 5) & 3) * 16 + (lane & 7)) * 16;
                unit_flush<false>(a, ha);
                bad = unit_store(a, dst, ivs, lane);
                wg_wait<0>();
                mbar_arrive_elect(eb);
                unit_flush<false>(c, hc);
                bad |= unit_store(c, dst + 4096, ivs, lane) << 2;
                break;
            }
            const uint64_t dkn = dk0 + st * (A_WIN >> 4);
            mbar_wait(rb + B_AF + 8 * st, ph);
            wg_fence();
            issue_pv<false>(ha, PA, dvb + T1); issue_qk(SA, dqa, dkn);
            wg_wait<2>();
            exp_tile(PC, SC, c);
            wg_fence();
            issue_pv<false>(hc, PC, dvb + T1); issue_qk(SC, dqc, dkn);
            wg_wait<2>();
            unit_flush<true>(a, ha);
            exp_tile(PA, SA, a);
        }
        if (__builtin_expect(named_any(bad != 0, 3 + wg), 0)) {
            exact_rows(L, pass, wg, bad);
        }
        fence_async_smem();
        named_arrive(N_OST + 2 * pass + wg, 160);
        TL(pass ? -1 : 0, L, 8); TL(pass ? 0 : -1, L, 9);
    }
}

#define XS0 0
#define GDP 0
#define DDP 1

template <bool INIT>
__device__ __forceinline__ void oproj_step(float (&acc)[64], uint32_t s, int wg) {
    const uint64_t da = desc_plain(SB, 1024, 128) + ((o_stage(s) + wg * 4096) >> 4);
    const uint64_t db = desc_sw128(SB + 16384, 8192, 1024) + (o_stage(s) >> 4);
    wg_fence();
    if (INIT) wg_gemm_n128_init(acc, da, db);
    #pragma unroll
    for (int kk = INIT ? 1 : 0; kk < 4; kk++) wg_gemm_n128(acc, da + (kk >> 1) * 512 + (kk & 1) * 128, db + kk * 128);
    wg_commit();
}
__device__ __forceinline__ void oproj_phase(int L, int wg, bf16* __restrict__ out) {
    const int c = cta_now(), tid = tid_now(), lane = tid & 31, W = tid >> 5, g = lane >> 2, t = lane & 3;
    const int row0 = (c >> 4) * 256 + (c & 1) * 128, col0 = ((c & 15) >> 1) * 128;
    float acc[64];
    mbar_wait(B_OF, 0);
    TL(0, L, 10);
    oproj_step<true>(acc, 0, wg);
    #pragma unroll 1
    for (int k = 1; k < 16; k++) {
        mbar_wait(B_OF + 8 * (k & 3), (k >> 2) & 1);
        TL(k == 8 ? 0 : -1, L, 11);
        oproj_step<false>(acc, k & 3, wg);
        wg_wait<1>();
        if ((tid & 127) == 0) mbar_arrive(B_OE + 8 * ((k - 1) & 3));
    }
    mbar_wait(B_RES2, L);
    const uint32_t xa = SB + OFF_XT + (W * 16 + ((lane >> 3) & 1) * 8 + (lane & 7)) * 128, xs = (lane >> 4) ^ (lane & 7);
    uint32_t x[32];
    const uint32_t wra = SB + OFF_WR + (g == 0 ? t * 8 : 256), wrs = g == 0 ? 32 : 0;
    wg_wait<0>();
    if ((tid & 127) == 0) mbar_arrive(B_OE + 24);
    TL(0, L, 12);
    {
        float sd[4] = {0.f, 0.f, 0.f, 0.f}, q0[4] = {0.f, 0.f, 0.f, 0.f}, q1[4] = {0.f, 0.f, 0.f, 0.f};
        #pragma unroll
        for (int ks = 0; ks < 8; ks++) {
            ldsm4(x[4*ks], x[4*ks+1], x[4*ks+2], x[4*ks+3], xa + (ks >> 2) * 16384 + ((xs ^ ((ks & 3) * 2)) << 4));
            const float2 wb = lds64f(wra + ks * wrs);
            #pragma unroll
            for (int i = 0; i < 4; i++) x[4*ks + i] = badd2(x[4*ks + i], pack_bf16(acc[8*ks + 2*i], acc[8*ks + 2*i + 1]));
            mma_bf16(sd, x[4*ks], x[4*ks+1], x[4*ks+2], x[4*ks+3], __float_as_uint(wb.x), __float_as_uint(wb.y));
            mma_bf16(q0, x[4*ks], x[4*ks+1], x[4*ks+2], x[4*ks+3], x[4*ks], x[4*ks+2]);
            mma_bf16(q1, x[4*ks], x[4*ks+1], x[4*ks+2], x[4*ks+3], x[4*ks+1], x[4*ks+3]);
        }
        const float s0 = __shfl_sync(0xffffffffu, (g & 1) ? q0[1] : q0[0], 4 * g + (g >> 1));
        const float s1 = __shfl_sync(0xffffffffu, (g & 1) ? q1[3] : q1[2], 4 * g + (g >> 1));
        if (t == 0) {
            float4* p = &g_sums[L][row0 + W * 16 + g];
            asm volatile("red.relaxed.gpu.global.add.v4.f32 [%0], {%1, %2, %3, %4};" :: "l"(p), "f"(sd[1]), "f"(s0), "f"(sd[0]), "f"(1.f) : "memory");
            asm volatile("red.relaxed.gpu.global.add.v4.f32 [%0], {%1, %2, %3, %4};" :: "l"(p + 8), "f"(sd[3]), "f"(s1), "f"(sd[2]), "f"(1.f) : "memory");
        }
    }
    TL(0, L, 13);
    if (L == 0) {
        #pragma unroll
        for (int ks = 0; ks < 8; ks++) stsm4(xa + (ks >> 2) * 16384 + ((xs ^ ((ks & 3) * 2)) << 4), x[4*ks], x[4*ks+1], x[4*ks+2], x[4*ks+3]);
        fence_async_smem();
        if (XS0 == 0) named_arrive(N_XST + wg, 160);
    }
    const bool ffn = c < NFC;
    uint4 fa[32], fd[16];
    const uint32_t ga = SB + W * 2048 + ((lane >> 4) * 8 + (lane & 7)) * 64 + ((((lane >> 3) & 1) ^ ((lane >> 1) & 3)) << 4);
    if (ffn) mbar_wait(B_FE, L);
    #pragma unroll
    for (int i = 0; i < 12; i++) ldsm4t(fa[i].x, fa[i].y, fa[i].z, fa[i].w, (ga ^ ((i & 1) * 32)) + gu_piece(i >> 2) + (i & 2) * 512);
    float2 r0, r1;
    {
        const float ws = ldsf(SB + OFF_M + M_WS) + ldsf(SB + OFF_M + M_WS + 4) + ldsf(SB + OFF_M + M_WS + 8);
        const uint32_t row = row0 + W * 16 + g;
        uint4 s0 = make_uint4(0u, 0u, 0u, 0u), s1 = s0;
        uint32_t n = 0;
        do {
            ld_relaxed4_unless(s0, &g_sums[L][row], STAT_FULL); ld_relaxed4_unless(s1, &g_sums[L][row + 8], STAT_FULL);
        } while ((s0.w != STAT_FULL || s1.w != STAT_FULL) && ++n < SPIN_MAX);
        spin_check(n);
        __syncwarp();
        TL(0, L, 46);
        if (XS0 == 1 && L == 0) named_arrive(N_XST + wg, 160);
        r0 = ln_coef(s0); r1 = ln_coef(s1);
        const bool odd = t & 1;
        const float2 r = odd ? r1 : r0;
        const uint32_t k = min(order_bits(r.x * fmaf(-r.y, ws, __uint_as_float(odd ? s1.z : s0.z))), SENT - 1), me = row + (odd ? 8 : 0);
        const uint32_t m = redux_max(k), mrow = redux_min(k == m ? me : 0x7FFFFFFFu);
        if (me == mrow) sts128(SB + OFF_RT + W * 16, make_uint4(k, me, not_sent(r.y), not_sent(r.x)));
    }
    named_sync(1, 256);
    {
        const uint4 e = lds128(SB + OFF_RT + (lane & 7) * 16);
        const uint32_t m = redux_max(e.x), row = redux_min(e.x == m ? e.y : 0x7FFFFFFFu);
        const int lr = row - row0;
        st_relaxed4_if(&g_tab[L][(c & 15) >> 1][row0 >> 7][(lane >> 3) & 1], e, W == ((lr >> 4) ^ 1) && e.y == row && lane < 16);
        if ((lr >> 4) == W) {
            const bool hi = lr & 8;
            uint32_t* dst = &g_xrow[L][row0 >> 7][(col0 & 128) * 2 + (col0 >> 8) * 16 + t * 4];
            #pragma unroll
            for (int i = 0; i < 4; i++)
                st_relaxed4_if(dst + i * 64, make_uint4(min(hi ? x[8*i+1] : x[8*i], SENT - 1), min(hi ? x[8*i+3] : x[8*i+2], SENT - 1),
                               min(hi ? x[8*i+5] : x[8*i+4], SENT - 1), min(hi ? x[8*i+7] : x[8*i+6], SENT - 1)), g == (lr & 7));
        }
        __syncwarp();
    }
    TL(0, L, 15);
    if (XS0 == 2 && L == 0) named_arrive(N_XST + wg, 160);
    if (L == 1) {
        const float b0 = -r0.x * r0.y, b1 = -r1.x * r1.y;
        #pragma unroll
        for (int ks = 0; ks < 8; ks++)
            stsm4(xa + (ks >> 2) * 16384 + ((xs ^ ((ks & 3) * 2)) << 4), add_ln2(x[4*ks], r0.x, b0), add_ln2(x[4*ks+1], r1.x, b1),
                  add_ln2(x[4*ks+2], r0.x, b0), add_ln2(x[4*ks+3], r1.x, b1));
        fence_async_smem();
        named_arrive(N_XST + wg, 160);
    }
    TL(0, L, 45);
    RouteOut rt;
    {
        const uint4* tp = &g_tab[L][(c & 15) >> 1][lane & 15][0];
        uint4 e = ld_relaxed4(tp);
        if (ffn) mbar_wait(B_FL, L);
        #pragma unroll
        for (int i = 12; i < 32; i++) ldsm4t(fa[i].x, fa[i].y, fa[i].z, fa[i].w, (ga ^ ((i & 1) * 32)) + gu_piece(i >> 2) + (i & 2) * 512);
        if (L == 0 && GDP == 0) named_arrive(N_GD, 288);
        uint32_t n = 0;
        while (has_sent(e) && ++n < SPIN_MAX) e = ld_relaxed4(tp);
        spin_check(n);
        __syncwarp();
        e = warp_best(e);
        rt = route_out(e);
        if (W == 7 && L == 0) { sts128(SB + OFF_RT + 128, e); named_arrive(N_RT, 128); }
    }
    TL(0, L, 16);
    uint2 xrow;
    {
        const uint32_t* xp = &g_xrow[L][rt.idx >> 7][W * 64 + (g >> 1) * 16 + t * 4 + (g & 1) * 2];
        xrow = ld_relaxed2(xp);
        if (ffn) mbar_wait(B_FD, L);
        const uint32_t wa = SB + OFF_FD + W * 8192 + ((lane >> 4) * 8 + (lane & 7)) * 128 + ((((lane >> 3) & 1) ^ (lane & 7)) << 4);
        #pragma unroll
        for (int i = 0; i < 16; i++) ldsm4t(fd[i].x, fd[i].y, fd[i].z, fd[i].w, (wa ^ (((i >> 1) & 3) * 32)) + (i >> 3) * 4096 + (i & 1) * 2048);
        if (L == 0 && GDP == 1) named_arrive(N_GD, 288);
        if (L == 0 && DDP == 1) named_arrive(N_DD, 288);
        uint32_t n = 0;
        while ((xrow.x == SENT || xrow.y == SENT) && ++n < SPIN_MAX) xrow = ld_relaxed2(xp);
        spin_check(n);
        __syncwarp();
    }
    if (L == 0 && GDP == 2) named_arrive(N_GD, 288);
    if (L == 0 && DDP == 2) named_arrive(N_DD, 288);
    TL(0, L, 17);
    {
        const float nb = -rt.mean * rt.rstd;
        const uint32_t n0 = pack_bf16(fmaf(bf_lo(xrow.x), rt.rstd, nb), fmaf(bf_hi(xrow.x), rt.rstd, nb));
        const uint32_t n1 = pack_bf16(fmaf(bf_lo(xrow.y), rt.rstd, nb), fmaf(bf_hi(xrow.y), rt.rstd, nb));
        float gu[4][4];
        #pragma unroll
        for (int i = 0; i < 4; i++) { gu[i][0] = 0.f; gu[i][1] = 0.f; gu[i][2] = 0.f; gu[i][3] = 0.f; }
        #pragma unroll
        for (int ks = 0; ks < 8; ks++) {
            const uint32_t b0 = __shfl_sync(0xffffffffu, n0, 4 * ks + t), b1 = __shfl_sync(0xffffffffu, n1, 4 * ks + t);
            #pragma unroll
            for (int i = 0; i < 4; i++) {
                const uint4& a = fa[(ks >> 1) * 8 + (i >> 1) * 4 + (ks & 1) * 2 + (i & 1)];
                mma_bf16(gu[i], a.x, a.y, a.z, a.w, b0, b1);
            }
        }
        stsf(SB + OFF_PART + (W * 64 + t * 16 + g) * 4, sel4(t, gu[0][0], gu[1][0], gu[2][0], gu[3][0]));
        stsf(SB + OFF_PART + (W * 64 + t * 16 + g + 8) * 4, sel4(t, gu[0][2], gu[1][2], gu[2][2], gu[3][2]));
    }
    named_sync(1, 256);
    TL(0, L, 18);
    {
        float gsum = 0.f, usum = 0.f;
        #pragma unroll
        for (int i = 0; i < 8; i++) { gsum += ldsf(SB + OFF_PART + (i * 64 + lane) * 4); usum += ldsf(SB + OFF_PART + (i * 64 + 32 + lane) * 4); }
        const float gv = bf_round(gsum), uv = bf_round(usum);
        const float hv = bf_round(__fdividef(gv, 1.f + __expf(-gv))) * uv;
        const uint32_t hp = pack_bf16(hv, __shfl_down_sync(0xffffffffu, hv, 1));
        uint32_t hb[4];
        #pragma unroll
        for (int i = 0; i < 4; i++) hb[i] = __shfl_sync(0xffffffffu, hp, 8 * i + 2 * t);
        float y[8][4];
        #pragma unroll
        for (int mb = 0; mb < 8; mb++) {
            y[mb][0] = 0.f; y[mb][1] = 0.f; y[mb][2] = 0.f; y[mb][3] = 0.f;
            #pragma unroll
            for (int ks = 0; ks < 2; ks++) mma_bf16(y[mb], fd[2*mb + ks].x, fd[2*mb + ks].y, fd[2*mb + ks].z, fd[2*mb + ks].w, hb[2 * ks], hb[2 * ks + 1]);
        }
        st_relaxed4_if(&g_ypart[L][min(c, NFC - 1)][tid * 4], make_uint4(not_sent(sel4(t, y[0][0], y[2][0], y[4][0], y[6][0])), not_sent(sel4(t, y[0][2], y[2][2], y[4][2], y[6][2])),
                       not_sent(sel4(t, y[1][0], y[3][0], y[5][0], y[7][0])), not_sent(sel4(t, y[1][2], y[3][2], y[5][2], y[7][2]))), ffn);
    }
    if (L == 0 && DDP == 3) named_arrive(N_DD, 288);
    TL(0, L, 19);
    if (L == 1) {
        if (W == 7) ctr_wait(&g_xc[1][rt.idx >> 8], 32);
        const float v = ffn_finish<256>(1, rt, tid, SB + OFF_FE, 1);
        if (tid < 8) reinterpret_cast<unsigned short*>(out)[(size_t)rt.idx * D_ + ypos_col(c * 8 + tid)] = (unsigned short)(__float_as_uint(v) >> 16);
        TL(0, L, 20);
    }
}

#define FW0 9
#define RK0 7
#define BAL 640
#define KW1 4
static_assert(FW0 >= 8 && KW1 >= 3 && KW1 < 7, "buffer reuse");
__device__ __forceinline__ void qkv_fill(const CUtensorMap* tx, const CUtensorMap* tw, uint32_t bar, int st, int k) {
    const uint32_t sa = SB + st * Q_STB;
    mbar_expect_tx(bar, Q_STB);
    tma_load(sa, tx, k * 64, (blockIdx.x >> 4) * 256, bar);
    tma_load3(sa + Q_ABYTES, tw, (blockIdx.x & 15) * 64, k * 64, 0, bar);
}
__device__ __forceinline__ void producer_role(const Maps& mp) {
    const int c = blockIdx.x, mt = c >> 4, nt = c & 15, lane = threadIdx.x & 31;
    #pragma unroll 1
    for (int i = 2; i < 13; i++) tm_prefetch(&mp.xa0 + i);
    #pragma unroll 1
    for (int L = 0; L < 2; L++) {
        const uint32_t rb = L * 32;
        uint32_t st = 0, ph = L;
        #pragma unroll 1
        for (int k = L == 0 ? 3 : 0; k < 16; k++) {
            if (k == 0) { ctr_wait(&g_xc[0][mt], 32); fence_async_global(); named_sync(N_GD, 288); }
            if (k == 1) named_sync(N_DD, 288);
            mbar_wait(rb + B_QE + 8 * st, ph);
            TL(k == 3 ? 256 : -1, L, 28);
            qkv_fill(L == 0 ? &mp.xa0 : &mp.xa, &mp.wqkv, rb + B_QF + 8 * st, st, k);
            if (L == 1 && k >= RK0 && k < RK0 + 4) {
                if (k == RK0) mbar_expect_tx(B_SW, 4 * 12288);
                tma_load(SB + OFF_SIDE + (k - RK0) * 12288, &mp.r, c * 24, (k - RK0) * 256, B_SW);
            }
            if (++st == 3) { st = 0; ph ^= 1; }
        }
        mbar_wait(B_KV0, L);
        mbar_arrive_elect(rb + B_AF);
        TL(256, L, 29);
        st = 1; ph = 1;
        #pragma unroll 1
        for (int w = 1; w < 16; w++) {
            const int win = (nt * 2 + (w >> 3)) * 8 + ((mt + w) & 7);
            if (w <= 3 || w == 8) {
                ctr_wait(&g_kvc[L][0][0] + (w < 3 ? win : (win & ~7) + (lane & 7)), 1);
                __syncwarp();
                fence_async_global();
            }
            TL(w == 1 ? 256 : -1, L, 7);
            mbar_wait(rb + B_AE + 8 * st, ph);
            mbar_expect_tx(rb + B_AF + 8 * st, KV_WIN);
            bulk_load(SB + st * A_WIN, g_kv + (size_t)win * KV_WIN, KV_WIN, rb + B_AF + 8 * st);
            if (w == KW1 || w == FW0) named_arrive(w == FW0 ? N_FW : N_KV1, 64);
            if (++st == 3) { st = 0; ph ^= 1; }
        }
        #pragma unroll 1
        for (int k = 0; k < 16; k++) {
            const uint32_t s = k & 3, fb = B_OF + 8 * s, sa = SB + o_stage(s);
            mbar_wait(k < 2 ? rb + B_AE + 8 + 8 * k : k == 2 ? rb + B_AE : k == 3 ? B_QAF : B_OE + 8 * s, k < 2 ? 0 : k == 2 ? 1 : k == 3 ? L : ((k >> 2) - 1) & 1);
            mbar_expect_tx(fb, 32768);
            tma_load5(sa + 16384, &mp.wo, 0, 0, k >> 3, (k & 7) * 2, nt & 14, fb);
            if ((k & 7) == 0) { ctr_wait(&g_oc[L][mt * 2 + (nt & 1)][k >> 3], 16); fence_async_global(); }
            bulk_load(sa, g_o + (size_t)((mt * 2 + (nt & 1)) * 16 + k) * 16384, 16384, fb);
        }
        if (c < NFC) {
            mbar_expect_tx(B_FL, 5 * 16384);
            mbar_expect_tx(B_FD, 4 * 16384);
            #pragma unroll 1
            for (int i = 3; i < 12; i++) {
                mbar_wait(B_OE + (i < 5 ? 0 : i == 5 ? 8 : i < 9 ? 16 : 24), 1);
                TL(i == 9 ? 256 : -1, L, 32);
                ffn_load(mp, i, SB + (i < 8 ? gu_piece(i) : OFF_FD + (i - 8) * 16384), i < 8 ? B_FL : B_FD);
            }
        }
    }
}

__global__ void __launch_bounds__(384, 1) k_all(const bf16* __restrict__ x0, const bf16* __restrict__ wo, const bf16* __restrict__ w_r, bf16* __restrict__ out,
                                                const __grid_constant__ Maps mp) {
    extern __shared__ __align__(1024) char smem[];
    if (smem_u32(smem) != SB) __trap();
    const int warp = warp_uniform(threadIdx.x >> 5), wg = warp >> 2;
    TL(0, 0, 0);
    {
        const int grp = warp >= 8 ? warp - 8 : warp + 4;
        #pragma unroll
        for (int i = 0; i < 4; i++) mbar_init(BB + grp * 32 + i * 8, grp < 7 ? 1 : grp < 10 ? 2 : 8);
        fence_mbar_init();
    }
    if (warp == 8) {
        #pragma unroll 1
        for (int s = 0; s < 3; s++) qkv_fill(&mp.xa0, &mp.wqkv, B_QF + 8 * s, s, s);
    }
    __syncthreads();
    if (wg == 2) {
        reg_dec<40>();
        if (warp == 8) producer_role(mp);
        else side_role(mp, x0, wo, w_r);
        if (gridDim.y == 2) {
            uint32_t v = threadIdx.x;
            #pragma unroll
            for (int i = 0; i < BAL; i++) asm volatile("fma.rn.f16x2 %0, %0, %0, %0;" : "+r"(v));
            sts32(SB, v);
        }
    } else {
        reg_inc<232>();
        #pragma unroll 1
        for (int L = 0; L < 2; L++) {
            qkv_phase(L, wg);
            attention_phase(L, wg);
            oproj_phase(L, wg, out);
        }
    }
}

typedef CUresult (*EncodeFn)(CUtensorMap*, CUtensorMapDataType, cuuint32_t, void*, const cuuint64_t*, const cuuint64_t*, const cuuint32_t*,
                             const cuuint32_t*, CUtensorMapInterleave, CUtensorMapSwizzle, CUtensorMapL2promotion, CUtensorMapFloatOOBfill);

void make_map(EncodeFn enc, CUtensorMap* tm, const void* ptr, int rank, const cuuint64_t* dims, const cuuint64_t* strides, const cuuint32_t* box, CUtensorMapSwizzle sw) {
    const cuuint32_t es[5] = {1, 1, 1, 1, 1};
    enc(tm, CU_TENSOR_MAP_DATA_TYPE_BFLOAT16, rank, const_cast<void*>(ptr), dims, strides, box, es, CU_TENSOR_MAP_INTERLEAVE_NONE, sw,
        box[0] == 64 ? CU_TENSOR_MAP_L2_PROMOTION_L2_128B : CU_TENSOR_MAP_L2_PROMOTION_NONE, CU_TENSOR_MAP_FLOAT_OOB_FILL_NONE);
}
void make_map2(EncodeFn enc, CUtensorMap* tm, const void* ptr, uint64_t cols, uint64_t rows, uint32_t bc, uint32_t br, CUtensorMapSwizzle sw) {
    const cuuint64_t dims[2] = {cols, rows}, strides[1] = {cols * 2};
    const cuuint32_t box[2] = {bc, br};
    make_map(enc, tm, ptr, 2, dims, strides, box, sw);
}

}

extern "C" void kernel_launch(void* const* d_in, const int* in_sizes, int n_in, void* d_out, int out_size) {
    const bf16* x0 = (const bf16*)d_in[0];
    const bf16* wqkv = (const bf16*)d_in[1];
    const bf16* wo = (const bf16*)d_in[2];
    const bf16* w_r = (const bf16*)d_in[4];
    const bf16* w_gate = (const bf16*)d_in[5];
    const bf16* w_up = (const bf16*)d_in[6];
    const bf16* w_down = (const bf16*)d_in[7];

    EncodeFn enc = nullptr;
    cudaDriverEntryPointQueryResult qr;
    cudaGetDriverEntryPoint("cuTensorMapEncodeTiled", (void**)&enc, cudaEnableDefault, &qr);
    void* p_x;
    cudaGetSymbolAddress(&p_x, g_x);
    Maps mp;
    const CUtensorMapSwizzle S128 = CU_TENSOR_MAP_SWIZZLE_128B;
    make_map2(enc, &mp.x0, x0, D_, S_, 64, 64, S128);
    make_map2(enc, &mp.x, p_x, D_, S_, 64, 64, S128);
    make_map2(enc, &mp.out, d_out, D_, S_, 64, 16, S128);
    make_map2(enc, &mp.xs, p_x, D_, S_, 64, 16, S128);
    make_map2(enc, &mp.xa0, x0, D_, S_, 64, 256, S128);
    make_map2(enc, &mp.xa, p_x, D_, S_, 64, 256, S128);
    make_map2(enc, &mp.w64, wqkv, 3 * D_, D_, 64, 64, S128);
    {
        const cuuint64_t dims[3] = {D_, D_, 3}, strides[2] = {3 * D_ * 2, D_ * 2};
        const cuuint32_t box[3] = {64, 64, 3};
        make_map(enc, &mp.wqkv, wqkv, 3, dims, strides, box, S128);
    }
    make_map2(enc, &mp.r, wqkv, 3 * D_, D_, 24, 256, CU_TENSOR_MAP_SWIZZLE_NONE);
    make_map2(enc, &mp.g, w_gate, FF, D_, 32, 256, CU_TENSOR_MAP_SWIZZLE_64B);
    make_map2(enc, &mp.u, w_up, FF, D_, 32, 256, CU_TENSOR_MAP_SWIZZLE_64B);
    {
        const cuuint64_t dims[5] = {64, 32, 2, 16, 16}, strides[4] = {D_ * 2, 32 * D_ * 2, 64 * D_ * 2, 128};
        const cuuint32_t box[5] = {64, 32, 1, 2, 2};
        make_map(enc, &mp.wo, wo, 5, dims, strides, box, S128);
    }
    {
        const cuuint64_t dims[3] = {64, FF, 16}, strides[2] = {D_ * 2, 128};
        const cuuint32_t box[3] = {64, 32, 4};
        make_map(enc, &mp.d, w_down, 3, dims, strides, box, S128);
    }
    cudaFuncSetAttribute(k_all, cudaFuncAttributeMaxDynamicSharedMemorySize, K_SMEM);
    k_all<<<128, 384, K_SMEM, cudaStreamPerThread>>>(x0, wo, w_r, (bf16*)d_out, mp);
}
```

```cpp
#include <cuda_runtime.h>
#include <cuda_bf16.h>
#include <cuda_fp16.h>
#include <cuda.h>
#include <cudaTypedefs.h>
#include <stdint.h>

namespace {

typedef __nv_bfloat16 bf16;

constexpr int S_ = 2048, D_ = 1024, NH = 32, FF = 3584, NFC = FF / 32;
constexpr float LN_EPS = 1e-5f;
constexpr float QSCALE = 0.17677669529663687f * 1.4426950408889634f;
constexpr uint32_t SENT = 0xFFFFFFFFu;

constexpr uint32_t STAT_FULL = 0x41000000u;

constexpr int KV_WIN = 32768;
__device__ __align__(1024) char g_kv[NH * 8 * KV_WIN];
__device__ __align__(1024) char g_o[32 * 2 * 16 * 4096];
__device__ __align__(1024) bf16 g_x[S_ * D_];
__device__ float g_csum[8 * 3 * D_];
__device__ float g_wsq[8 * 96];
__device__ float2 g_rs0[S_];
__device__ __align__(128) float4 g_sums[2][S_];
__device__ __align__(128) uint32_t g_ypart[2][NFC][D_];
__device__ __align__(128) uint4 g_tab[2][8][16][2];
__device__ __align__(128) uint32_t g_xrow[2][16][D_ / 2];
__device__ __align__(128) uint32_t g_x2row[D_];
__device__ __align__(128) uint32_t g_fix[3 * D_];
__device__ uint32_t g_c0;
__device__ __align__(128) uint32_t g_kvc[2][NH][8];
__device__ __align__(128) uint32_t g_oc[2][16][2][16];
__device__ __align__(128) uint32_t g_xc[2][8];
struct RouteOut { int idx; float r; float mean; float rstd; };

constexpr uint32_t SB = 1024;

__device__ __forceinline__ uint32_t smem_u32(const void* p) { return (uint32_t)__cvta_generic_to_shared(p); }
__device__ __forceinline__ void mbar_arrive(uint32_t bar) { asm volatile("mbarrier.arrive.shared::cta.b64 _, [%0];" :: "r"(bar) : "memory"); }
__device__ __forceinline__ void mbar_wait(uint32_t bar, uint32_t parity) {
    asm volatile("{\n.reg .pred p;\n.reg .u32 n;\nmov.u32 n, 0;\n"
                 "LAB_WAIT:\nmbarrier.try_wait.parity.shared::cta.b64 p, [%0], %1, 2000;\n@p bra LAB_DONE;\n"
                 "add.u32 n, n, 1;\nsetp.lt.u32 p, n, 0x200000;\n@p bra LAB_WAIT;\ntrap;\nLAB_DONE:\n}" :: "r"(bar), "r"(parity) : "memory");
}
__device__ __forceinline__ void mbar_arrive_elect(uint32_t bar) {
    asm volatile("{\n.reg .pred p;\nelect.sync _|p, 0xffffffff;\n@p mbarrier.arrive.shared::cta.b64 _, [%0];\n}" :: "r"(bar) : "memory");
}
__device__ __forceinline__ int tid_now() { int v; asm volatile("mov.u32 %0, %%tid.x;" : "=r"(v)); return v; }
__device__ __forceinline__ int cta_now() { int v; asm volatile("mov.u32 %0, %%ctaid.x;" : "=r"(v)); return v; }
__device__ __forceinline__ int warp_uniform(int v) { return __shfl_sync(0xffffffffu, v, 0); }
__device__ __forceinline__ void fence_mbar_init() { asm volatile("fence.mbarrier_init.release.cluster;" ::: "memory"); }
__device__ __forceinline__ void fence_async_smem() { asm volatile("fence.proxy.async.shared::cta;" ::: "memory"); }
__device__ __forceinline__ void fence_async_global() { asm volatile("fence.proxy.async.global;" ::: "memory"); }
__device__ __forceinline__ void named_sync(int id, int n) { asm volatile("bar.sync %0, %1;" :: "r"(id), "r"(n) : "memory"); }
__device__ __forceinline__ void named_arrive(int id, int n) { asm volatile("bar.arrive %0, %1;" :: "r"(id), "r"(n) : "memory"); }
__device__ __forceinline__ bool named_any(bool p, int id) {
    uint32_t r;
    asm volatile("{\n.reg .pred a, b;\nsetp.ne.u32 a, %1, 0;\nbarrier.cta.red.or.pred b, %2, 128, a;\nselp.u32 %0, 1, 0, b;\n}" : "=r"(r) : "r"((uint32_t)p), "r"(id) : "memory");
    return r != 0;
}
#define ELECT(op) "{\n.reg .pred e;\nelect.sync _|e, 0xffffffff;\n@e " op "\n}"
__device__ __forceinline__ void mbar_init(uint32_t bar, int cnt) { asm volatile(ELECT("mbarrier.init.shared::cta.b64 [%0], %1;") :: "r"(bar), "r"(cnt) : "memory"); }
__device__ __forceinline__ void mbar_expect_tx(uint32_t bar, uint32_t bytes) { asm volatile(ELECT("mbarrier.arrive.expect_tx.shared::cta.b64 _, [%0], %1;") :: "r"(bar), "r"(bytes) : "memory"); }
__device__ __forceinline__ void bulk_load(uint32_t dst, const void* src, uint32_t bytes, uint32_t bar) {
    asm volatile(ELECT("cp.async.bulk.shared::cluster.global.mbarrier::complete_tx::bytes [%0], [%1], %2, [%3];") :: "r"(dst), "l"(src), "r"(bytes), "r"(bar) : "memory");
}
__device__ __forceinline__ void bulk_store(void* dst, uint32_t src, uint32_t bytes) {
    asm volatile(ELECT("cp.async.bulk.global.shared::cta.bulk_group [%0], [%1], %2;") :: "l"(dst), "r"(src), "r"(bytes) : "memory");
}
__device__ __forceinline__ void bulk_commit() { asm volatile("cp.async.bulk.commit_group;" ::: "memory"); }
__device__ __forceinline__ void bulk_wait() { asm volatile("cp.async.bulk.wait_group 0;" ::: "memory"); }
template <int N> __device__ __forceinline__ void bulk_wait_n() { asm volatile("cp.async.bulk.wait_group %0;" :: "n"(N) : "memory"); }
__device__ __forceinline__ void bulk_wait_read() { asm volatile("cp.async.bulk.wait_group.read 0;" ::: "memory"); }
__device__ __forceinline__ void l2_prefetch(const void* src, uint32_t bytes) {
    asm volatile(ELECT("cp.async.bulk.prefetch.L2.global [%0], %1;") :: "l"(src), "r"(bytes) : "memory");
}
__device__ __forceinline__ void tma_load(uint32_t dst, const CUtensorMap* tm, int c0, int c1, uint32_t bar) {
    asm volatile(ELECT("cp.async.bulk.tensor.2d.shared::cluster.global.mbarrier::complete_tx::bytes [%0], [%1, {%3, %4}], [%2];")
                 :: "r"(dst), "l"(tm), "r"(bar), "r"(c0), "r"(c1) : "memory");
}
__device__ __forceinline__ void tma_load3(uint32_t dst, const CUtensorMap* tm, int c0, int c1, int c2, uint32_t bar) {
    asm volatile(ELECT("cp.async.bulk.tensor.3d.shared::cluster.global.mbarrier::complete_tx::bytes [%0], [%1, {%3, %4, %5}], [%2];")
                 :: "r"(dst), "l"(tm), "r"(bar), "r"(c0), "r"(c1), "r"(c2) : "memory");
}
__device__ __forceinline__ uint64_t evict_first() { uint64_t a; asm("createpolicy.fractional.L2::evict_first.b64 %0, 1.0;" : "=l"(a)); return a; }
__device__ __forceinline__ void tma_load_h(uint32_t dst, const CUtensorMap* tm, int c0, int c1, uint32_t bar, bool ef) {
    if (!ef) tma_load(dst, tm, c0, c1, bar);
    else asm volatile(ELECT("cp.async.bulk.tensor.2d.shared::cluster.global.mbarrier::complete_tx::bytes.L2::cache_hint [%0], [%1, {%3, %4}], [%2], %5;")
                      :: "r"(dst), "l"(tm), "r"(bar), "r"(c0), "r"(c1), "l"(evict_first()) : "memory");
}
__device__ __forceinline__ void tma_load3_h(uint32_t dst, const CUtensorMap* tm, int c0, int c1, int c2, uint32_t bar, bool ef) {
    if (!ef) tma_load3(dst, tm, c0, c1, c2, bar);
    else asm volatile(ELECT("cp.async.bulk.tensor.3d.shared::cluster.global.mbarrier::complete_tx::bytes.L2::cache_hint [%0], [%1, {%3, %4, %5}], [%2], %6;")
                      :: "r"(dst), "l"(tm), "r"(bar), "r"(c0), "r"(c1), "r"(c2), "l"(evict_first()) : "memory");
}
__device__ __forceinline__ void tma_load5(uint32_t dst, const CUtensorMap* tm, int c0, int c1, int c2, int c3, int c4, uint32_t bar) {
    asm volatile(ELECT("cp.async.bulk.tensor.5d.shared::cluster.global.mbarrier::complete_tx::bytes [%0], [%1, {%3, %4, %5, %6, %7}], [%2];")
                 :: "r"(dst), "l"(tm), "r"(bar), "r"(c0), "r"(c1), "r"(c2), "r"(c3), "r"(c4) : "memory");
}
__device__ __forceinline__ void tma_store(const CUtensorMap* tm, uint32_t src, int c0, int c1) {
    asm volatile(ELECT("cp.async.bulk.tensor.2d.global.shared::cta.bulk_group [%0, {%2, %3}], [%1];") :: "l"(tm), "r"(src), "r"(c0), "r"(c1) : "memory");
}
__device__ __forceinline__ void tm_prefetch(const CUtensorMap* tm) { asm volatile(ELECT("prefetch.tensormap [%0];") :: "l"(tm) : "memory"); }
__device__ __forceinline__ uint32_t lds32(uint32_t a) { uint32_t v; asm volatile("ld.shared.b32 %0, [%1];" : "=r"(v) : "r"(a) : "memory"); return v; }
__device__ __forceinline__ float ldsf(uint32_t a) { return __uint_as_float(lds32(a)); }
__device__ __forceinline__ float2 lds64f(uint32_t a) { float2 v; asm volatile("ld.shared.v2.f32 {%0, %1}, [%2];" : "=f"(v.x), "=f"(v.y) : "r"(a) : "memory"); return v; }
__device__ __forceinline__ uint4 lds128(uint32_t a) { uint4 v; asm volatile("ld.shared.v4.b32 {%0, %1, %2, %3}, [%4];" : "=r"(v.x), "=r"(v.y), "=r"(v.z), "=r"(v.w) : "r"(a) : "memory"); return v; }
__device__ __forceinline__ void sts32(uint32_t a, uint32_t v) { asm volatile("st.shared.b32 [%0], %1;" :: "r"(a), "r"(v) : "memory"); }
__device__ __forceinline__ void stsf(uint32_t a, float v) { sts32(a, __float_as_uint(v)); }
__device__ __forceinline__ void sts64f(uint32_t a, float x, float y) { asm volatile("st.shared.v2.f32 [%0], {%1, %2};" :: "r"(a), "f"(x), "f"(y) : "memory"); }
__device__ __forceinline__ void sts128(uint32_t a, const uint4& v) { asm volatile("st.shared.v4.b32 [%0], {%1, %2, %3, %4};" :: "r"(a), "r"(v.x), "r"(v.y), "r"(v.z), "r"(v.w) : "memory"); }
__device__ __forceinline__ void stsm4(uint32_t a, uint32_t x, uint32_t y, uint32_t z, uint32_t w) {
    asm volatile("stmatrix.sync.aligned.m8n8.x4.shared.b16 [%0], {%1, %2, %3, %4};" :: "r"(a), "r"(x), "r"(y), "r"(z), "r"(w) : "memory");
}
__device__ __forceinline__ void ldsm4(uint32_t& a0, uint32_t& a1, uint32_t& a2, uint32_t& a3, uint32_t addr) {
    asm volatile("ldmatrix.sync.aligned.m8n8.x4.shared.b16 {%0,%1,%2,%3}, [%4];" : "=r"(a0), "=r"(a1), "=r"(a2), "=r"(a3) : "r"(addr) : "memory");
}
__device__ __forceinline__ void ldsm4t(uint32_t& a0, uint32_t& a1, uint32_t& a2, uint32_t& a3, uint32_t addr) {
    asm volatile("ldmatrix.sync.aligned.m8n8.x4.trans.shared.b16 {%0,%1,%2,%3}, [%4];" : "=r"(a0), "=r"(a1), "=r"(a2), "=r"(a3) : "r"(addr) : "memory");
}
__device__ __forceinline__ void mma_bf16(float (&c)[4], uint32_t a0, uint32_t a1, uint32_t a2, uint32_t a3, uint32_t b0, uint32_t b1) {
    asm("mma.sync.aligned.m16n8k16.row.col.f32.bf16.bf16.f32 {%0,%1,%2,%3}, {%4,%5,%6,%7}, {%8,%9}, {%0,%1,%2,%3};"
        : "+f"(c[0]), "+f"(c[1]), "+f"(c[2]), "+f"(c[3]) : "r"(a0), "r"(a1), "r"(a2), "r"(a3), "r"(b0), "r"(b1));
}
__device__ __forceinline__ uint32_t ld_acquire(const void* p) { uint32_t v; asm volatile("ld.acquire.gpu.global.u32 %0, [%1];" : "=r"(v) : "l"(p) : "memory"); return v; }
__device__ __forceinline__ void sts_release(uint32_t a, uint32_t v) { asm volatile("st.release.cta.shared.u32 [%0], %1;" :: "r"(a), "r"(v) : "memory"); }
__device__ __forceinline__ uint32_t ld_relaxed(const void* p) { uint32_t v; asm volatile("ld.relaxed.gpu.global.u32 %0, [%1];" : "=r"(v) : "l"(p) : "memory"); return v; }
__device__ __forceinline__ uint4 ld_relaxed4(const void* p) {
    uint4 v; asm volatile("ld.relaxed.gpu.global.v4.b32 {%0, %1, %2, %3}, [%4];" : "=r"(v.x), "=r"(v.y), "=r"(v.z), "=r"(v.w) : "l"(p) : "memory"); return v;
}
__device__ __forceinline__ void ld_relaxed4_unless(uint4& v, const void* p, uint32_t full) {
    asm volatile("{\n.reg .pred q;\nsetp.ne.u32 q, %3, %5;\n@q ld.relaxed.gpu.global.v4.b32 {%0, %1, %2, %3}, [%4];\n}"
                 : "+r"(v.x), "+r"(v.y), "+r"(v.z), "+r"(v.w) : "l"(p), "r"(full) : "memory");
}
__device__ __forceinline__ uint2 ld_relaxed2(const void* p) { uint2 v; asm volatile("ld.relaxed.gpu.global.v2.b32 {%0, %1}, [%2];" : "=r"(v.x), "=r"(v.y) : "l"(p) : "memory"); return v; }
__device__ __forceinline__ void st_relaxed(void* p, uint32_t v) { asm volatile("st.relaxed.gpu.global.u32 [%0], %1;" :: "l"(p), "r"(v) : "memory"); }
__device__ __forceinline__ void st_relaxed4_if(void* p, const uint4& v, bool on) {
    asm volatile("{\n.reg .pred q;\nsetp.ne.u32 q, %5, 0;\n@q st.relaxed.gpu.global.v4.b32 [%0], {%1, %2, %3, %4};\n}"
                 :: "l"(p), "r"(v.x), "r"(v.y), "r"(v.z), "r"(v.w), "r"((uint32_t)on) : "memory");
}
__device__ __forceinline__ uint32_t not_sent(float v) { const uint32_t u = __float_as_uint(v); return u == SENT ? 0x7FFFFFFFu : u; }
__device__ __forceinline__ bool has_sent(const uint4& v) { return max(max(v.x, v.y), max(v.z, v.w)) == SENT; }
constexpr uint32_t SPIN_MAX = 1u << 22;
__device__ __forceinline__ void spin_check(uint32_t n) { asm volatile("{\n.reg .pred p;\nsetp.ge.u32 p, %0, %1;\n@p st.global.u32 [%2], %0;\n}" :: "r"(n), "n"(SPIN_MAX), "l"(0ull) : "memory"); }
__device__ __forceinline__ void ctr_arrive(uint32_t* c) { asm volatile(ELECT("red.release.gpu.global.add.u32 [%0], 1;") :: "l"(c) : "memory"); }
__device__ __forceinline__ void ctr_wait(const uint32_t* c, uint32_t target) {
    asm volatile("{\n.reg .pred p;\n.reg .u32 n, v;\nmov.u32 n, 0;\n"
                 "LAB_WAIT:\nld.acquire.gpu.global.u32 v, [%0];\nsetp.ge.u32 p, v, %1;\n@p bra LAB_DONE;\n"
                 "add.u32 n, n, 1;\nsetp.lt.u32 p, n, 0x400000;\n@p bra LAB_WAIT;\ntrap;\nLAB_DONE:\n}" :: "l"(c), "r"(target) : "memory");
}
__device__ __forceinline__ void ctr_wait_all(const uint32_t* c, uint32_t target) {
    asm volatile("{\n.reg .pred p;\n.reg .u32 n, v;\nmov.u32 n, 0;\n"
                 "LAB_WAIT:\nld.acquire.gpu.global.u32 v, [%0];\nsetp.ge.u32 p, v, %1;\nvote.sync.all.pred p, p, 0xffffffff;\n@p bra.uni LAB_DONE;\n"
                 "add.u32 n, n, 1;\nsetp.lt.u32 p, n, 0x400000;\n@p bra.uni LAB_WAIT;\ntrap;\nLAB_DONE:\n}" :: "l"(c), "r"(target) : "memory");
}
__device__ __forceinline__ uint32_t flags_wait(const uint32_t* c, uint32_t mask, bool all) {
    uint32_t r;
    asm volatile("{\n.reg .pred p;\n.reg .u32 n, v;\nmov.u32 n, 0;\n"
                 "LAB_WAIT:\nld.acquire.gpu.global.u32 v, [%1];\nsetp.ne.u32 p, v, 0;\nvote.sync.ballot.b32 %0, p, 0xffffffff;\nand.b32 v, %0, %2;\nsetp.ge.u32 p, v, %3;\n@p bra.uni LAB_DONE;\n"
                 "add.u32 n, n, 1;\nsetp.lt.u32 p, n, 0x400000;\n@p bra.uni LAB_WAIT;\ntrap;\nLAB_DONE:\n}" : "=&r"(r) : "l"(c), "r"(mask), "r"(all ? mask : 1u) : "memory");
    return r;
}
__device__ __forceinline__ uint32_t smem_wait_any(uint32_t a, uint32_t mask) {
    uint32_t v;
    asm volatile("{\n.reg .pred p;\n.reg .u32 n, t;\nmov.u32 n, 0;\n"
                 "LAB_WAIT:\nld.acquire.cta.shared.u32 %0, [%1];\nand.b32 t, %0, %2;\nsetp.ne.u32 p, t, 0;\nvote.sync.all.pred p, p, 0xffffffff;\n@p bra.uni LAB_DONE;\n"
                 "add.u32 n, n, 1;\nsetp.lt.u32 p, n, 0x4000000;\n@p bra.uni LAB_WAIT;\ntrap;\nLAB_DONE:\n}" : "=r"(v) : "r"(a), "r"(mask) : "memory");
    return warp_uniform(v);
}
__device__ __forceinline__ void publish(uint32_t* c) { bulk_wait(); fence_async_global(); ctr_arrive(c); }

__device__ __forceinline__ void wg_fence() { asm volatile("wgmma.fence.sync.aligned;" ::: "memory"); }
__device__ __forceinline__ void wg_commit() { asm volatile("wgmma.commit_group.sync.aligned;" ::: "memory"); }
template <int N> __device__ __forceinline__ void wg_wait() { asm volatile("wgmma.wait_group.sync.aligned %0;" :: "n"(N) : "memory"); }
template <int N> __device__ __forceinline__ void reg_inc() { asm volatile("setmaxnreg.inc.sync.aligned.u32 %0;" :: "n"(N)); }
template <int N> __device__ __forceinline__ void reg_dec() { asm volatile("setmaxnreg.dec.sync.aligned.u32 %0;" :: "n"(N)); }
__host__ __device__ constexpr uint64_t desc_plain(uint32_t addr, uint32_t lbo, uint32_t sbo) {
    return (uint64_t)((addr & 0x3FFFF) >> 4) | ((uint64_t)(lbo >> 4) << 16) | ((uint64_t)(sbo >> 4) << 32);
}
__host__ __device__ constexpr uint64_t desc_sw128(uint32_t addr, uint32_t lbo, uint32_t sbo) { return desc_plain(addr, lbo, sbo) | (1ull << 62); }

__device__ __forceinline__ float ex2(float x) { float y; asm("ex2.approx.ftz.f32 %0, %1;" : "=f"(y) : "f"(x)); return y; }
__device__ __forceinline__ float rcp(float x) { float y; asm("rcp.approx.ftz.f32 %0, %1;" : "=f"(y) : "f"(x)); return y; }
__device__ __forceinline__ float rsq(float x) { float y; asm("rsqrt.approx.ftz.f32 %0, %1;" : "=f"(y) : "f"(x)); return y; }
__device__ __forceinline__ uint32_t pack_bf16(float lo, float hi) { uint32_t r; asm("cvt.rn.bf16x2.f32 %0, %1, %2;" : "=r"(r) : "f"(hi), "f"(lo)); return r; }
__device__ __forceinline__ uint32_t pack_f16(float lo, float hi) { uint32_t r; asm("cvt.rn.f16x2.f32 %0, %1, %2;" : "=r"(r) : "f"(hi), "f"(lo)); return r; }
__device__ __forceinline__ float bf_lo(uint32_t v) { return __uint_as_float(v << 16); }
__device__ __forceinline__ float bf_hi(uint32_t v) { return __uint_as_float(v & 0xFFFF0000u); }
__device__ __forceinline__ float bf_round(float x) { return __uint_as_float(pack_bf16(0.f, x)); }
__device__ __forceinline__ uint32_t badd2(uint32_t a, uint32_t b) { uint32_t r; asm("add.rn.bf16x2 %0, %1, %2;" : "=r"(r) : "r"(a), "r"(b)); return r; }
__device__ __forceinline__ void h2_unpack(uint32_t v, float& lo, float& hi) {
    asm("{.reg .f16 l, h; mov.b32 {l, h}, %2; cvt.f32.f16 %0, l; cvt.f32.f16 %1, h;}" : "=f"(lo), "=f"(hi) : "r"(v));
}
__device__ __forceinline__ uint32_t add_ln2(uint32_t x, float rstd, float nb) { return badd2(x, pack_bf16(fmaf(bf_lo(x), rstd, nb), fmaf(bf_hi(x), rstd, nb))); }
__device__ __forceinline__ float sel4(int t, float a0, float a1, float a2, float a3) {
    float r;
    asm("{\n.reg .pred p, q;\n.reg .f32 x, y;\nsetp.ne.u32 p, %1, 0;\nsetp.ne.u32 q, %2, 0;\nselp.f32 x, %4, %3, p;\nselp.f32 y, %6, %5, p;\nselp.f32 %0, y, x, q;\n}"
        : "=f"(r) : "r"(t & 1), "r"(t & 2), "f"(a0), "f"(a1), "f"(a2), "f"(a3));
    return r;
}
__device__ __forceinline__ float warp_sum(float v) {
    #pragma unroll
    for (int o = 16; o > 0; o >>= 1) v += __shfl_xor_sync(0xffffffffu, v, o);
    return v;
}
__device__ __forceinline__ float warp_max(float v) {
    #pragma unroll
    for (int o = 16; o > 0; o >>= 1) v = fmaxf(v, __shfl_xor_sync(0xffffffffu, v, o));
    return v;
}
__device__ __forceinline__ uint32_t redux_max(uint32_t v) { uint32_t r; asm volatile("redux.sync.max.u32 %0, %1, 0xffffffff;" : "=r"(r) : "r"(v)); return r; }
__device__ __forceinline__ uint32_t redux_min(uint32_t v) { uint32_t r; asm volatile("redux.sync.min.u32 %0, %1, 0xffffffff;" : "=r"(r) : "r"(v)); return r; }

#define TL(T, L, i)

__device__ __forceinline__ void wg_gemm_n128(float (&d)[64], uint64_t desca, uint64_t desc) {
    asm volatile("{\n.reg .pred p;\nsetp.ne.b32 p, 1, 0;\n"
        "wgmma.mma_async.sync.aligned.m64n128k16.f32.bf16.bf16 "
        "{%0,%1,%2,%3,%4,%5,%6,%7,%8,%9,%10,%11,%12,%13,%14,%15,%16,%17,%18,%19,%20,%21,%22,%23,%24,%25,%26,%27,%28,%29,%30,%31,%32,%33,%34,%35,%36,%37,%38,%39,%40,%41,%42,%43,%44,%45,%46,%47,%48,%49,%50,%51,%52,%53,%54,%55,%56,%57,%58,%59,%60,%61,%62,%63}, "
        "%64, %65, p, 1, 1, 0, 1;\n}\n"
        : "+f"(d[0]), "+f"(d[1]), "+f"(d[2]), "+f"(d[3]), "+f"(d[4]), "+f"(d[5]), "+f"(d[6]), "+f"(d[7]),
          "+f"(d[8]), "+f"(d[9]), "+f"(d[10]), "+f"(d[11]), "+f"(d[12]), "+f"(d[13]), "+f"(d[14]), "+f"(d[15]),
          "+f"(d[16]), "+f"(d[17]), "+f"(d[18]), "+f"(d[19]), "+f"(d[20]), "+f"(d[21]), "+f"(d[22]), "+f"(d[23]),
          "+f"(d[24]), "+f"(d[25]), "+f"(d[26]), "+f"(d[27]), "+f"(d[28]), "+f"(d[29]), "+f"(d[30]), "+f"(d[31]),
          "+f"(d[32]), "+f"(d[33]), "+f"(d[34]), "+f"(d[35]), "+f"(d[36]), "+f"(d[37]), "+f"(d[38]), "+f"(d[39]),
          "+f"(d[40]), "+f"(d[41]), "+f"(d[42]), "+f"(d[43]), "+f"(d[44]), "+f"(d[45]), "+f"(d[46]), "+f"(d[47]),
          "+f"(d[48]), "+f"(d[49]), "+f"(d[50]), "+f"(d[51]), "+f"(d[52]), "+f"(d[53]), "+f"(d[54]), "+f"(d[55]),
          "+f"(d[56]), "+f"(d[57]), "+f"(d[58]), "+f"(d[59]), "+f"(d[60]), "+f"(d[61]), "+f"(d[62]), "+f"(d[63])
        : "l"(desca), "l"(desc));
}
__device__ __forceinline__ void wg_gemm_n128_init(float (&d)[64], uint64_t desca, uint64_t desc) {
    asm volatile("{\n.reg .pred p;\nsetp.ne.b32 p, 0, 0;\n"
        "wgmma.mma_async.sync.aligned.m64n128k16.f32.bf16.bf16 "
        "{%0,%1,%2,%3,%4,%5,%6,%7,%8,%9,%10,%11,%12,%13,%14,%15,%16,%17,%18,%19,%20,%21,%22,%23,%24,%25,%26,%27,%28,%29,%30,%31,%32,%33,%34,%35,%36,%37,%38,%39,%40,%41,%42,%43,%44,%45,%46,%47,%48,%49,%50,%51,%52,%53,%54,%55,%56,%57,%58,%59,%60,%61,%62,%63}, "
        "%64, %65, p, 1, 1, 0, 1;\n}\n"
        : "=f"(d[0]), "=f"(d[1]), "=f"(d[2]), "=f"(d[3]), "=f"(d[4]), "=f"(d[5]), "=f"(d[6]), "=f"(d[7]),
          "=f"(d[8]), "=f"(d[9]), "=f"(d[10]), "=f"(d[11]), "=f"(d[12]), "=f"(d[13]), "=f"(d[14]), "=f"(d[15]),
          "=f"(d[16]), "=f"(d[17]), "=f"(d[18]), "=f"(d[19]), "=f"(d[20]), "=f"(d[21]), "=f"(d[22]), "=f"(d[23]),
          "=f"(d[24]), "=f"(d[25]), "=f"(d[26]), "=f"(d[27]), "=f"(d[28]), "=f"(d[29]), "=f"(d[30]), "=f"(d[31]),
          "=f"(d[32]), "=f"(d[33]), "=f"(d[34]), "=f"(d[35]), "=f"(d[36]), "=f"(d[37]), "=f"(d[38]), "=f"(d[39]),
          "=f"(d[40]), "=f"(d[41]), "=f"(d[42]), "=f"(d[43]), "=f"(d[44]), "=f"(d[45]), "=f"(d[46]), "=f"(d[47]),
          "=f"(d[48]), "=f"(d[49]), "=f"(d[50]), "=f"(d[51]), "=f"(d[52]), "=f"(d[53]), "=f"(d[54]), "=f"(d[55]),
          "=f"(d[56]), "=f"(d[57]), "=f"(d[58]), "=f"(d[59]), "=f"(d[60]), "=f"(d[61]), "=f"(d[62]), "=f"(d[63])
        : "l"(desca), "l"(desc));
}
__device__ __forceinline__ void wg_gemm_n192(float (&d)[96], uint64_t desca, uint64_t desc) {
    asm volatile("{\n.reg .pred p;\nsetp.ne.b32 p, 1, 0;\n"
        "wgmma.mma_async.sync.aligned.m64n192k16.f32.bf16.bf16 "
        "{%0,%1,%2,%3,%4,%5,%6,%7,%8,%9,%10,%11,%12,%13,%14,%15,%16,%17,%18,%19,%20,%21,%22,%23,%24,%25,%26,%27,%28,%29,%30,%31,%32,%33,%34,%35,%36,%37,%38,%39,%40,%41,%42,%43,%44,%45,%46,%47,%48,%49,%50,%51,%52,%53,%54,%55,%56,%57,%58,%59,%60,%61,%62,%63,%64,%65,%66,%67,%68,%69,%70,%71,%72,%73,%74,%75,%76,%77,%78,%79,%80,%81,%82,%83,%84,%85,%86,%87,%88,%89,%90,%91,%92,%93,%94,%95}, "
        "%96, %97, p, 1, 1, 0, 1;\n}\n"
        : "+f"(d[0]), "+f"(d[1]), "+f"(d[2]), "+f"(d[3]), "+f"(d[4]), "+f"(d[5]), "+f"(d[6]), "+f"(d[7]),
          "+f"(d[8]), "+f"(d[9]), "+f"(d[10]), "+f"(d[11]), "+f"(d[12]), "+f"(d[13]), "+f"(d[14]), "+f"(d[15]),
          "+f"(d[16]), "+f"(d[17]), "+f"(d[18]), "+f"(d[19]), "+f"(d[20]), "+f"(d[21]), "+f"(d[22]), "+f"(d[23]),
          "+f"(d[24]), "+f"(d[25]), "+f"(d[26]), "+f"(d[27]), "+f"(d[28]), "+f"(d[29]), "+f"(d[30]), "+f"(d[31]),
          "+f"(d[32]), "+f"(d[33]), "+f"(d[34]), "+f"(d[35]), "+f"(d[36]), "+f"(d[37]), "+f"(d[38]), "+f"(d[39]),
          "+f"(d[40]), "+f"(d[41]), "+f"(d[42]), "+f"(d[43]), "+f"(d[44]), "+f"(d[45]), "+f"(d[46]), "+f"(d[47]),
          "+f"(d[48]), "+f"(d[49]), "+f"(d[50]), "+f"(d[51]), "+f"(d[52]), "+f"(d[53]), "+f"(d[54]), "+f"(d[55]),
          "+f"(d[56]), "+f"(d[57]), "+f"(d[58]), "+f"(d[59]), "+f"(d[60]), "+f"(d[61]), "+f"(d[62]), "+f"(d[63]),
          "+f"(d[64]), "+f"(d[65]), "+f"(d[66]), "+f"(d[67]), "+f"(d[68]), "+f"(d[69]), "+f"(d[70]), "+f"(d[71]),
          "+f"(d[72]), "+f"(d[73]), "+f"(d[74]), "+f"(d[75]), "+f"(d[76]), "+f"(d[77]), "+f"(d[78]), "+f"(d[79]),
          "+f"(d[80]), "+f"(d[81]), "+f"(d[82]), "+f"(d[83]), "+f"(d[84]), "+f"(d[85]), "+f"(d[86]), "+f"(d[87]),
          "+f"(d[88]), "+f"(d[89]), "+f"(d[90]), "+f"(d[91]), "+f"(d[92]), "+f"(d[93]), "+f"(d[94]), "+f"(d[95])
        : "l"(desca), "l"(desc));
}
__device__ __forceinline__ void wg_gemm_n192_init(float (&d)[96], uint64_t desca, uint64_t desc) {
    asm volatile("{\n.reg .pred p;\nsetp.ne.b32 p, 0, 0;\n"
        "wgmma.mma_async.sync.aligned.m64n192k16.f32.bf16.bf16 "
        "{%0,%1,%2,%3,%4,%5,%6,%7,%8,%9,%10,%11,%12,%13,%14,%15,%16,%17,%18,%19,%20,%21,%22,%23,%24,%25,%26,%27,%28,%29,%30,%31,%32,%33,%34,%35,%36,%37,%38,%39,%40,%41,%42,%43,%44,%45,%46,%47,%48,%49,%50,%51,%52,%53,%54,%55,%56,%57,%58,%59,%60,%61,%62,%63,%64,%65,%66,%67,%68,%69,%70,%71,%72,%73,%74,%75,%76,%77,%78,%79,%80,%81,%82,%83,%84,%85,%86,%87,%88,%89,%90,%91,%92,%93,%94,%95}, "
        "%96, %97, p, 1, 1, 0, 1;\n}\n"
        : "=f"(d[0]), "=f"(d[1]), "=f"(d[2]), "=f"(d[3]), "=f"(d[4]), "=f"(d[5]), "=f"(d[6]), "=f"(d[7]),
          "=f"(d[8]), "=f"(d[9]), "=f"(d[10]), "=f"(d[11]), "=f"(d[12]), "=f"(d[13]), "=f"(d[14]), "=f"(d[15]),
          "=f"(d[16]), "=f"(d[17]), "=f"(d[18]), "=f"(d[19]), "=f"(d[20]), "=f"(d[21]), "=f"(d[22]), "=f"(d[23]),
          "=f"(d[24]), "=f"(d[25]), "=f"(d[26]), "=f"(d[27]), "=f"(d[28]), "=f"(d[29]), "=f"(d[30]), "=f"(d[31]),
          "=f"(d[32]), "=f"(d[33]), "=f"(d[34]), "=f"(d[35]), "=f"(d[36]), "=f"(d[37]), "=f"(d[38]), "=f"(d[39]),
          "=f"(d[40]), "=f"(d[41]), "=f"(d[42]), "=f"(d[43]), "=f"(d[44]), "=f"(d[45]), "=f"(d[46]), "=f"(d[47]),
          "=f"(d[48]), "=f"(d[49]), "=f"(d[50]), "=f"(d[51]), "=f"(d[52]), "=f"(d[53]), "=f"(d[54]), "=f"(d[55]),
          "=f"(d[56]), "=f"(d[57]), "=f"(d[58]), "=f"(d[59]), "=f"(d[60]), "=f"(d[61]), "=f"(d[62]), "=f"(d[63]),
          "=f"(d[64]), "=f"(d[65]), "=f"(d[66]), "=f"(d[67]), "=f"(d[68]), "=f"(d[69]), "=f"(d[70]), "=f"(d[71]),
          "=f"(d[72]), "=f"(d[73]), "=f"(d[74]), "=f"(d[75]), "=f"(d[76]), "=f"(d[77]), "=f"(d[78]), "=f"(d[79]),
          "=f"(d[80]), "=f"(d[81]), "=f"(d[82]), "=f"(d[83]), "=f"(d[84]), "=f"(d[85]), "=f"(d[86]), "=f"(d[87]),
          "=f"(d[88]), "=f"(d[89]), "=f"(d[90]), "=f"(d[91]), "=f"(d[92]), "=f"(d[93]), "=f"(d[94]), "=f"(d[95])
        : "l"(desca), "l"(desc));
}
__device__ __forceinline__ void wg_qk_init(uint32_t (&d)[32], uint64_t desca, uint64_t desc) {
    asm volatile("{\n.reg .pred p;\nsetp.ne.b32 p, 0, 0;\n"
        "wgmma.mma_async.sync.aligned.m64n128k16.f16.f16.f16 "
        "{%0,%1,%2,%3,%4,%5,%6,%7,%8,%9,%10,%11,%12,%13,%14,%15,%16,%17,%18,%19,%20,%21,%22,%23,%24,%25,%26,%27,%28,%29,%30,%31}, "
        "%32, %33, p, 1, 1, 0, 0;\n}\n"
        : "=r"(d[0]), "=r"(d[1]), "=r"(d[2]), "=r"(d[3]), "=r"(d[4]), "=r"(d[5]), "=r"(d[6]), "=r"(d[7]),
          "=r"(d[8]), "=r"(d[9]), "=r"(d[10]), "=r"(d[11]), "=r"(d[12]), "=r"(d[13]), "=r"(d[14]), "=r"(d[15]),
          "=r"(d[16]), "=r"(d[17]), "=r"(d[18]), "=r"(d[19]), "=r"(d[20]), "=r"(d[21]), "=r"(d[22]), "=r"(d[23]),
          "=r"(d[24]), "=r"(d[25]), "=r"(d[26]), "=r"(d[27]), "=r"(d[28]), "=r"(d[29]), "=r"(d[30]), "=r"(d[31])
        : "l"(desca), "l"(desc));
}
__device__ __forceinline__ void wg_qk_acc(uint32_t (&d)[32], uint64_t desca, uint64_t desc) {
    asm volatile("{\n.reg .pred p;\nsetp.ne.b32 p, 1, 0;\n"
        "wgmma.mma_async.sync.aligned.m64n128k16.f16.f16.f16 "
        "{%0,%1,%2,%3,%4,%5,%6,%7,%8,%9,%10,%11,%12,%13,%14,%15,%16,%17,%18,%19,%20,%21,%22,%23,%24,%25,%26,%27,%28,%29,%30,%31}, "
        "%32, %33, p, 1, 1, 0, 0;\n}\n"
        : "+r"(d[0]), "+r"(d[1]), "+r"(d[2]), "+r"(d[3]), "+r"(d[4]), "+r"(d[5]), "+r"(d[6]), "+r"(d[7]),
          "+r"(d[8]), "+r"(d[9]), "+r"(d[10]), "+r"(d[11]), "+r"(d[12]), "+r"(d[13]), "+r"(d[14]), "+r"(d[15]),
          "+r"(d[16]), "+r"(d[17]), "+r"(d[18]), "+r"(d[19]), "+r"(d[20]), "+r"(d[21]), "+r"(d[22]), "+r"(d[23]),
          "+r"(d[24]), "+r"(d[25]), "+r"(d[26]), "+r"(d[27]), "+r"(d[28]), "+r"(d[29]), "+r"(d[30]), "+r"(d[31])
        : "l"(desca), "l"(desc));
}
__device__ __forceinline__ void wg_pv_init(uint32_t (&d)[10], uint32_t a0, uint32_t a1, uint32_t a2, uint32_t a3, uint64_t desc) {
    asm volatile("{\n.reg .pred p;\nsetp.ne.b32 p, 0, 0;\n"
        "wgmma.mma_async.sync.aligned.m64n40k16.f16.f16.f16 "
        "{%0,%1,%2,%3,%4,%5,%6,%7,%8,%9}, "
        "{%10,%11,%12,%13}, %14, p, 1, 1, 1;\n}\n"
        : "=r"(d[0]), "=r"(d[1]), "=r"(d[2]), "=r"(d[3]), "=r"(d[4]), "=r"(d[5]), "=r"(d[6]), "=r"(d[7]),
          "=r"(d[8]), "=r"(d[9])
        : "r"(a0), "r"(a1), "r"(a2), "r"(a3), "l"(desc));
}
__device__ __forceinline__ void wg_pv_acc(uint32_t (&d)[10], uint32_t a0, uint32_t a1, uint32_t a2, uint32_t a3, uint64_t desc) {
    asm volatile("{\n.reg .pred p;\nsetp.ne.b32 p, 1, 0;\n"
        "wgmma.mma_async.sync.aligned.m64n40k16.f16.f16.f16 "
        "{%0,%1,%2,%3,%4,%5,%6,%7,%8,%9}, "
        "{%10,%11,%12,%13}, %14, p, 1, 1, 1;\n}\n"
        : "+r"(d[0]), "+r"(d[1]), "+r"(d[2]), "+r"(d[3]), "+r"(d[4]), "+r"(d[5]), "+r"(d[6]), "+r"(d[7]),
          "+r"(d[8]), "+r"(d[9])
        : "r"(a0), "r"(a1), "r"(a2), "r"(a3), "l"(desc));
}

constexpr int Q_ABYTES = 256 * 64 * 2, Q_STB = Q_ABYTES + 192 * 64 * 2;
constexpr int OFF_SIDE = 3 * Q_STB;
constexpr int OFF_XS = OFF_SIDE + 49152;
constexpr int OFF_CS = OFF_XS + 4096;
constexpr int OFF_RC = OFF_CS + 768;
constexpr int OFF_FIX = OFF_RC + 2048;
constexpr int A_WIN = KV_WIN + 4096;
constexpr int OFF_QA = 3 * A_WIN;
constexpr int OFF_LC = OFF_QA + 32768;
constexpr int OFF_FE = 147456;
constexpr int OFF_XT = 196608;
__host__ __device__ constexpr uint32_t o_stage(uint32_t s) { return s == 3 ? OFF_QA : s == 2 ? 0 : (s + 1) * A_WIN; }
__host__ __device__ constexpr uint32_t gu_piece(uint32_t i) { return i < 3 ? OFF_FE + i * 16384 : i < 6 ? (i - 1) * 16384 : (i - 6) * 16384; }
constexpr int OFF_FD = 5 * 16384;
constexpr int OFF_BAR = OFF_XT + 32768;
constexpr int OFF_PART = OFF_BAR + 384;
constexpr int OFF_RED = OFF_PART + 2048;
constexpr int OFF_RT = OFF_RED + 96;
constexpr int OFF_M = OFF_RT + 144;
constexpr int OFF_WR = OFF_M + 72;
constexpr int K_SMEM = OFF_WR + 264;
static_assert(K_SMEM <= 232448 && OFF_FIX + 768 <= OFF_BAR && OFF_QA + 32768 <= OFF_FE, "smem");
constexpr uint32_t CH_OK = 0x38003800u;
constexpr int M_SC = 0,
              M_IVS = 24,
              M_ISC = 32,
              M_OK = 40,
              M_WS = 48,
              M_RIDX = 60,
              M_ORDY = 64;
constexpr uint32_t BB = SB + OFF_BAR;
constexpr uint32_t B_QF = BB, B_EPI = BB + 24, B_RES2 = BB + 56, B_AF = BB + 64, B_RES = BB + 120, B_OF = BB + 128,
                   B_FE = BB + 160, B_FL = BB + 168, B_FD = BB + 184, B_PR = BB + 192, B_FW = B_PR, B_SW = BB + 216,
                   B_QE = BB + 224, B_QAF = BB + 248, B_OE = BB + 288, B_AE = BB + 320, B_KV0 = BB + 376;

constexpr int N_OST = 5, N_XST = 9, N_RT = 11, N_KV1 = 12, N_FW = 13, N_GD = 14, N_DD = 15;

struct Maps { CUtensorMap xa0, wqkv, xa, x0, x, out, w64, wo, r, g, u, d, xs; };

__device__ __forceinline__ float2 ln_coef(const uint4& s) {
    const float mean = __uint_as_float(s.x) * (1.f / D_);
    return make_float2(rsq(fmaxf(fmaf(-mean, mean, fmaf(__uint_as_float(s.y), 1.f / D_, LN_EPS)), LN_EPS)), mean);
}
__device__ __forceinline__ uint32_t order_bits(float r) { const uint32_t u = __float_as_uint(r); return (u & 0x80000000u) ? ~u : (u | 0x80000000u); }
__device__ __forceinline__ uint4 warp_best(const uint4& e) {
    const uint32_t m = redux_max(e.x), row = redux_min(e.x == m ? e.y : 0x7FFFFFFFu);
    const int src = __ffs(__ballot_sync(0xffffffffu, e.y == row)) - 1;
    return make_uint4(m, row, __shfl_sync(0xffffffffu, e.z, src), __shfl_sync(0xffffffffu, e.w, src));
}
__device__ __forceinline__ RouteOut route_out(const uint4& e) {
    RouteOut rt;
    rt.idx = e.y; rt.r = __uint_as_float((e.x & 0x80000000u) ? e.x & 0x7FFFFFFFu : ~e.x); rt.mean = __uint_as_float(e.z); rt.rstd = __uint_as_float(e.w);
    return rt;
}

__device__ __forceinline__ void prep_work(const bf16* __restrict__ x0, const CUtensorMap* tmW, int t) {
    const int c = blockIdx.x, lane = t & 31, warp = warp_uniform(t >> 5);
    const int ki = c >> 4, n = c & 15;
    constexpr uint32_t red = SB + OFF_SIDE, xs = red + 4096;
    if (warp == 0) {
        mbar_expect_tx(B_PR, 32768);
        bulk_load(xs, x0 + (size_t)c * 16 * D_, 32768, B_PR);
        mbar_expect_tx(B_PR + 8, 16384);
        tma_load(xs + 32768, tmW, 2 * D_ + n * 64, ki * 128, B_PR + 8);
        tma_load(xs + 32768 + 8192, tmW, 2 * D_ + n * 64, ki * 128 + 64, B_PR + 8);
    }
    if (t < 32) g_sums[t >> 4][c * 16 + (t & 15)] = make_float4(0.f, 0.f, 0.f, 0.f);
    const uint4 sent = make_uint4(SENT, SENT, SENT, SENT);
    for (int i = t; i < 2 * NFC * 2; i += 96) reinterpret_cast<uint4*>(&g_ypart[0][0][0])[c * (2 * NFC * 2) + i] = sent;
    if (t < 2) reinterpret_cast<uint4*>(g_x2row)[c * 2 + t] = sent;
    else if (t < 8) reinterpret_cast<uint4*>(g_fix)[c * 6 + t - 2] = sent;
    else if (t < 12) (&g_kvc[0][0][0])[c * 4 + t - 8] = 0u;
    else if (t >= 24 && t < 32) (&g_oc[0][0][0][0])[c * 8 + t - 24] = 0u;
    else if (t == 13 && c < 16) (&g_xc[0][0])[c] = 0u;
    else if (t >= 16 && t < 20) (&g_tab[0][0][0][0])[c * 4 + t - 16] = sent;
    else if (t >= 32 && t < 64) reinterpret_cast<uint4*>(&g_xrow[0][0][0])[c * 32 + t - 32] = sent;
    mbar_wait(B_PR, 0);
    #pragma unroll 1
    for (int r = warp; r < 16; r += 3) {
        float s = 0.f, q = 0.f;
        #pragma unroll
        for (int i = 0; i < 4; i++) {
            const uint4 u = lds128(xs + r * 2048 + (lane + 32 * i) * 16);
            const float f[8] = {bf_lo(u.x), bf_hi(u.x), bf_lo(u.y), bf_hi(u.y), bf_lo(u.z), bf_hi(u.z), bf_lo(u.w), bf_hi(u.w)};
            #pragma unroll
            for (int e = 0; e < 8; e++) { s += f[e]; q = fmaf(f[e], f[e], q); }
        }
        #pragma unroll
        for (int o = 16; o > 0; o >>= 1) { s += __shfl_xor_sync(0xffffffffu, s, o); q += __shfl_xor_sync(0xffffffffu, q, o); }
        const float mean = s * (1.f / D_);
        const float var = fmaxf(q * (1.f / D_) - mean * mean, 0.f);
        if (lane == 0) g_rs0[c * 16 + r] = make_float2(rsqrtf(var + LN_EPS), mean);
    }
    named_sync(2, 96);
    if (warp == 0) {
        mbar_expect_tx(B_PR + 16, 32768);
        #pragma unroll
        for (int b = 0; b < 4; b++) tma_load(xs + b * 8192, tmW, (b >> 1) * D_ + n * 64, ki * 128 + (b & 1) * 64, B_PR + 16);
    }
    const int j = t & 7, rg = t >> 3;
    #pragma unroll 1
    for (int blk = 0; blk < 3; blk++) {
        const int type = blk == 0 ? 2 : blk - 1;
        const uint32_t wb = xs + type * 16384;
        if (blk < 2) mbar_wait(B_PR + 8 + 8 * blk, 0);
        float cs[8];
        uint32_t z2[4] = {0u, 0u, 0u, 0u};
        #pragma unroll
        for (int i = 0; i < 8; i++) cs[i] = 0.f;
        #pragma unroll 4
        for (int r = rg; r < 128; r += 12) {
            const uint4 u = lds128(wb + r * 128 + ((j ^ (r & 7)) << 4));
            cs[0] += bf_lo(u.x); cs[1] += bf_hi(u.x); cs[2] += bf_lo(u.y); cs[3] += bf_hi(u.y);
            cs[4] += bf_lo(u.z); cs[5] += bf_hi(u.z); cs[6] += bf_lo(u.w); cs[7] += bf_hi(u.w);
            asm("fma.rn.bf16x2 %0, %1, %1, %0;" : "+r"(z2[0]) : "r"(u.x));
            asm("fma.rn.bf16x2 %0, %1, %1, %0;" : "+r"(z2[1]) : "r"(u.y));
            asm("fma.rn.bf16x2 %0, %1, %1, %0;" : "+r"(z2[2]) : "r"(u.z));
            asm("fma.rn.bf16x2 %0, %1, %1, %0;" : "+r"(z2[3]) : "r"(u.w));
        }
        #pragma unroll
        for (int i = 0; i < 8; i++) { cs[i] += __shfl_xor_sync(0xffffffffu, cs[i], 8); cs[i] += __shfl_xor_sync(0xffffffffu, cs[i], 16); }
        float z = ((bf_lo(z2[0]) + bf_hi(z2[0])) + (bf_lo(z2[1]) + bf_hi(z2[1]))) + ((bf_lo(z2[2]) + bf_hi(z2[2])) + (bf_lo(z2[3]) + bf_hi(z2[3])));
        z += __shfl_xor_sync(0xffffffffu, z, 1); z += __shfl_xor_sync(0xffffffffu, z, 2);
        z += __shfl_xor_sync(0xffffffffu, z, 8); z += __shfl_xor_sync(0xffffffffu, z, 16);
        if (lane < 8) {
            #pragma unroll
            for (int i = 0; i < 8; i++) stsf(red + (warp * 200 + type * 64 + j * 8 + i) * 4, cs[i]);
            if ((lane & 3) == 0) stsf(red + (warp * 200 + 192 + type * 2 + (lane >> 2)) * 4, z);
        }
    }
    named_sync(2, 96);
    for (int i = t; i < 198; i += 96) {
        const float v = ldsf(red + i * 4) + ldsf(red + (200 + i) * 4) + ldsf(red + (400 + i) * 4);
        if (i < 192) g_csum[ki * (3 * D_) + (i >> 6) * D_ + n * 64 + (i & 63)] = v;
        else g_wsq[ki * 96 + ((i - 192) >> 1) * 32 + n * 2 + (i & 1)] = v;
    }
    named_sync(2, 96);
    if (warp == 0) { ctr_arrive(&g_c0); ctr_wait(&g_c0, 128); }
    named_sync(2, 96);
}

__device__ __forceinline__ float pow2_inv(float b) {
    const int e = min(max((int)(__float_as_uint(b) >> 23) + 1, 20), 234);
    return __uint_as_float((uint32_t)(254 - e) << 23);
}
__device__ __forceinline__ void epi_inputs(int L) {
    const int t = tid_now() - 288, mt = cta_now() >> 4, nt = cta_now() & 15;
    float p[2][8], r0[3], r1[3];
    #pragma unroll
    for (int k = 0; k < 2; k++)
        #pragma unroll
        for (int q = 0; q < 8; q++) p[k][q] = __ldcg(g_csum + q * (3 * D_) + ((t + 96 * k) >> 6) * D_ + nt * 64 + ((t + 96 * k) & 63));
    #pragma unroll
    for (int k = 0; k < 2; k++) stsf(SB + OFF_CS + (t + 96 * k) * 4, ((p[k][0] + p[k][1]) + (p[k][2] + p[k][3])) + ((p[k][4] + p[k][5]) + (p[k][6] + p[k][7])));
    bool wait;
    uint32_t n = 0;
    do {
        wait = false;
        #pragma unroll
        for (int k = 0; k < 3; k++) {
            const int row = mt * 256 + min(t + 96 * k, 255);
            if (L == 0) { const float2 s = __ldcg(&g_rs0[row]); r0[k] = s.x; r1[k] = s.y; }
            else { const uint4 s = ld_relaxed4(&g_sums[0][row]); r0[k] = __uint_as_float(s.x); r1[k] = __uint_as_float(s.y); wait = wait || s.w != STAT_FULL; }
        }
    } while (wait && ++n < SPIN_MAX);
    #pragma unroll
    for (int k = 0; k < 3; k++) {
        if (L != 0) {
            const float mean = r0[k] * (1.f / D_);
            const float var = fmaxf(r1[k] * (1.f / D_) - mean * mean, 0.f);
            const float a = 1.f + rsqrtf(var + LN_EPS);
            r0[k] = a * rsqrtf(a * a * var + LN_EPS); r1[k] = mean;
        }
        if (t + 96 * k < 256) sts64f(SB + OFF_RC + (t + 96 * k) * 8, r0[k], r1[k]);
    }
    if (L == 0 && t < 32) {
        float z = 0.f;
        if (t < 6) {
            #pragma unroll
            for (int q = 0; q < 8; q++) z += __ldcg(g_wsq + q * 96 + (t >> 1) * 32 + nt * 2 + (t & 1));
        }
        const float b = sqrtf(z) * (t < 2 ? 34.f * QSCALE : 34.f);
        const float sc = t < 4 ? fminf(pow2_inv(b) * 32768.f, 1.f) : pow2_inv(b);
        const float bk = __shfl_down_sync(0xffffffffu, b, 2), sk = __shfl_down_sync(0xffffffffu, sc, 2);
        if (t < 6) stsf(SB + OFF_M + M_SC + t * 4, t < 2 ? sc * QSCALE : sc);
        if (t < 2) { stsf(SB + OFF_M + M_ISC + t * 4, 1.f / (sc * sk)); sts32(SB + OFF_M + M_OK + t * 4, sc == 1.f && sk == 1.f && b * bk < 60000.f ? CH_OK : 0u); }
        if (t == 4 || t == 5) stsf(SB + OFF_M + M_IVS + (t - 4) * 4, 1.f / sc);
    }
}

__device__ __forceinline__ int ypos_col(int p) { return (p >> 7) * 128 + ((p >> 1) & 7) * 16 + (p & 1) * 8 + ((p >> 4) & 7); }

template <int NT>
__device__ __forceinline__ float ffn_finish(int L, const RouteOut& rt, int t, uint32_t red, int bid) {
    constexpr int NL = (2 * NFC + NT - 1) / NT;
    const int c = cta_now(), col = ypos_col(c * 8 + (t & 7));
    const uint32_t* src = &g_ypart[L][t >> 1][c * 8 + (t & 1) * 4];
    uint32_t n = 0, xp;
    do { xp = ld_relaxed(&g_xrow[L][rt.idx >> 7][((col >> 5) & 7) * 64 + (col >> 8) * 16 + (col & 6) * 2 + ((col >> 3) & 3)]); } while (xp == SENT && ++n < SPIN_MAX);
    uint4 v[NL];
    #pragma unroll
    for (int i = 0; i < NL; i++) v[i] = t + NT * i < 2 * NFC ? ld_relaxed4(src + i * (NT / 2) * D_) : make_uint4(0u, 0u, 0u, 0u);
    const float xv = (col & 1) ? bf_hi(xp) : bf_lo(xp);
    float rsel = bf_round(rcp(1.f + ex2(bf_round(rt.r) * -1.4426950408889634f))), xn = bf_round((xv - rt.mean) * rt.rstd);
    asm volatile("" : "+f"(rsel), "+f"(xn));
    while (true) {
        bool wait = false;
        #pragma unroll
        for (int i = 0; i < NL; i++) wait = wait || has_sent(v[i]);
        if (!wait || ++n >= SPIN_MAX) break;
        #pragma unroll
        for (int i = 0; i < NL; i++) if (t + NT * i < 2 * NFC) v[i] = ld_relaxed4(src + i * (NT / 2) * D_);
    }
    spin_check(n);
    __syncwarp();
    float a[4] = {0.f, 0.f, 0.f, 0.f};
    #pragma unroll
    for (int i = 0; i < NL; i++) { a[0] += __uint_as_float(v[i].x); a[1] += __uint_as_float(v[i].y); a[2] += __uint_as_float(v[i].z); a[3] += __uint_as_float(v[i].w); }
    const bool b1 = t & 2, b2 = t & 4;
    a[0] = (b1 ? a[1] : a[0]) + __shfl_xor_sync(0xffffffffu, b1 ? a[0] : a[1], 2);
    a[2] = (b1 ? a[3] : a[2]) + __shfl_xor_sync(0xffffffffu, b1 ? a[2] : a[3], 2);
    a[0] = (b2 ? a[2] : a[0]) + __shfl_xor_sync(0xffffffffu, b2 ? a[0] : a[2], 4);
    a[0] += __shfl_xor_sync(0xffffffffu, a[0], 8); a[0] += __shfl_xor_sync(0xffffffffu, a[0], 16);
    if ((t & 31) < 8) stsf(red + (t >> 5) * 32 + (t & 1) * 16 + (t & 6) * 2, a[0]);
    named_sync(bid, NT);
    float y = 0.f, y2 = 0.f;
    #pragma unroll
    for (int i = 0; i < NT / 32; i++) { const float p = ldsf(red + (t & 7) * 4 + i * 32); if (i & 1) y2 += p; else y += p; }
    y += y2;
    return bf_round(xv + bf_round(xn + bf_round(bf_round(y) * rsel)));
}

__device__ __forceinline__ void routed_qkv(int ridx) {
    const int t = tid_now() - 288, c = cta_now(), lane = t & 31, warp = t >> 5;
    constexpr uint32_t red = SB + OFF_RED;
    {
        uint4 v[3];
        uint32_t n = 0;
        do {
            v[0] = ld_relaxed4(g_x2row + t * 4); v[1] = ld_relaxed4(g_x2row + (t + 96) * 4);
            v[2] = t < 64 ? ld_relaxed4(g_x2row + (t + 192) * 4) : make_uint4(0u, 0u, 0u, 0u);
        } while ((has_sent(v[0]) || has_sent(v[1]) || has_sent(v[2])) && ++n < SPIN_MAX);
        spin_check(n);
        __syncwarp();
        TL(288, 0, 21);
        float f[12];
        float s = 0.f;
        #pragma unroll
        for (int i = 0; i < 3; i++) { f[4*i] = __uint_as_float(v[i].x); f[4*i+1] = __uint_as_float(v[i].y); f[4*i+2] = __uint_as_float(v[i].z); f[4*i+3] = __uint_as_float(v[i].w); }
        #pragma unroll
        for (int i = 0; i < 12; i++) s += f[i];
        s = warp_sum(s);
        if (lane == 0) stsf(red + warp * 4, s);
        named_sync(2, 96);
        const float mean = (ldsf(red) + ldsf(red + 4) + ldsf(red + 8)) * (1.f / D_);
        float q = 0.f;
        #pragma unroll
        for (int i = 0; i < 12; i++) { f[i] -= mean; if (i < 8 || t < 64) q = fmaf(f[i], f[i], q); }
        q = warp_sum(q);
        if (lane == 0) stsf(red + 16 + warp * 4, q);
        named_sync(2, 96);
        const float rstd = rsqrtf((ldsf(red + 16) + ldsf(red + 20) + ldsf(red + 24)) * (1.f / D_) + LN_EPS);
        #pragma unroll
        for (int i = 0; i < 3; i++)
            if (i < 2 || t < 64) sts128(SB + OFF_XS + (t + 96 * i) * 16, make_uint4(pack_bf16(0.f, f[4*i] * rstd), pack_bf16(0.f, f[4*i+1] * rstd), pack_bf16(0.f, f[4*i+2] * rstd), pack_bf16(0.f, f[4*i+3] * rstd)));
    }
    named_sync(2, 96);
    TL(288, 0, 22);
    mbar_wait(B_SW, 0);
    TL(288, 0, 23);
    float a[8];
    #pragma unroll
    for (int i = 0; i < 8; i++) a[i] = 0.f;
    const uint32_t wa = SB + OFF_SIDE + t * 16, xa = SB + OFF_XS + (t / 3) * 4;
    #pragma unroll 4
    for (int i = 0; i < 32; i++) {
        const uint4 u = lds128(wa + i * 1536);
        const float xv = ldsf(xa + i * 128);
        a[0] = fmaf(xv, bf_lo(u.x), a[0]); a[1] = fmaf(xv, bf_hi(u.x), a[1]); a[2] = fmaf(xv, bf_lo(u.y), a[2]); a[3] = fmaf(xv, bf_hi(u.y), a[3]);
        a[4] = fmaf(xv, bf_lo(u.z), a[4]); a[5] = fmaf(xv, bf_hi(u.z), a[5]); a[6] = fmaf(xv, bf_lo(u.w), a[6]); a[7] = fmaf(xv, bf_hi(u.w), a[7]);
    }
    named_sync(2, 96);
    TL(288, 0, 41);
    sts128(SB + OFF_SIDE + t * 32, make_uint4(__float_as_uint(a[0]), __float_as_uint(a[1]), __float_as_uint(a[2]), __float_as_uint(a[3])));
    sts128(SB + OFF_SIDE + t * 32 + 16, make_uint4(__float_as_uint(a[4]), __float_as_uint(a[5]), __float_as_uint(a[6]), __float_as_uint(a[7])));
    named_sync(2, 96);
    {
        float y = 0.f;
        #pragma unroll
        for (int i = 0; i < 8; i++) y += ldsf(SB + OFF_SIDE + ((t & 3) * 8 + i) * 96 + (t >> 2) * 4);
        y += __shfl_xor_sync(0xffffffffu, y, 1); y += __shfl_xor_sync(0xffffffffu, y, 2);
        if ((t & 3) == 0) st_relaxed(g_fix + c * 24 + (t >> 2), not_sent(y));
    }
    if ((ridx >> 8) == (c >> 4) && t < 24) {
        const uint32_t* src = g_fix + (t >> 3) * D_ + (c & 15) * 64 + (t & 7) * 8;
        uint4 a, b;
        uint32_t n = 0;
        do { a = ld_relaxed4(src); b = ld_relaxed4(src + 4); } while ((has_sent(a) || has_sent(b)) && ++n < SPIN_MAX);
        spin_check(n);
        const int hh = t >> 2, ch = t & 3, lr = ridx & 255;
        const float hs = ldsf(SB + OFF_M + M_SC + hh * 4);
        sts128(SB + OFF_FIX + t * 16, make_uint4(pack_f16(__uint_as_float(a.x) * hs, __uint_as_float(a.y) * hs), pack_f16(__uint_as_float(a.z) * hs, __uint_as_float(a.w) * hs),
                                                 pack_f16(__uint_as_float(b.x) * hs, __uint_as_float(b.y) * hs), pack_f16(__uint_as_float(b.z) * hs, __uint_as_float(b.w) * hs)));
        sts32(SB + OFF_FIX + 512 + t * 4, SB + (hh < 2 ? OFF_QA + hh * 16384 + (lr >> 6) * 4096 + ch * 1024 + (lr & 63) * 16
                                                        : (hh & 1) * OFF_FE + (hh >> 2) * 16384 + ch * 4096 + lr * 16));
    }
    __syncwarp();
}

#define DYN 1
#define XP0 2
#define XP1 7
#define FW_NS 1000
__device__ __forceinline__ void ffn_load(const Maps& mp, int i, uint32_t dst, uint32_t bar, bool last_use) {
    if (i < 8) tma_load_h(dst, (i & 1) ? &mp.u : &mp.g, blockIdx.x * 32, (i >> 1) * 256, bar, last_use);
    else tma_load3_h(dst, &mp.d, 0, blockIdx.x * 32, (i - 8) * 4, bar, last_use);
}
__device__ __forceinline__ void side_role(const Maps& mp, const bf16* __restrict__ x0, const bf16* __restrict__ wo, const bf16* __restrict__ w_r) {
    prep_work(x0, &mp.w64, threadIdx.x - 288);
    epi_inputs(0);
    #pragma unroll 1
    for (int L = 0; L < 2; L++) {
        const int t = tid_now() - 288, lane = t & 31, sw = warp_uniform(t >> 5);
        const int c = blockIdx.x, mt = c >> 4, nt = c & 15;
        named_sync(2, 96);
        if (t == 0) mbar_arrive(B_EPI);
        TL(288, L, 5);
        if (L == 0) {
            float ws = 0.f;
            for (int i = t; i < D_ / 8; i += 96) {
                const uint4 v = reinterpret_cast<const uint4*>(w_r)[i];
                ws += ((bf_lo(v.x) + bf_hi(v.x)) + (bf_lo(v.y) + bf_hi(v.y))) + ((bf_lo(v.z) + bf_hi(v.z)) + (bf_lo(v.w) + bf_hi(v.w)));
            }
            ws = warp_sum(ws);
            if (lane == 0) stsf(SB + OFF_M + M_WS + sw * 4, ws);
            if (t >= 94) sts32(SB + OFF_M + M_ORDY + (t - 94) * 4, 0u);
            if (t < 66) sts32(SB + OFF_WR + t * 4, t < 64 ? reinterpret_cast<const uint32_t*>(w_r)[(nt >> 1) * 64 + (t >> 3) * 8 + (t & 1) * 4 + ((t >> 1) & 3)] : 0x3F803F80u);
        }
        __syncwarp();
        if (sw == 0) {
            char* kv = g_kv + (size_t)(nt * 16 + mt) * KV_WIN;
            mbar_wait(B_KV0, L);
            bulk_store(kv, SB, KV_WIN);
            bulk_commit();
            publish(&g_kvc[L][nt * 2][mt]);
            TL(288, L, 6);
            named_sync(N_KV1, 64);
            bulk_store(kv + 8 * KV_WIN, SB + OFF_FE, KV_WIN);
            bulk_commit();
            publish(&g_kvc[L][nt * 2 + 1][mt]);
        }
        if (sw < 2) {
            #pragma unroll 1
            for (int p = 0; p < 2; p++) {
                named_sync(N_OST + 2 * p + sw, p > sw ? 192 : 160);
                TL(p ? -1 : 288, L, 30); TL(p ? 288 : -1, L, 31);
                if (p == 1) mbar_arrive_elect(B_QAF);
                ctr_arrive(&g_oc[L][mt * 2 + sw][p][nt]);
            }
        } else {
            named_sync(N_FW, 64);
            mbar_expect_tx(B_RES, 32768);
            #pragma unroll
            for (int i = 0; i < 4; i++) tma_load_h(SB + OFF_XT + i * 8192, L == 0 ? &mp.x0 : &mp.x, (nt >> 1) * 128 + (i >> 1) * 64, mt * 256 + (nt & 1) * 128 + (i & 1) * 64, B_RES, true);
            if (c < NFC) {
                #pragma unroll 1
                for (int r = 0; r < 4; r++) {
                    __nanosleep(FW_NS);
                    if (r > 0) mbar_wait(B_FW, (r + L) & 1);
                    const uint32_t bar = r < 3 ? B_FW : B_FE;
                    mbar_expect_tx(bar, 3 * 16384);
                    #pragma unroll 1
                    for (int b = 0; b < 3; b++) ffn_load(mp, 9 - 3 * r + b, SB + OFF_FE + b * 16384, bar, r == 3);
                }
            }
        }
        if (sw == 2) {
            l2_prefetch(reinterpret_cast<const char*>(wo) + (size_t)c * 16384, 16384);
            mbar_wait(B_RES, L);
            const uint32_t lr = lds32(SB + OFF_M + M_RIDX) - (mt * 256 + (nt & 1) * 128);
            if (L == 1 && lr < 128u && lane < 16) {
                const uint4 a = ld_relaxed4(g_x2row + (nt >> 1) * 128 + lane * 8), b = ld_relaxed4(g_x2row + (nt >> 1) * 128 + lane * 8 + 4);
                sts128(SB + OFF_XT + (lane >> 3) * 16384 + lr * 128 + (((lane & 7) ^ (lr & 7)) << 4),
                       make_uint4(__byte_perm(a.x, a.y, 0x7632), __byte_perm(a.z, a.w, 0x7632), __byte_perm(b.x, b.y, 0x7632), __byte_perm(b.z, b.w, 0x7632)));
            }
            if (L == 1) {
                #pragma unroll
                for (int i = 0; i < 4; i++) {
                    const float2 r = ln_coef(ld_relaxed4(&g_sums[0][mt * 256 + (nt & 1) * 128 + i * 32 + lane]));
                    const float a = i * 32 + lane == lr ? 0.f : r.x;
                    sts64f(SB + OFF_LC + (i * 32 + lane) * 8, a, -a * r.y);
                }
            }
            __syncwarp();
            mbar_arrive_elect(B_RES2);
            named_sync(N_OST + 2, 192);
            l2_prefetch(&g_ypart[L][0][0] + c * (NFC * 8), NFC * 32);
            l2_prefetch(&g_sums[L][c * 16], 256);
            l2_prefetch(&g_xrow[L][0][0] + c * 64, 256);
            l2_prefetch(&g_tab[L][0][0][0] + c * 2, 32);
            l2_prefetch(c < 32 ? &g_x2row[c * 32] : c < 40 ? &g_kvc[1][(c - 32) * 4][0] : &g_xc[0][0], c < 40 ? 128 : 64);
            l2_prefetch(&g_fix[c * 24], 96);
            uint32_t ready, n = 0;
            do {
                ready = __ballot_sync(0xffffffffu, ld_acquire(&g_oc[L][mt * 2 + (nt & 1)][1][lane & 15]) != 0);
                fence_async_global();
                if (lane == 0) sts_release(SB + OFF_M + M_ORDY + 4 * L, DYN ? ready & ready >> 1 : ready == 0xFFFFFFFFu ? ready : 0u);
            } while (ready != 0xFFFFFFFFu && ++n < SPIN_MAX);
            spin_check(n);
        }
        if (sw < 2) {
            named_sync(N_XST + sw, 160);
            const int row0 = mt * 256 + (nt & 1) * 128 + sw * 64, col0 = (nt >> 1) * 128;
            #pragma unroll 1
            for (int h = 0; h < 8; h++) {
                if (L == 0) bulk_wait_n<XP0>(); else bulk_wait_n<XP1>();
                tma_store(L == 0 ? &mp.xs : &mp.out, SB + OFF_XT + (h & 1) * 16384 + sw * 8192 + (h >> 1) * 2048, col0 + (h & 1) * 64, row0 + (h >> 1) * 16);
                bulk_commit();
            }
            publish(&g_xc[L][mt]);
            TL(288, L, 14);
        }
        if (L == 0) {
            __syncwarp();
            named_sync(N_RT, 128);
            const RouteOut rt = route_out(lds128(SB + OFF_RT + 128));
            if (t == 0) { sts32(SB + OFF_M + M_RIDX, rt.idx); if (c == 0) g_c0 = 0u; }
            epi_inputs(1);
            const float v = ffn_finish<96>(0, rt, t, SB + OFF_RED, 2);
            TL(288, L, 20);
            if (t < 8) st_relaxed(g_x2row + ypos_col(c * 8 + t), not_sent(v));
            routed_qkv(rt.idx);
        }
    }
}

struct EpiIn { float2 c2[4]; float hs; };
template <int HH>
__device__ __forceinline__ EpiIn qkv_epi_in(int t) {
    EpiIn e;
    #pragma unroll
    for (int jj = 0; jj < 4; jj++) e.c2[jj] = lds64f(SB + OFF_CS + (HH * 32 + jj * 8) * 4 + t * 8);
    e.hs = ldsf(SB + OFF_M + M_SC + HH * 4);
    return e;
}
template <int HH, int NEXT>
__device__ __forceinline__ void qkv_epi_head(const float (&acc0)[96], const float (&acc1)[96], const float (&cf)[4], const float (&nm)[4], EpiIn& in, uint32_t dst, int t) {
    const EpiIn e = in;
    #pragma unroll
    for (int i = 0; i < 4; i++) {
        const float* a = (i >> 1) ? acc1 : acc0;
        const float sc = cf[i] * e.hs;
        uint32_t pk[4];
        #pragma unroll
        for (int jj = 0; jj < 4; jj++)
            pk[jj] = pack_f16(fmaf(nm[i], e.c2[jj].x, a[4 * (4 * HH + jj) + 2 * (i & 1)]) * sc, fmaf(nm[i], e.c2[jj].y, a[4 * (4 * HH + jj) + 2 * (i & 1) + 1]) * sc);
        stsm4(dst + (i >> 1) * (HH < 2 ? 4096 : 1024) + (i & 1) * 128, pk[0], pk[1], pk[2], pk[3]);
        if (i == 1 && NEXT >= 0) in = qkv_epi_in<NEXT < 0 ? 0 : NEXT>(t);
    }
}
__device__ __forceinline__ void qkv_patch(int lane, uint32_t mask) {
    const uint4 v = lds128(SB + OFF_FIX + lane * 16);
    const uint32_t dst = lds32(SB + OFF_FIX + 512 + lane * 4);
    __syncwarp();
    asm volatile("{\n.reg .pred q;\nsetp.ne.u32 q, %5, 0;\n@q st.shared.v4.b32 [%0], {%1, %2, %3, %4};\n}"
                 :: "r"(dst), "r"(v.x), "r"(v.y), "r"(v.z), "r"(v.w), "r"((mask >> lane) & 1) : "memory");
}

template <bool INIT>
__device__ __forceinline__ void qkv_step(float (&acc0)[96], float (&acc1)[96], uint32_t st, int wg) {
    const uint64_t da = desc_sw128(SB, 16, 1024) + ((st * Q_STB + wg * 16384) >> 4);
    const uint64_t db = desc_sw128(SB + Q_ABYTES, 8192, 1024) + ((st * Q_STB) >> 4);
    wg_fence();
    if (INIT) { wg_gemm_n192_init(acc0, da, db); wg_gemm_n192_init(acc1, da + (8192 >> 4), db); }
    #pragma unroll
    for (int kk = INIT ? 1 : 0; kk < 4; kk++) {
        wg_gemm_n192(acc0, da + kk * 2, db + kk * 128);
        wg_gemm_n192(acc1, da + (8192 >> 4) + kk * 2, db + kk * 128);
    }
    wg_commit();
}
__device__ __forceinline__ void qkv_phase(int L, int wg) {
    const uint32_t rb = L * 32;
    float acc0[96], acc1[96];
    const bool leader = (tid_now() & 127) == 0;
    mbar_wait(rb + B_QF, 0);
    TL(0, L, 1);
    qkv_step<true>(acc0, acc1, 0, wg);
    uint32_t st = 1, ph = 0;
    #pragma unroll 1
    for (int k = 1; k < 16; k++) {
        mbar_wait(rb + B_QF + 8 * st, ph);
        qkv_step<false>(acc0, acc1, st, wg);
        wg_wait<1>();
        if (leader) mbar_arrive(rb + B_QE + 8 * (st == 0 ? 2 : st - 1));
        if (++st == 3) { st = 0; ph ^= 1; }
    }
    const int tid = tid_now(), lane = tid & 31, w = (tid >> 5) & 3, g = lane >> 2, t = lane & 3;
    mbar_wait(B_EPI, L);
    float cf[4], nm[4];
    #pragma unroll
    for (int i = 0; i < 4; i++) { const float2 r = lds64f(SB + OFF_RC + (wg * 128 + w * 16 + g + (i >> 1) * 64 + (i & 1) * 8) * 8); cf[i] = r.x; nm[i] = -r.y; }
    const int d = (int)lds32(SB + OFF_M + M_RIDX) - (cta_now() >> 4) * 256;
    const bool own = L == 1 && (d >> 7) == wg && ((d >> 4) & 3) == w;
    EpiIn in = qkv_epi_in<2>(t);
    wg_wait<0>();
    TL(0, L, 2);
    TL(128, L, 40);
    named_sync(1, 256);
    const uint32_t dk = SB + wg * 2048 + (lane >> 3) * 4096 + (w * 16 + (lane & 7)) * 16;
    const uint32_t dq = SB + OFF_QA + wg * 8192 + (lane >> 3) * 1024 + (w * 16 + (lane & 7)) * 16;
    qkv_epi_head<2, 4>(acc0, acc1, cf, nm, in, dk, t);
    qkv_epi_head<4, 0>(acc0, acc1, cf, nm, in, dk + 16384, t);
    if (own) qkv_patch(lane, 0x0F0F00u);
    #pragma unroll
    for (int s = 0; s < 3; s++) sts128(SB + s * A_WIN + KV_WIN + tid * 16, make_uint4(0x3C003C00u, 0x3C003C00u, 0x3C003C00u, 0x3C003C00u));
    fence_async_smem();
    __syncwarp();
    mbar_arrive_elect(B_KV0);
    TL(0, L, 4);
    qkv_epi_head<0, 1>(acc0, acc1, cf, nm, in, dq, t);
    qkv_epi_head<1, 3>(acc0, acc1, cf, nm, in, dq + 16384, t);
    qkv_epi_head<3, 5>(acc0, acc1, cf, nm, in, dk + OFF_FE, t);
    qkv_epi_head<5, -1>(acc0, acc1, cf, nm, in, dk + OFF_FE + 16384, t);
    if (own) qkv_patch(lane, 0xF0F0FFu);
    fence_async_smem();
    named_sync(3 + wg, 128);
    TL(0, L, 3);
}

struct Unit {
    uint32_t o[8];
    uint32_t l, bz, sc;
    uint32_t ch[2];
};
template <int H> __device__ __forceinline__ uint32_t hdup(uint32_t v) {
    uint32_t r;
    if (H) asm("{.reg .b16 l, h; mov.b32 {l, h}, %1; mov.b32 %0, {h, h};}" : "=r"(r) : "r"(v));
    else asm("{.reg .b16 l, h; mov.b32 {l, h}, %1; mov.b32 %0, {l, l};}" : "=r"(r) : "r"(v));
    return r;
}
__device__ __forceinline__ uint32_t hmax2(uint32_t a, uint32_t b) { uint32_t r; asm("max.f16x2 %0, %1, %2;" : "=r"(r) : "r"(a), "r"(b)); return r; }
__device__ __forceinline__ uint32_t hadd2(uint32_t a, uint32_t b) { uint32_t r; asm("add.rn.f16x2 %0, %1, %2;" : "=r"(r) : "r"(a), "r"(b)); return r; }
__device__ __forceinline__ uint32_t hsub2(uint32_t a, uint32_t b) { uint32_t r; asm("sub.rn.f16x2 %0, %1, %2;" : "=r"(r) : "r"(a), "r"(b)); return r; }
__device__ __forceinline__ uint32_t hfma2(uint32_t a, uint32_t b, uint32_t c) { uint32_t r; asm("fma.rn.f16x2 %0, %1, %2, %3;" : "=r"(r) : "r"(a), "r"(b), "r"(c)); return r; }
__device__ __forceinline__ uint32_t exp2_h2(uint32_t s, uint32_t bz, uint32_t& ch) {
    uint32_t z, w, d;
    asm("fma.rn.relu.f16x2 %0, %1, %2, %3;" : "=r"(z) : "r"(s), "r"(0x00400040u), "r"(bz));
    asm("lop3.b32 %0, %1, 0x003F003F, %0, 0xC2;" : "+r"(ch) : "r"(z));
    asm("fma.rn.f16x2 %0, %1, %2, %3;" : "=r"(w) : "r"(ch), "r"(0x30A630A6u), "r"(0xACCCACCCu));
    asm("{.reg .b32 n; neg.f16x2 n, %1; fma.rn.relu.f16x2 %0, n, %1, %2;}" : "=r"(d) : "r"(w), "r"(0x00580058u));
    return (z << 4) - d;
}
__device__ __forceinline__ void exp_tile(uint32_t (&p)[32], const uint32_t (&s)[32], Unit& u) {
    #pragma unroll
    for (int i = 0; i < 32; i++) p[i] = exp2_h2(s[i], (i & 1) ? hdup<1>(u.bz) : hdup<0>(u.bz), u.ch[i & 1]);
}
__device__ __forceinline__ void issue_qk(uint32_t (&s)[32], uint64_t dq, uint64_t dk) {
    wg_qk_init(s, dq, dk); wg_qk_acc(s, dq + (2048 >> 4), dk + (8192 >> 4));
    wg_commit();
}
template <bool INIT>
__device__ __forceinline__ void issue_pv(uint32_t (&h)[10], const uint32_t (&p)[32], uint64_t dv) {
    #pragma unroll
    for (int k = 0; k < 8; k++) {
        if (INIT && k == 0) wg_pv_init(h, p[0], p[1], p[2], p[3], dv);
        else wg_pv_acc(h, p[4*k], p[4*k+1], p[4*k+2], p[4*k+3], dv + k * 16);
    }
    wg_commit();
}
__device__ __forceinline__ void unit_init(Unit& u, const uint32_t (&s)[32], uint32_t ok) {
    uint32_t m0 = s[0], m1 = s[1];
    #pragma unroll
    for (int i = 1; i < 16; i++) { m0 = hmax2(m0, s[2 * i]); m1 = hmax2(m1, s[2 * i + 1]); }
    uint32_t m = hmax2(__byte_perm(m0, m1, 0x5410), __byte_perm(m0, m1, 0x7632));
    m = hmax2(m, __shfl_xor_sync(0xffffffffu, m, 1)); m = hmax2(m, __shfl_xor_sync(0xffffffffu, m, 2));
    float f0, f1; h2_unpack(m, f0, f1);
    u.ch[0] = fabsf(f0) < 1000.f ? ok : 0u; u.ch[1] = fabsf(f1) < 1000.f ? ok : 0u;
    f0 = (18.f - ceilf(f0)) * 3.814697265625e-06f; f1 = (18.f - ceilf(f1)) * 3.814697265625e-06f;
    u.bz = pack_f16(f0, f1); u.sc = 0u; u.l = 0u;
    #pragma unroll
    for (int i = 0; i < 8; i++) u.o[i] = 0u;
}
template <bool MORE>
__device__ __forceinline__ void unit_flush(Unit& u, const uint32_t (&h)[10]) {
    u.l = hfma2(u.l, u.sc, __byte_perm(h[8], h[9], 0x5410));
    #pragma unroll
    for (int i = 0; i < 8; i++) u.o[i] = hfma2(u.o[i], (i & 1) ? hdup<1>(u.sc) : hdup<0>(u.sc), h[i]);
    if (MORE) {
        const uint32_t ex = u.l & 0x7C007C00u;
        u.sc = 0x84008400u - ex;
        u.bz = hsub2(hadd2(u.bz, 0x04800480u), ex >> 4);
    }
}
__device__ __forceinline__ char* o_block(int wg, int pass) { const int c = cta_now(); return g_o + (size_t)((((c >> 4) * 2 + wg) * 2 + pass) * 16 + (c & 15)) * 8192; }
__device__ __forceinline__ uint32_t unit_store(const Unit& u, char* dst, float ivs) {
    uint32_t bad = 0;
    float lf[2]; h2_unpack(u.l, lf[0], lf[1]);
    #pragma unroll
    for (int h = 0; h < 2; h++) {
        uint32_t b = __ballot_sync(0xffffffffu, (~u.ch[h] & CH_OK) != 0 || !(lf[h] >= 2.f && lf[h] <= 65504.f));
        b |= b >> 1; b = (b | b >> 2) & 0x11111111u;
        const float inv = ivs * rcp(lf[h]);
        #pragma unroll
        for (int j = 0; j < 4; j++) { float x, y; h2_unpack(u.o[2 * j + h], x, y); *reinterpret_cast<uint32_t*>(dst + j * 1024 + h * 128) = pack_bf16(x * inv, y * inv); }
        bad |= b << h;
    }
    return bad;
}
__device__ __noinline__ void exact_rows(int L, int pass, int wg, uint32_t bad) {
    const int tid = tid_now() & 127, lane = tid & 31, w = tid >> 5;
    const int head = (cta_now() & 15) * 2 + pass;
    const uint32_t scr = SB + OFF_PART + wg * 1024;
    if (lane == 0) sts32(scr + w * 4, bad);
    if (tid < 8) ctr_wait(&g_kvc[L][head][tid], 1);
    named_sync(3 + wg, 128);
    const float isc = ldsf(SB + OFF_M + M_ISC + pass * 4), ivs = ldsf(SB + OFF_M + M_IVS + pass * 4);
    const char* kv = g_kv + (size_t)head * 8 * KV_WIN + tid * 16;
    #pragma unroll 1
    for (int ww = 0; ww < 4; ww++) {
        uint32_t m = lds32(scr + ww * 4);
        #pragma unroll 1
        while (m) {
            const int bit = __ffs(m) - 1;
            m &= m - 1;
            const uint32_t ro = ((bit >> 1) & 1) * 4096 + (ww * 16 + (bit & 1) * 8 + (bit >> 2)) * 16, qa = SB + OFF_QA + pass * 16384 + wg * 8192 + ro;
            float q[32], a[32], mx = -INFINITY, l = 0.f;
            #pragma unroll
            for (int ch = 0; ch < 4; ch++) {
                const uint4 u = lds128(qa + ch * 1024);
                h2_unpack(u.x, q[8*ch], q[8*ch+1]); h2_unpack(u.y, q[8*ch+2], q[8*ch+3]); h2_unpack(u.z, q[8*ch+4], q[8*ch+5]); h2_unpack(u.w, q[8*ch+6], q[8*ch+7]);
            }
            #pragma unroll
            for (int i = 0; i < 32; i++) a[i] = 0.f;
            #pragma unroll 1
            for (int it = 0; it < 16; it += 4) {
                uint4 u[4][8];
                #pragma unroll
                for (int i = 0; i < 4; i++)
                    #pragma unroll
                    for (int ch = 0; ch < 8; ch++) u[i][ch] = __ldcg(reinterpret_cast<const uint4*>(kv + ((it + i) >> 1) * KV_WIN + (i & 1) * 2048 + ch * 4096));
                float s[4], mn = mx;
                #pragma unroll
                for (int i = 0; i < 4; i++) {
                    s[i] = 0.f;
                    #pragma unroll
                    for (int ch = 0; ch < 4; ch++) {
                        const uint32_t v[4] = {u[i][ch].x, u[i][ch].y, u[i][ch].z, u[i][ch].w};
                        #pragma unroll
                        for (int e = 0; e < 4; e++) { float x, y; h2_unpack(v[e], x, y); s[i] = fmaf(x, q[8*ch + 2*e], fmaf(y, q[8*ch + 2*e + 1], s[i])); }
                    }
                    mn = fmaxf(mn, s[i]);
                }
                const float al = ex2((mx - mn) * isc);
                mx = mn; l *= al;
                #pragma unroll
                for (int i = 0; i < 32; i++) a[i] *= al;
                #pragma unroll
                for (int i = 0; i < 4; i++) {
                    const float p = ex2((s[i] - mx) * isc);
                    l += p;
                    #pragma unroll
                    for (int ch = 0; ch < 4; ch++) {
                        const uint32_t v[4] = {u[i][4 + ch].x, u[i][4 + ch].y, u[i][4 + ch].z, u[i][4 + ch].w};
                        #pragma unroll
                        for (int e = 0; e < 4; e++) { float x, y; h2_unpack(v[e], x, y); a[8*ch + 2*e] = fmaf(p, x, a[8*ch + 2*e]); a[8*ch + 2*e + 1] = fmaf(p, y, a[8*ch + 2*e + 1]); }
                    }
                }
            }
            const float mw = warp_max(mx);
            if (lane == 0) stsf(scr + 16 + w * 4, mw);
            named_sync(3 + wg, 128);
            const float al = ex2((mx - fmaxf(fmaxf(ldsf(scr + 16), ldsf(scr + 20)), fmaxf(ldsf(scr + 24), ldsf(scr + 28)))) * isc);
            l *= al;
            #pragma unroll
            for (int i = 0; i < 32; i++) a[i] *= al;
            l = warp_sum(l);
            #pragma unroll
            for (int j = 0; j < 31; j++) {
                const int o = j < 16 ? 16 : j < 24 ? 8 : j < 28 ? 4 : j < 30 ? 2 : 1, i = j - (32 - 2 * o);
                const bool up = lane & o;
                const float lo = a[i], hi = a[i + o];
                a[i] = (up ? hi : lo) + __shfl_xor_sync(0xffffffffu, up ? lo : hi, o);
            }
            stsf(scr + 32 + (w * 33 + lane) * 4, a[0]);
            if (lane == 0) stsf(scr + 32 + (w * 33 + 32) * 4, l);
            named_sync(3 + wg, 128);
            if (w == 0) {
                float o = 0.f, ls = 0.f;
                #pragma unroll
                for (int i = 0; i < 4; i++) { o += ldsf(scr + 32 + (i * 33 + lane) * 4); ls += ldsf(scr + 32 + (i * 33 + 32) * 4); }
                *reinterpret_cast<unsigned short*>(o_block(wg, pass) + ro + (lane >> 3) * 1024 + (lane & 7) * 2) = (unsigned short)pack_bf16(o * ivs / ls, 0.f);
            }
        }
    }
    named_sync(3 + wg, 128);
}

__device__ __forceinline__ void attention_phase(int L, int wg) {
    const uint32_t rb = L * 32;
    constexpr uint64_t dk0 = desc_plain(SB, 4096, 128), dv0 = desc_plain(SB + 16384, 128, 4096);
    constexpr int T1 = 2048 >> 4;
    uint32_t st = 0, ph = 0;
    #pragma unroll 1
    for (int pass = 0; pass < 2; pass++) {
        const uint64_t dqa = desc_plain(SB + OFF_QA, 1024, 128) + (pass * 4 + wg * 2) * (4096 >> 4), dqc = dqa + (4096 >> 4);
        Unit a, c;
        st = warp_uniform(st); ph = warp_uniform(ph);
        uint32_t SA[32], SC[32], PA[32], PC[32], ha[10], hc[10], bad;
        #pragma unroll
        for (int i = 0; i < 10; i++) hc[i] = 0u;
        #pragma unroll
        for (int i = 0; i < 32; i++) PC[i] = 0u;
        const uint32_t ok = lds32(SB + OFF_M + M_OK + pass * 4);
        mbar_wait(rb + B_AF + 8 * st, ph);
        wg_fence();
        issue_qk(SA, dqa, dk0 + st * (A_WIN >> 4));
        issue_qk(SC, dqc, dk0 + st * (A_WIN >> 4));
        wg_wait<1>();
        unit_init(a, SA, ok);
        exp_tile(PA, SA, a);
        wg_wait<0>();
        unit_init(c, SC, ok);
        uint32_t eb = 0;
        #pragma unroll 1
        for (int s = 0;; s++) {
            const uint64_t dkb = dk0 + st * (A_WIN >> 4), dvb = dv0 + st * (A_WIN >> 4);
            if (__builtin_expect(s == 8 * gridDim.y, 0)) {
                wg_wait<0>();
                bad = 0;
                #pragma unroll
                for (int i = 0; i < 32; i++) bad |= PC[i];
                break;
            }
            wg_fence();
            issue_pv<true>(ha, PA, dvb); issue_qk(SA, dqa, dkb + T1);
            wg_wait<2>();
            if (s > 0) { mbar_arrive_elect(eb); unit_flush<true>(c, hc); }
            exp_tile(PC, SC, c);
            wg_fence();
            issue_pv<true>(hc, PC, dvb); issue_qk(SC, dqc, dkb + T1);
            wg_wait<2>();
            exp_tile(PA, SA, a);
            eb = rb + B_AE + 8 * st;
            if (++st == 3) { st = 0; ph ^= 1; }
            if (s == 7) {
                wg_fence(); issue_pv<false>(ha, PA, dvb + T1);
                wg_wait<1>();
                exp_tile(PC, SC, c);
                wg_fence(); issue_pv<false>(hc, PC, dvb + T1);
                wg_wait<1>();
                const int tid = tid_now();
                const float ivs = ldsf(SB + OFF_M + M_IVS + pass * 4);
                char* dst = o_block(wg, pass) + (tid & 96) * 8 + (tid & 31) * 4;
                unit_flush<false>(a, ha);
                bad = unit_store(a, dst, ivs);
                wg_wait<0>();
                mbar_arrive_elect(eb);
                unit_flush<false>(c, hc);
                bad |= unit_store(c, dst + 4096, ivs) << 2;
                break;
            }
            const uint64_t dkn = dk0 + st * (A_WIN >> 4);
            mbar_wait(rb + B_AF + 8 * st, ph);
            wg_fence();
            issue_pv<false>(ha, PA, dvb + T1); issue_qk(SA, dqa, dkn);
            wg_wait<2>();
            exp_tile(PC, SC, c);
            wg_fence();
            issue_pv<false>(hc, PC, dvb + T1); issue_qk(SC, dqc, dkn);
            wg_wait<2>();
            unit_flush<true>(a, ha);
            exp_tile(PA, SA, a);
        }
        if (__builtin_expect(named_any(bad != 0, 3 + wg), 0)) {
            exact_rows(L, pass, wg, bad);
        }
        named_arrive(N_OST + 2 * pass + wg, pass > wg ? 192 : 160);
        TL(pass ? -1 : 0, L, 8); TL(pass ? 0 : -1, L, 9);
    }
}

#define XS0 0
#define OW0 1
#define OUNR 1
#define OWARM 1
#define TPE 0
#define GDP 0
#define DDP 1

template <bool INIT>
__device__ __forceinline__ void oproj_step(float (&acc)[64], uint32_t s, int wg) {
    const uint64_t da = desc_plain(SB, 1024, 128) + ((o_stage(s) + wg * 4096) >> 4);
    const uint64_t db = desc_sw128(SB + 16384, 8192, 1024) + (o_stage(s) >> 4);
    wg_fence();
    if (INIT) wg_gemm_n128_init(acc, da, db);
    #pragma unroll
    for (int kk = INIT ? 1 : 0; kk < 4; kk++) wg_gemm_n128(acc, da + (kk >> 1) * 512 + (kk & 1) * 128, db + kk * 128);
    wg_commit();
}
__device__ __forceinline__ void oproj_phase(int L, int wg, bf16* __restrict__ out) {
    const int c = cta_now(), tid = tid_now(), lane = tid & 31, W = tid >> 5, g = lane >> 2, t = lane & 3;
    const int row0 = (c >> 4) * 256 + (c & 1) * 128, col0 = ((c & 15) >> 1) * 128;
    float acc[64];
    mbar_wait(B_OF, 0);
    TL(0, L, 10);
    oproj_step<true>(acc, 0, wg);
    const uint32_t xa = SB + OFF_XT + (W * 16 + ((lane >> 3) & 1) * 8 + (lane & 7)) * 128, xs = (lane >> 4) ^ (lane & 7);
    mbar_wait(B_RES2, L);
    const float2 c0 = lds64f(SB + OFF_LC + (W * 16 + g) * 8), c1 = lds64f(SB + OFF_LC + (W * 16 + g + 8) * 8);
    constexpr int ounr = OUNR;
    #pragma unroll ounr
    for (int k = 1; k < 16; k++) {
        if (OW0) { wg_wait<0>(); if ((tid & 127) == 0) mbar_arrive(B_OE + 8 * ((k - 1) & 3)); }
        mbar_wait(B_OF + 8 * (k & 3), (k >> 2) & 1);
        TL(k == 8 ? 0 : -1, L, 11);
        oproj_step<false>(acc, k & 3, wg);
        if (!OW0) { wg_wait<1>(); if ((tid & 127) == 0) mbar_arrive(B_OE + 8 * ((k - 1) & 3)); }
        if (L == 1 && (k & 1)) {
            const uint32_t a = xa + (k & 8) * 2048 + ((xs ^ (k & 6)) << 4);
            uint32_t v0, v1, v2, v3;
            ldsm4(v0, v1, v2, v3, a);
            stsm4(a, add_ln2(v0, c0.x, c0.y), add_ln2(v1, c1.x, c1.y), add_ln2(v2, c0.x, c0.y), add_ln2(v3, c1.x, c1.y));
        }
    }
    uint32_t x[32];
    const uint32_t wra = SB + OFF_WR + (g == 0 ? t * 8 : 256), wrs = g == 0 ? 32 : 0;
    float2 wb[8];
    #pragma unroll
    for (int ks = 0; ks < 8; ks++) {
        ldsm4(x[4*ks], x[4*ks+1], x[4*ks+2], x[4*ks+3], xa + (ks >> 2) * 16384 + ((xs ^ ((ks & 3) * 2)) << 4));
        wb[ks] = lds64f(wra + ks * wrs);
    }
    wg_wait<0>();
    if ((tid & 127) == 0) mbar_arrive(B_OE + 24);
    TL(0, L, 12);
    {
        float sd[4] = {0.f, 0.f, 0.f, 0.f}, z0[4] = {0.f, 0.f, 0.f, 0.f}, z1[4] = {0.f, 0.f, 0.f, 0.f};
        #pragma unroll
        for (int ks = 0; ks < 8; ks++) {
            #pragma unroll
            for (int i = 0; i < 4; i++) x[4*ks + i] = badd2(x[4*ks + i], pack_bf16(acc[8*ks + 2*i], acc[8*ks + 2*i + 1]));
            mma_bf16(sd, x[4*ks], x[4*ks+1], x[4*ks+2], x[4*ks+3], __float_as_uint(wb[ks].x), __float_as_uint(wb[ks].y));
            mma_bf16(z0, x[4*ks], x[4*ks+1], x[4*ks+2], x[4*ks+3], x[4*ks], x[4*ks+2]);
            mma_bf16(z1, x[4*ks], x[4*ks+1], x[4*ks+2], x[4*ks+3], x[4*ks+1], x[4*ks+3]);
        }
        const float s0 = __shfl_sync(0xffffffffu, (g & 1) ? z0[1] : z0[0], 4 * g + (g >> 1));
        const float s1 = __shfl_sync(0xffffffffu, (g & 1) ? z1[3] : z1[2], 4 * g + (g >> 1));
        if (t == 0) {
            float4* p = &g_sums[L][row0 + W * 16 + g];
            asm volatile("red.relaxed.gpu.global.add.v4.f32 [%0], {%1, %2, %3, %4};" :: "l"(p), "f"(sd[1]), "f"(s0), "f"(sd[0]), "f"(1.f) : "memory");
            asm volatile("red.relaxed.gpu.global.add.v4.f32 [%0], {%1, %2, %3, %4};" :: "l"(p + 8), "f"(sd[3]), "f"(s1), "f"(sd[2]), "f"(1.f) : "memory");
        }
    }
    TL(0, L, 13);
    if (L == 0) {
        #pragma unroll
        for (int ks = 0; ks < 8; ks++) stsm4(xa + (ks >> 2) * 16384 + ((xs ^ ((ks & 3) * 2)) << 4), x[4*ks], x[4*ks+1], x[4*ks+2], x[4*ks+3]);
        fence_async_smem();
        if (XS0 == 0) named_arrive(N_XST + wg, 160);
    }
    const bool ffn = c < NFC;
    uint4 fa[32], fd[16];
    const uint32_t ga = SB + W * 2048 + ((lane >> 4) * 8 + (lane & 7)) * 64 + ((((lane >> 3) & 1) ^ ((lane >> 1) & 3)) << 4);
    if (ffn) mbar_wait(B_FE, L);
    #pragma unroll
    for (int i = 0; i < 12; i++) ldsm4t(fa[i].x, fa[i].y, fa[i].z, fa[i].w, (ga ^ ((i & 1) * 32)) + gu_piece(i >> 2) + (i & 2) * 512);
    float2 r0, r1;
    {
        const float ws = ldsf(SB + OFF_M + M_WS) + ldsf(SB + OFF_M + M_WS + 4) + ldsf(SB + OFF_M + M_WS + 8);
        const uint32_t row = row0 + W * 16 + g;
        uint4 s0 = make_uint4(0u, 0u, 0u, 0u), s1 = s0;
        uint32_t n = 0;
        do {
            ld_relaxed4_unless(s0, &g_sums[L][row], STAT_FULL); ld_relaxed4_unless(s1, &g_sums[L][row + 8], STAT_FULL);
        } while ((s0.w != STAT_FULL || s1.w != STAT_FULL) && ++n < SPIN_MAX);
        spin_check(n);
        __syncwarp();
        TL(0, L, 46);
        if (XS0 == 1 && L == 0) named_arrive(N_XST + wg, 160);
        r0 = ln_coef(s0); r1 = ln_coef(s1);
        const bool odd = t & 1;
        const float2 r = odd ? r1 : r0;
        const uint32_t k = min(order_bits(r.x * fmaf(-r.y, ws, __uint_as_float(odd ? s1.z : s0.z))), SENT - 1), me = row + (odd ? 8 : 0);
        const uint32_t m = redux_max(k), mrow = redux_min(k == m ? me : 0x7FFFFFFFu);
        if (me == mrow) sts128(SB + OFF_RT + W * 16, make_uint4(k, me, not_sent(r.y), not_sent(r.x)));
    }
    named_sync(1, 256);
    {
        const uint4 e = lds128(SB + OFF_RT + (lane & 7) * 16);
        const uint32_t m = redux_max(e.x), row = redux_min(e.x == m ? e.y : 0x7FFFFFFFu);
        const int lr = row - row0;
        st_relaxed4_if(&g_tab[L][(c & 15) >> 1][row0 >> 7][(lane >> 3) & 1], e, W == ((lr >> 4) ^ 1) && e.y == row && lane < 16);
        if ((lr >> 4) == W) {
            const bool hi = lr & 8;
            uint32_t* dst = &g_xrow[L][row0 >> 7][(col0 & 128) * 2 + (col0 >> 8) * 16 + t * 4];
            #pragma unroll
            for (int i = 0; i < 4; i++)
                st_relaxed4_if(dst + i * 64, make_uint4(min(hi ? x[8*i+1] : x[8*i], SENT - 1), min(hi ? x[8*i+3] : x[8*i+2], SENT - 1),
                               min(hi ? x[8*i+5] : x[8*i+4], SENT - 1), min(hi ? x[8*i+7] : x[8*i+6], SENT - 1)), g == (lr & 7));
        }
        __syncwarp();
    }
    TL(0, L, 15);
    if (XS0 == 2 && L == 0) named_arrive(N_XST + wg, 160);
    const uint4* tp = &g_tab[L][(c & 15) >> 1][lane & 15][0];
    uint4 e;
    if (TPE) e = ld_relaxed4(tp);
    if (L == 1 || OWARM) {
        const float b0 = -r0.x * r0.y, b1 = -r1.x * r1.y;
        const uint32_t oa = L ? xa : xa - (OFF_XT - OFF_FE);
        #pragma unroll
        for (int ks = 0; ks < 8; ks++)
            stsm4(oa + (ks >> 2) * 16384 + ((xs ^ ((ks & 3) * 2)) << 4), add_ln2(x[4*ks], r0.x, b0), add_ln2(x[4*ks+1], r1.x, b1),
                  add_ln2(x[4*ks+2], r0.x, b0), add_ln2(x[4*ks+3], r1.x, b1));
        TL(0, L, 47);
        fence_async_smem();
        if (L == 1) named_arrive(N_XST + wg, 160);
    }
    TL(0, L, 45);
    RouteOut rt;
    {
        if (!TPE) e = ld_relaxed4(tp);
        if (ffn) mbar_wait(B_FL, L);
        #pragma unroll
        for (int i = 12; i < 32; i++) ldsm4t(fa[i].x, fa[i].y, fa[i].z, fa[i].w, (ga ^ ((i & 1) * 32)) + gu_piece(i >> 2) + (i & 2) * 512);
        TL(0, L, 44);
        if (L == 0 && GDP == 0) named_arrive(N_GD, 288);
        uint32_t n = 0;
        while (has_sent(e) && ++n < SPIN_MAX) e = ld_relaxed4(tp);
        spin_check(n);
        __syncwarp();
        e = warp_best(e);
        rt = route_out(e);
        if (W == 7 && L == 0) { sts128(SB + OFF_RT + 128, e); named_arrive(N_RT, 128); }
    }
    TL(0, L, 16);
    uint2 xrow;
    {
        const uint32_t* xp = &g_xrow[L][rt.idx >> 7][W * 64 + (g >> 1) * 16 + t * 4 + (g & 1) * 2];
        xrow = ld_relaxed2(xp);
        if (ffn) mbar_wait(B_FD, L);
        const uint32_t wa = SB + OFF_FD + W * 8192 + ((lane >> 4) * 8 + (lane & 7)) * 128 + ((((lane >> 3) & 1) ^ (lane & 7)) << 4);
        #pragma unroll
        for (int i = 0; i < 16; i++) ldsm4t(fd[i].x, fd[i].y, fd[i].z, fd[i].w, (wa ^ (((i >> 1) & 3) * 32)) + (i >> 3) * 4096 + (i & 1) * 2048);
        if (L == 0 && GDP == 1) named_arrive(N_GD, 288);
        if (L == 0 && DDP == 1) named_arrive(N_DD, 288);
        uint32_t n = 0;
        while ((xrow.x == SENT || xrow.y == SENT) && ++n < SPIN_MAX) xrow = ld_relaxed2(xp);
        spin_check(n);
        __syncwarp();
    }
    if (L == 0 && GDP == 2) named_arrive(N_GD, 288);
    if (L == 0 && DDP == 2) named_arrive(N_DD, 288);
    TL(0, L, 17);
    {
        const float nb = -rt.mean * rt.rstd;
        const uint32_t n0 = pack_bf16(fmaf(bf_lo(xrow.x), rt.rstd, nb), fmaf(bf_hi(xrow.x), rt.rstd, nb));
        const uint32_t n1 = pack_bf16(fmaf(bf_lo(xrow.y), rt.rstd, nb), fmaf(bf_hi(xrow.y), rt.rstd, nb));
        float gu[4][4];
        #pragma unroll
        for (int i = 0; i < 4; i++) { gu[i][0] = 0.f; gu[i][1] = 0.f; gu[i][2] = 0.f; gu[i][3] = 0.f; }
        #pragma unroll
        for (int ks = 0; ks < 8; ks++) {
            const uint32_t b0 = __shfl_sync(0xffffffffu, n0, 4 * ks + t), b1 = __shfl_sync(0xffffffffu, n1, 4 * ks + t);
            #pragma unroll
            for (int i = 0; i < 4; i++) {
                const uint4& a = fa[(ks >> 1) * 8 + (i >> 1) * 4 + (ks & 1) * 2 + (i & 1)];
                mma_bf16(gu[i], a.x, a.y, a.z, a.w, b0, b1);
            }
        }
        stsf(SB + OFF_PART + (W * 64 + t * 16 + g) * 4, sel4(t, gu[0][0], gu[1][0], gu[2][0], gu[3][0]));
        stsf(SB + OFF_PART + (W * 64 + t * 16 + g + 8) * 4, sel4(t, gu[0][2], gu[1][2], gu[2][2], gu[3][2]));
    }
    named_sync(1, 256);
    TL(0, L, 18);
    {
        float gp[8], up[8];
        #pragma unroll
        for (int i = 0; i < 8; i++) gp[i] = ldsf(SB + OFF_PART + (i * 64 + lane) * 4);
        #pragma unroll
        for (int i = 0; i < 8; i++) up[i] = ldsf(SB + OFF_PART + (i * 64 + 32 + lane) * 4);
        const float gv = bf_round(((gp[0] + gp[1]) + (gp[2] + gp[3])) + ((gp[4] + gp[5]) + (gp[6] + gp[7])));
        const float uv = bf_round(((up[0] + up[1]) + (up[2] + up[3])) + ((up[4] + up[5]) + (up[6] + up[7])));
        const float hv = bf_round(gv * rcp(1.f + ex2(gv * -1.4426950408889634f))) * uv;
        const uint32_t hp = pack_bf16(hv, __shfl_down_sync(0xffffffffu, hv, 1));
        uint32_t hb[4];
        #pragma unroll
        for (int i = 0; i < 4; i++) hb[i] = __shfl_sync(0xffffffffu, hp, 8 * i + 2 * t);
        float y[8][4];
        #pragma unroll
        for (int mb = 0; mb < 8; mb++) {
            y[mb][0] = 0.f; y[mb][1] = 0.f; y[mb][2] = 0.f; y[mb][3] = 0.f;
            #pragma unroll
            for (int ks = 0; ks < 2; ks++) mma_bf16(y[mb], fd[2*mb + ks].x, fd[2*mb + ks].y, fd[2*mb + ks].z, fd[2*mb + ks].w, hb[2 * ks], hb[2 * ks + 1]);
        }
        st_relaxed4_if(&g_ypart[L][min(c, NFC - 1)][tid * 4], make_uint4(not_sent(sel4(t, y[0][0], y[2][0], y[4][0], y[6][0])), not_sent(sel4(t, y[0][2], y[2][2], y[4][2], y[6][2])),
                       not_sent(sel4(t, y[1][0], y[3][0], y[5][0], y[7][0])), not_sent(sel4(t, y[1][2], y[3][2], y[5][2], y[7][2]))), ffn);
    }
    if (L == 0 && DDP == 3) named_arrive(N_DD, 288);
    TL(0, L, 19);
    if (L == 1) {
        if (W == 7) ctr_wait(&g_xc[1][rt.idx >> 8], 32);
        unsigned short* dst = reinterpret_cast<unsigned short*>(out) + (size_t)rt.idx * D_ + ypos_col(c * 8 + (tid & 7));
        asm volatile("" : "+l"(dst));
        const float v = ffn_finish<256>(1, rt, tid, SB + OFF_FE, 1);
        if (tid < 8) asm volatile("st.global.u16 [%0], %1;" :: "l"(dst), "h"((unsigned short)(__float_as_uint(v) >> 16)) : "memory");
        TL(0, L, 20);
    }
}

#define FW0 9
#define RK0 7
#define BAL 1000
#define PFENCE 1
#define KW1 4
static_assert(FW0 >= 8 && KW1 >= 3 && KW1 < 7, "buffer reuse");
__device__ __forceinline__ void qkv_fill(const CUtensorMap* tx, const CUtensorMap* tw, uint32_t bar, int st, int k) {
    const uint32_t sa = SB + st * Q_STB;
    mbar_expect_tx(bar, Q_STB);
    tma_load(sa, tx, k * 64, (blockIdx.x >> 4) * 256, bar);
    tma_load3(sa + Q_ABYTES, tw, (blockIdx.x & 15) * 64, k * 64, 0, bar);
}
__device__ __forceinline__ void oproj_fill(const Maps& mp, const char* osrc, int s, int par, int pair, int L, int k) {
    const uint32_t fb = B_OF + 8 * s, sa = SB + o_stage(s);
    mbar_expect_tx(fb, 32768);
    bulk_load(sa, osrc + (par * 16 + pair) * 8192, 16384, fb);
    tma_load5(sa + 16384, &mp.wo, 0, 0, par, pair, blockIdx.x & 14, fb);
}
__device__ __forceinline__ void producer_role(const Maps& mp) {
    const int c = blockIdx.x, mt = c >> 4, nt = c & 15, lane = threadIdx.x & 31;
    #pragma unroll 1
    for (int i = 2; i < 13; i++) tm_prefetch(&mp.xa0 + i);
    #pragma unroll 1
    for (int L = 0; L < 2; L++) {
        const uint32_t rb = L * 32;
        uint32_t st = 0, ph = L;
        #pragma unroll 1
        for (int k = L == 0 ? 3 : 0; k < 16; k++) {
            if (k == 0) { ctr_wait_all(&g_xc[0][mt], 32); fence_async_global(); named_sync(N_GD, 288); }
            if (k == 1) named_sync(N_DD, 288);
            mbar_wait(rb + B_QE + 8 * st, ph);
            TL(k == 3 ? 256 : -1, L, 28);
            qkv_fill(L == 0 ? &mp.xa0 : &mp.xa, &mp.wqkv, rb + B_QF + 8 * st, st, k);
            if (L == 1 && k >= RK0 && k < RK0 + 4) {
                if (k == RK0) mbar_expect_tx(B_SW, 4 * 12288);
                tma_load(SB + OFF_SIDE + (k - RK0) * 12288, &mp.r, c * 24, (k - RK0) * 256, B_SW);
            }
            if (++st == 3) { st = 0; ph ^= 1; }
        }
        mbar_wait(B_KV0, L);
        mbar_arrive_elect(rb + B_AF);
        TL(256, L, 29);
        st = 1; ph = 1;
        uint32_t wtodo = 0xFEu, wready = 0;
        #pragma unroll 1
        for (int w = 1; w < 16; w++) {
            if (w <= 3 || w == 8) {
                if (w == 8) wtodo = 0xFFu;
                wready = flags_wait(&g_kvc[L][nt * 2 + (w >> 3)][(mt + lane) & 7], w < 3 ? wtodo : 0xFFu, w >= 3);
                fence_async_global();
            }
            const int j = __ffs(wready & wtodo) - 1, win = nt * 16 + (w & 8) + ((mt + j) & 7);
            wtodo &= ~(1u << j);
            TL(w == 1 ? 256 : -1, L, 7);
            mbar_wait(rb + B_AE + 8 * st, ph);
            mbar_expect_tx(rb + B_AF + 8 * st, KV_WIN);
            bulk_load(SB + st * A_WIN, g_kv + (size_t)win * KV_WIN, KV_WIN, rb + B_AF + 8 * st);
            if (w == KW1 || w == FW0) named_arrive(w == FW0 ? N_FW : N_KV1, 64);
            if (++st == 3) { st = 0; ph ^= 1; }
        }
        ctr_wait_all(&g_oc[L][mt * 2 + (nt & 1)][0][lane & 15], 1);
        fence_async_global();
        const char* osrc = g_o + (size_t)(mt * 2 + (nt & 1)) * 32 * 8192;
        #pragma unroll
        for (int k = 0; k < 4; k++) {
            mbar_wait(k < 2 ? rb + B_AE + 8 + 8 * k : k == 2 ? rb + B_AE : B_QAF, k < 2 ? 0 : k == 2 ? 1 : L);
            oproj_fill(mp, osrc, k, 0, 2 * k, L, k);
        }
        uint32_t todo = 0x55555500u, ready = 0xFFFFu;
        #pragma unroll 1
        for (int k4 = 1; k4 < 4; k4++) {
            #pragma unroll
            for (int s = 0; s < 4; s++) {
                if ((ready & todo) == 0) {
                    ready = smem_wait_any(SB + OFF_M + M_ORDY + 4 * L, todo);
                    if (PFENCE) fence_async_global();
                }
                const int p = __ffs(ready & todo) - 1;
                todo &= ~(1u << p);
                mbar_wait(B_OE + 8 * s, (k4 - 1) & 1);
                oproj_fill(mp, osrc, s, p >> 4, p & 15, L, k4 * 4 + s);
            }
        }
        if (c < NFC) {
            mbar_expect_tx(B_FL, 5 * 16384);
            mbar_expect_tx(B_FD, 4 * 16384);
            #pragma unroll 1
            for (int i = 3; i < 12; i++) {
                mbar_wait(B_OE + (i < 5 ? 0 : i == 5 ? 8 : i < 9 ? 16 : 24), 1);
                TL(i == 9 ? 256 : -1, L, 32);
                ffn_load(mp, i, SB + (i < 8 ? gu_piece(i) : OFF_FD + (i - 8) * 16384), i < 8 ? B_FL : B_FD, true);
            }
        }
    }
}

__global__ void __launch_bounds__(384, 1) k_all(const bf16* __restrict__ x0, const bf16* __restrict__ wo, const bf16* __restrict__ w_r, bf16* __restrict__ out,
                                                const __grid_constant__ Maps mp) {
    extern __shared__ __align__(1024) char smem[];
    if (smem_u32(smem) != SB) __trap();
    const int warp = warp_uniform(threadIdx.x >> 5), wg = warp >> 2;
    TL(0, 0, 0);
    {
        const int grp = warp >= 8 ? warp - 8 : warp + 4;
        #pragma unroll
        for (int i = 0; i < 4; i++) mbar_init(BB + grp * 32 + i * 8, grp < 7 ? 1 : grp < 10 ? 2 : 8);
        fence_mbar_init();
    }
    if (warp == 8) {
        #pragma unroll 1
        for (int s = 0; s < 3; s++) qkv_fill(&mp.xa0, &mp.wqkv, B_QF + 8 * s, s, s);
    }
    __syncthreads();
    if (wg == 2) {
        reg_dec<40>();
        if (warp == 8) producer_role(mp);
        else side_role(mp, x0, wo, w_r);
        if (gridDim.y == 2) {
            uint32_t v = threadIdx.x;
            #pragma unroll
            for (int i = 0; i < BAL; i++) asm volatile("fma.rn.f16x2 %0, %0, %0, %0;" : "+r"(v));
            sts32(SB, v);
        }
    } else {
        reg_inc<232>();
        #pragma unroll 1
        for (int L = 0; L < 2; L++) {
            qkv_phase(L, wg);
            attention_phase(L, wg);
            oproj_phase(L, wg, out);
        }
    }
}

typedef CUresult (*EncodeFn)(CUtensorMap*, CUtensorMapDataType, cuuint32_t, void*, const cuuint64_t*, const cuuint64_t*, const cuuint32_t*,
                             const cuuint32_t*, CUtensorMapInterleave, CUtensorMapSwizzle, CUtensorMapL2promotion, CUtensorMapFloatOOBfill);

void make_map(EncodeFn enc, CUtensorMap* tm, const void* ptr, int rank, const cuuint64_t* dims, const cuuint64_t* strides, const cuuint32_t* box, CUtensorMapSwizzle sw) {
    const cuuint32_t es[5] = {1, 1, 1, 1, 1};
    enc(tm, CU_TENSOR_MAP_DATA_TYPE_BFLOAT16, rank, const_cast<void*>(ptr), dims, strides, box, es, CU_TENSOR_MAP_INTERLEAVE_NONE, sw,
        box[0] == 64 ? CU_TENSOR_MAP_L2_PROMOTION_L2_128B : CU_TENSOR_MAP_L2_PROMOTION_NONE, CU_TENSOR_MAP_FLOAT_OOB_FILL_NONE);
}
void make_map2(EncodeFn enc, CUtensorMap* tm, const void* ptr, uint64_t cols, uint64_t rows, uint32_t bc, uint32_t br, CUtensorMapSwizzle sw) {
    const cuuint64_t dims[2] = {cols, rows}, strides[1] = {cols * 2};
    const cuuint32_t box[2] = {bc, br};
    make_map(enc, tm, ptr, 2, dims, strides, box, sw);
}

}

extern "C" void kernel_launch(void* const* d_in, const int* in_sizes, int n_in, void* d_out, int out_size) {
    const bf16* x0 = (const bf16*)d_in[0];
    const bf16* wqkv = (const bf16*)d_in[1];
    const bf16* wo = (const bf16*)d_in[2];
    const bf16* w_r = (const bf16*)d_in[4];
    const bf16* w_gate = (const bf16*)d_in[5];
    const bf16* w_up = (const bf16*)d_in[6];
    const bf16* w_down = (const bf16*)d_in[7];

    EncodeFn enc = nullptr;
    cudaDriverEntryPointQueryResult qr;
    cudaGetDriverEntryPoint("cuTensorMapEncodeTiled", (void**)&enc, cudaEnableDefault, &qr);
    void* p_x;
    cudaGetSymbolAddress(&p_x, g_x);
    Maps mp;
    const CUtensorMapSwizzle S128 = CU_TENSOR_MAP_SWIZZLE_128B;
    make_map2(enc, &mp.x0, x0, D_, S_, 64, 64, S128);
    make_map2(enc, &mp.x, p_x, D_, S_, 64, 64, S128);
    make_map2(enc, &mp.out, d_out, D_, S_, 64, 16, S128);
    make_map2(enc, &mp.xs, p_x, D_, S_, 64, 16, S128);
    make_map2(enc, &mp.xa0, x0, D_, S_, 64, 256, S128);
    make_map2(enc, &mp.xa, p_x, D_, S_, 64, 256, S128);
    make_map2(enc, &mp.w64, wqkv, 3 * D_, D_, 64, 64, S128);
    {
        const cuuint64_t dims[3] = {D_, D_, 3}, strides[2] = {3 * D_ * 2, D_ * 2};
        const cuuint32_t box[3] = {64, 64, 3};
        make_map(enc, &mp.wqkv, wqkv, 3, dims, strides, box, S128);
    }
    make_map2(enc, &mp.r, wqkv, 3 * D_, D_, 24, 256, CU_TENSOR_MAP_SWIZZLE_NONE);
    make_map2(enc, &mp.g, w_gate, FF, D_, 32, 256, CU_TENSOR_MAP_SWIZZLE_64B);
    make_map2(enc, &mp.u, w_up, FF, D_, 32, 256, CU_TENSOR_MAP_SWIZZLE_64B);
    {
        const cuuint64_t dims[5] = {64, 32, 2, 16, 16}, strides[4] = {D_ * 2, 32 * D_ * 2, 64 * D_ * 2, 128};
        const cuuint32_t box[5] = {64, 32, 1, 2, 2};
        make_map(enc, &mp.wo, wo, 5, dims, strides, box, S128);
    }
    {
        const cuuint64_t dims[3] = {64, FF, 16}, strides[2] = {D_ * 2, 128};
        const cuuint32_t box[3] = {64, 32, 4};
        make_map(enc, &mp.d, w_down, 3, dims, strides, box, S128);
    }
    cudaFuncSetAttribute(k_all, cudaFuncAttributeMaxDynamicSharedMemorySize, K_SMEM);
    k_all<<<128, 384, K_SMEM, cudaStreamPerThread>>>(x0, wo, w_r, (bf16*)d_out, mp);
}
```

```cpp
#include <cuda_runtime.h>
#include <cuda_bf16.h>
#include <cuda_fp16.h>
#include <cuda.h>
#include <cudaTypedefs.h>
#include <stdint.h>

namespace {

typedef __nv_bfloat16 bf16;

constexpr int S_ = 2048, D_ = 1024, NH = 32, FF = 3584, NFC = FF / 32;
constexpr float LN_EPS = 1e-5f;
constexpr float QSCALE = 0.17677669529663687f * 1.4426950408889634f;
constexpr uint32_t SENT = 0xFFFFFFFFu;

constexpr int KV_WIN = 32768;
__device__ __align__(1024) char g_kv[NH * 8 * KV_WIN];
__device__ __align__(1024) char g_o[32 * 2 * 16 * 4096];
__device__ __align__(1024) bf16 g_x[S_ * D_];
__device__ float g_csum[8 * 3 * D_];
__device__ float g_wsq[8 * 96];
__device__ float2 g_rs0[S_];
__device__ __align__(128) double g_acc[2][S_][4];
__device__ __align__(128) uint4 g_sums[S_];
__device__ __align__(128) uint32_t g_ypart[2][NFC][D_];
__device__ __align__(128) uint4 g_tab[2][8][16][2];
__device__ __align__(128) uint32_t g_xrow[2][16][D_ / 2];
__device__ __align__(128) uint32_t g_x2row[D_];
__device__ __align__(128) uint32_t g_fix[3 * D_];
__device__ uint32_t g_c0;
__device__ __align__(128) uint32_t g_kvc[2][NH][8];
__device__ __align__(128) uint32_t g_oc[2][16][2][16];
__device__ __align__(128) uint32_t g_xc[2][8];
struct RouteOut { int idx; float r; float mean; float rstd; };

constexpr uint32_t SB = 1024;

__device__ __forceinline__ uint32_t smem_u32(const void* p) { return (uint32_t)__cvta_generic_to_shared(p); }
__device__ __forceinline__ void mbar_arrive(uint32_t bar) { asm volatile("mbarrier.arrive.shared::cta.b64 _, [%0];" :: "r"(bar) : "memory"); }
__device__ __forceinline__ void mbar_wait(uint32_t bar, uint32_t parity) {
    asm volatile("{\n.reg .pred p;\n.reg .u32 n;\nmov.u32 n, 0;\n"
                 "LAB_WAIT:\nmbarrier.try_wait.parity.shared::cta.b64 p, [%0], %1, 2000;\n@p bra LAB_DONE;\n"
                 "add.u32 n, n, 1;\nsetp.lt.u32 p, n, 0x200000;\n@p bra LAB_WAIT;\ntrap;\nLAB_DONE:\n}" :: "r"(bar), "r"(parity) : "memory");
}
__device__ __forceinline__ void mbar_arrive_elect(uint32_t bar) {
    asm volatile("{\n.reg .pred p;\nelect.sync _|p, 0xffffffff;\n@p mbarrier.arrive.shared::cta.b64 _, [%0];\n}" :: "r"(bar) : "memory");
}
__device__ __forceinline__ int tid_now() { int v; asm volatile("mov.u32 %0, %%tid.x;" : "=r"(v)); return v; }
__device__ __forceinline__ int cta_now() { int v; asm volatile("mov.u32 %0, %%ctaid.x;" : "=r"(v)); return v; }
__device__ __forceinline__ int warp_uniform(int v) { return __shfl_sync(0xffffffffu, v, 0); }
__device__ __forceinline__ void fence_mbar_init() { asm volatile("fence.mbarrier_init.release.cluster;" ::: "memory"); }
__device__ __forceinline__ void fence_async_smem() { asm volatile("fence.proxy.async.shared::cta;" ::: "memory"); }
__device__ __forceinline__ void fence_async_global() { asm volatile("fence.proxy.async.global;" ::: "memory"); }
__device__ __forceinline__ void named_sync(int id, int n) { asm volatile("bar.sync %0, %1;" :: "r"(id), "r"(n) : "memory"); }
__device__ __forceinline__ void named_arrive(int id, int n) { asm volatile("bar.arrive %0, %1;" :: "r"(id), "r"(n) : "memory"); }
__device__ __forceinline__ bool named_any(bool p, int id) {
    uint32_t r;
    asm volatile("{\n.reg .pred a, b;\nsetp.ne.u32 a, %1, 0;\nbarrier.cta.red.or.pred b, %2, 128, a;\nselp.u32 %0, 1, 0, b;\n}" : "=r"(r) : "r"((uint32_t)p), "r"(id) : "memory");
    return r != 0;
}
#define ELECT(op) "{\n.reg .pred e;\nelect.sync _|e, 0xffffffff;\n@e " op "\n}"
__device__ __forceinline__ void mbar_init(uint32_t bar, int cnt) { asm volatile(ELECT("mbarrier.init.shared::cta.b64 [%0], %1;") :: "r"(bar), "r"(cnt) : "memory"); }
__device__ __forceinline__ void mbar_expect_tx(uint32_t bar, uint32_t bytes) { asm volatile(ELECT("mbarrier.arrive.expect_tx.shared::cta.b64 _, [%0], %1;") :: "r"(bar), "r"(bytes) : "memory"); }
__device__ __forceinline__ void bulk_load(uint32_t dst, const void* src, uint32_t bytes, uint32_t bar) {
    asm volatile(ELECT("cp.async.bulk.shared::cluster.global.mbarrier::complete_tx::bytes [%0], [%1], %2, [%3];") :: "r"(dst), "l"(src), "r"(bytes), "r"(bar) : "memory");
}
__device__ __forceinline__ void bulk_store(void* dst, uint32_t src, uint32_t bytes) {
    asm volatile(ELECT("cp.async.bulk.global.shared::cta.bulk_group [%0], [%1], %2;") :: "l"(dst), "r"(src), "r"(bytes) : "memory");
}
__device__ __forceinline__ void bulk_commit() { asm volatile("cp.async.bulk.commit_group;" ::: "memory"); }
__device__ __forceinline__ void bulk_wait() { asm volatile("cp.async.bulk.wait_group 0;" ::: "memory"); }
template <int N> __device__ __forceinline__ void bulk_wait_n() { asm volatile("cp.async.bulk.wait_group %0;" :: "n"(N) : "memory"); }
__device__ __forceinline__ void bulk_wait_read() { asm volatile("cp.async.bulk.wait_group.read 0;" ::: "memory"); }
__device__ __forceinline__ void l2_prefetch(const void* src, uint32_t bytes) {
    asm volatile(ELECT("cp.async.bulk.prefetch.L2.global [%0], %1;") :: "l"(src), "r"(bytes) : "memory");
}
__device__ __forceinline__ void tma_load(uint32_t dst, const CUtensorMap* tm, int c0, int c1, uint32_t bar) {
    asm volatile(ELECT("cp.async.bulk.tensor.2d.shared::cluster.global.mbarrier::complete_tx::bytes [%0], [%1, {%3, %4}], [%2];")
                 :: "r"(dst), "l"(tm), "r"(bar), "r"(c0), "r"(c1) : "memory");
}
__device__ __forceinline__ void tma_load3(uint32_t dst, const CUtensorMap* tm, int c0, int c1, int c2, uint32_t bar) {
    asm volatile(ELECT("cp.async.bulk.tensor.3d.shared::cluster.global.mbarrier::complete_tx::bytes [%0], [%1, {%3, %4, %5}], [%2];")
                 :: "r"(dst), "l"(tm), "r"(bar), "r"(c0), "r"(c1), "r"(c2) : "memory");
}
__device__ __forceinline__ uint64_t evict_first() { uint64_t a; asm("createpolicy.fractional.L2::evict_first.b64 %0, 1.0;" : "=l"(a)); return a; }
__device__ __forceinline__ void tma_load_h(uint32_t dst, const CUtensorMap* tm, int c0, int c1, uint32_t bar, bool ef) {
    if (!ef) tma_load(dst, tm, c0, c1, bar);
    else asm volatile(ELECT("cp.async.bulk.tensor.2d.shared::cluster.global.mbarrier::complete_tx::bytes.L2::cache_hint [%0], [%1, {%3, %4}], [%2], %5;")
                      :: "r"(dst), "l"(tm), "r"(bar), "r"(c0), "r"(c1), "l"(evict_first()) : "memory");
}
__device__ __forceinline__ void tma_load3_h(uint32_t dst, const CUtensorMap* tm, int c0, int c1, int c2, uint32_t bar, bool ef) {
    if (!ef) tma_load3(dst, tm, c0, c1, c2, bar);
    else asm volatile(ELECT("cp.async.bulk.tensor.3d.shared::cluster.global.mbarrier::complete_tx::bytes.L2::cache_hint [%0], [%1, {%3, %4, %5}], [%2], %6;")
                      :: "r"(dst), "l"(tm), "r"(bar), "r"(c0), "r"(c1), "r"(c2), "l"(evict_first()) : "memory");
}
__device__ __forceinline__ void tma_load5(uint32_t dst, const CUtensorMap* tm, int c0, int c1, int c2, int c3, int c4, uint32_t bar) {
    asm volatile(ELECT("cp.async.bulk.tensor.5d.shared::cluster.global.mbarrier::complete_tx::bytes [%0], [%1, {%3, %4, %5, %6, %7}], [%2];")
                 :: "r"(dst), "l"(tm), "r"(bar), "r"(c0), "r"(c1), "r"(c2), "r"(c3), "r"(c4) : "memory");
}
__device__ __forceinline__ void tma_store(const CUtensorMap* tm, uint32_t src, int c0, int c1) {
    asm volatile(ELECT("cp.async.bulk.tensor.2d.global.shared::cta.bulk_group [%0, {%2, %3}], [%1];") :: "l"(tm), "r"(src), "r"(c0), "r"(c1) : "memory");
}
__device__ __forceinline__ void tm_prefetch(const CUtensorMap* tm) { asm volatile(ELECT("prefetch.tensormap [%0];") :: "l"(tm) : "memory"); }
__device__ __forceinline__ uint32_t lds32(uint32_t a) { uint32_t v; asm volatile("ld.shared.b32 %0, [%1];" : "=r"(v) : "r"(a) : "memory"); return v; }
__device__ __forceinline__ float ldsf(uint32_t a) { return __uint_as_float(lds32(a)); }
__device__ __forceinline__ float2 lds64f(uint32_t a) { float2 v; asm volatile("ld.shared.v2.f32 {%0, %1}, [%2];" : "=f"(v.x), "=f"(v.y) : "r"(a) : "memory"); return v; }
__device__ __forceinline__ uint4 lds128(uint32_t a) { uint4 v; asm volatile("ld.shared.v4.b32 {%0, %1, %2, %3}, [%4];" : "=r"(v.x), "=r"(v.y), "=r"(v.z), "=r"(v.w) : "r"(a) : "memory"); return v; }
__device__ __forceinline__ void sts32(uint32_t a, uint32_t v) { asm volatile("st.shared.b32 [%0], %1;" :: "r"(a), "r"(v) : "memory"); }
__device__ __forceinline__ void stsf(uint32_t a, float v) { sts32(a, __float_as_uint(v)); }
__device__ __forceinline__ void sts64f(uint32_t a, float x, float y) { asm volatile("st.shared.v2.f32 [%0], {%1, %2};" :: "r"(a), "f"(x), "f"(y) : "memory"); }
__device__ __forceinline__ void sts128(uint32_t a, const uint4& v) { asm volatile("st.shared.v4.b32 [%0], {%1, %2, %3, %4};" :: "r"(a), "r"(v.x), "r"(v.y), "r"(v.z), "r"(v.w) : "memory"); }
__device__ __forceinline__ void stsm4(uint32_t a, uint32_t x, uint32_t y, uint32_t z, uint32_t w) {
    asm volatile("stmatrix.sync.aligned.m8n8.x4.shared.b16 [%0], {%1, %2, %3, %4};" :: "r"(a), "r"(x), "r"(y), "r"(z), "r"(w) : "memory");
}
__device__ __forceinline__ void ldsm4(uint32_t& a0, uint32_t& a1, uint32_t& a2, uint32_t& a3, uint32_t addr) {
    asm volatile("ldmatrix.sync.aligned.m8n8.x4.shared.b16 {%0,%1,%2,%3}, [%4];" : "=r"(a0), "=r"(a1), "=r"(a2), "=r"(a3) : "r"(addr) : "memory");
}
__device__ __forceinline__ void ldsm4t(uint32_t& a0, uint32_t& a1, uint32_t& a2, uint32_t& a3, uint32_t addr) {
    asm volatile("ldmatrix.sync.aligned.m8n8.x4.trans.shared.b16 {%0,%1,%2,%3}, [%4];" : "=r"(a0), "=r"(a1), "=r"(a2), "=r"(a3) : "r"(addr) : "memory");
}
__device__ __forceinline__ void mma_bf16(float (&c)[4], uint32_t a0, uint32_t a1, uint32_t a2, uint32_t a3, uint32_t b0, uint32_t b1) {
    asm("mma.sync.aligned.m16n8k16.row.col.f32.bf16.bf16.f32 {%0,%1,%2,%3}, {%4,%5,%6,%7}, {%8,%9}, {%0,%1,%2,%3};"
        : "+f"(c[0]), "+f"(c[1]), "+f"(c[2]), "+f"(c[3]) : "r"(a0), "r"(a1), "r"(a2), "r"(a3), "r"(b0), "r"(b1));
}
__device__ __forceinline__ void mma_f16(float (&c)[4], uint32_t a0, uint32_t a1, uint32_t a2, uint32_t a3, uint32_t b0, uint32_t b1) {
    asm("mma.sync.aligned.m16n8k16.row.col.f32.f16.f16.f32 {%0,%1,%2,%3}, {%4,%5,%6,%7}, {%8,%9}, {%0,%1,%2,%3};"
        : "+f"(c[0]), "+f"(c[1]), "+f"(c[2]), "+f"(c[3]) : "r"(a0), "r"(a1), "r"(a2), "r"(a3), "r"(b0), "r"(b1));
}
__device__ __forceinline__ uint32_t ld_acquire(const void* p) { uint32_t v; asm volatile("ld.acquire.gpu.global.u32 %0, [%1];" : "=r"(v) : "l"(p) : "memory"); return v; }
__device__ __forceinline__ void sts_release(uint32_t a, uint32_t v) { asm volatile("st.release.cta.shared.u32 [%0], %1;" :: "r"(a), "r"(v) : "memory"); }
__device__ __forceinline__ uint32_t ld_relaxed(const void* p) { uint32_t v; asm volatile("ld.relaxed.gpu.global.u32 %0, [%1];" : "=r"(v) : "l"(p) : "memory"); return v; }
__device__ __forceinline__ uint4 ld_relaxed4(const void* p) {
    uint4 v; asm volatile("ld.relaxed.gpu.global.v4.b32 {%0, %1, %2, %3}, [%4];" : "=r"(v.x), "=r"(v.y), "=r"(v.z), "=r"(v.w) : "l"(p) : "memory"); return v;
}
__device__ __forceinline__ uint2 ld_relaxed2(const void* p) { uint2 v; asm volatile("ld.relaxed.gpu.global.v2.b32 {%0, %1}, [%2];" : "=r"(v.x), "=r"(v.y) : "l"(p) : "memory"); return v; }
__device__ __forceinline__ void st_relaxed(void* p, uint32_t v) { asm volatile("st.relaxed.gpu.global.u32 [%0], %1;" :: "l"(p), "r"(v) : "memory"); }
__device__ __forceinline__ void st_relaxed4_if(void* p, const uint4& v, bool on) {
    asm volatile("{\n.reg .pred q;\nsetp.ne.u32 q, %5, 0;\n@q st.relaxed.gpu.global.v4.b32 [%0], {%1, %2, %3, %4};\n}"
                 :: "l"(p), "r"(v.x), "r"(v.y), "r"(v.z), "r"(v.w), "r"((uint32_t)on) : "memory");
}
__device__ __forceinline__ uint32_t not_sent(float v) { const uint32_t u = __float_as_uint(v); return u == SENT ? 0x7FFFFFFFu : u; }
__device__ __forceinline__ bool has_sent(const uint4& v) { return max(max(v.x, v.y), max(v.z, v.w)) == SENT; }
constexpr uint32_t SPIN_MAX = 1u << 22;
__device__ __forceinline__ void spin_check(uint32_t n) { asm volatile("{\n.reg .pred p;\nsetp.ge.u32 p, %0, %1;\n@p st.global.u32 [%2], %0;\n}" :: "r"(n), "n"(SPIN_MAX), "l"(0ull) : "memory"); }
__device__ __forceinline__ void ctr_arrive(uint32_t* c) { asm volatile(ELECT("red.release.gpu.global.add.u32 [%0], 1;") :: "l"(c) : "memory"); }
__device__ __forceinline__ void ctr_wait(const uint32_t* c, uint32_t target) {
    asm volatile("{\n.reg .pred p;\n.reg .u32 n, v;\nmov.u32 n, 0;\n"
                 "LAB_WAIT:\nld.acquire.gpu.global.u32 v, [%0];\nsetp.ge.u32 p, v, %1;\n@p bra LAB_DONE;\n"
                 "add.u32 n, n, 1;\nsetp.lt.u32 p, n, 0x400000;\n@p bra LAB_WAIT;\ntrap;\nLAB_DONE:\n}" :: "l"(c), "r"(target) : "memory");
}
__device__ __forceinline__ void ctr_wait_all(const uint32_t* c, uint32_t target) {
    asm volatile("{\n.reg .pred p;\n.reg .u32 n, v;\nmov.u32 n, 0;\n"
                 "LAB_WAIT:\nld.acquire.gpu.global.u32 v, [%0];\nsetp.ge.u32 p, v, %1;\nvote.sync.all.pred p, p, 0xffffffff;\n@p bra.uni LAB_DONE;\n"
                 "add.u32 n, n, 1;\nsetp.lt.u32 p, n, 0x400000;\n@p bra.uni LAB_WAIT;\ntrap;\nLAB_DONE:\n}" :: "l"(c), "r"(target) : "memory");
}
__device__ __forceinline__ uint32_t smem_wait_any(uint32_t a, uint32_t mask) {
    uint32_t v;
    asm volatile("{\n.reg .pred p;\n.reg .u32 n, t;\nmov.u32 n, 0;\n"
                 "LAB_WAIT:\nld.acquire.cta.shared.u32 %0, [%1];\nand.b32 t, %0, %2;\nsetp.ne.u32 p, t, 0;\nvote.sync.all.pred p, p, 0xffffffff;\n@p bra.uni LAB_DONE;\n"
                 "add.u32 n, n, 1;\nsetp.lt.u32 p, n, 0x4000000;\n@p bra.uni LAB_WAIT;\ntrap;\nLAB_DONE:\n}" : "=r"(v) : "r"(a), "r"(mask) : "memory");
    return warp_uniform(v);
}
__device__ __forceinline__ void publish(uint32_t* c) { bulk_wait(); fence_async_global(); ctr_arrive(c); }

__device__ __forceinline__ void wg_fence() { asm volatile("wgmma.fence.sync.aligned;" ::: "memory"); }
__device__ __forceinline__ void wg_commit() { asm volatile("wgmma.commit_group.sync.aligned;" ::: "memory"); }
template <int N> __device__ __forceinline__ void wg_wait() { asm volatile("wgmma.wait_group.sync.aligned %0;" :: "n"(N) : "memory"); }
template <int N> __device__ __forceinline__ void reg_inc() { asm volatile("setmaxnreg.inc.sync.aligned.u32 %0;" :: "n"(N)); }
template <int N> __device__ __forceinline__ void reg_dec() { asm volatile("setmaxnreg.dec.sync.aligned.u32 %0;" :: "n"(N)); }
__host__ __device__ constexpr uint64_t desc_plain(uint32_t addr, uint32_t lbo, uint32_t sbo) {
    return (uint64_t)((addr & 0x3FFFF) >> 4) | ((uint64_t)(lbo >> 4) << 16) | ((uint64_t)(sbo >> 4) << 32);
}
__host__ __device__ constexpr uint64_t desc_sw128(uint32_t addr, uint32_t lbo, uint32_t sbo) { return desc_plain(addr, lbo, sbo) | (1ull << 62); }

__device__ __forceinline__ float ex2(float x) { float y; asm("ex2.approx.ftz.f32 %0, %1;" : "=f"(y) : "f"(x)); return y; }
__device__ __forceinline__ float rcp(float x) { float y; asm("rcp.approx.ftz.f32 %0, %1;" : "=f"(y) : "f"(x)); return y; }
__device__ __forceinline__ float rsq(float x) { float y; asm("rsqrt.approx.ftz.f32 %0, %1;" : "=f"(y) : "f"(x)); return y; }
__device__ __forceinline__ uint32_t pack_bf16(float lo, float hi) { uint32_t r; asm("cvt.rn.bf16x2.f32 %0, %1, %2;" : "=r"(r) : "f"(hi), "f"(lo)); return r; }
__device__ __forceinline__ uint32_t pack_f16(float lo, float hi) { uint32_t r; asm("cvt.rn.f16x2.f32 %0, %1, %2;" : "=r"(r) : "f"(hi), "f"(lo)); return r; }
__device__ __forceinline__ float bf_lo(uint32_t v) { return __uint_as_float(v << 16); }
__device__ __forceinline__ float bf_hi(uint32_t v) { return __uint_as_float(v & 0xFFFF0000u); }
__device__ __forceinline__ float bf_round(float x) { return __uint_as_float(pack_bf16(0.f, x)); }
__device__ __forceinline__ uint32_t badd2(uint32_t a, uint32_t b) { uint32_t r; asm("add.rn.bf16x2 %0, %1, %2;" : "=r"(r) : "r"(a), "r"(b)); return r; }
__device__ __forceinline__ void h2_unpack(uint32_t v, float& lo, float& hi) {
    asm("{.reg .f16 l, h; mov.b32 {l, h}, %2; cvt.f32.f16 %0, l; cvt.f32.f16 %1, h;}" : "=f"(lo), "=f"(hi) : "r"(v));
}
__device__ __forceinline__ uint32_t add_ln2(uint32_t x, float rstd, float nb) { return badd2(x, pack_bf16(fmaf(bf_lo(x), rstd, nb), fmaf(bf_hi(x), rstd, nb))); }
__device__ __forceinline__ float sel4(int t, float a0, float a1, float a2, float a3) {
    float r;
    asm("{\n.reg .pred p, q;\n.reg .f32 x, y;\nsetp.ne.u32 p, %1, 0;\nsetp.ne.u32 q, %2, 0;\nselp.f32 x, %4, %3, p;\nselp.f32 y, %6, %5, p;\nselp.f32 %0, y, x, q;\n}"
        : "=f"(r) : "r"(t & 1), "r"(t & 2), "f"(a0), "f"(a1), "f"(a2), "f"(a3));
    return r;
}
__device__ __forceinline__ float warp_sum(float v) {
    #pragma unroll
    for (int o = 16; o > 0; o >>= 1) v += __shfl_xor_sync(0xffffffffu, v, o);
    return v;
}
__device__ __forceinline__ uint32_t redux_max(uint32_t v) { uint32_t r; asm volatile("redux.sync.max.u32 %0, %1, 0xffffffff;" : "=r"(r) : "r"(v)); return r; }
__device__ __forceinline__ uint32_t redux_min(uint32_t v) { uint32_t r; asm volatile("redux.sync.min.u32 %0, %1, 0xffffffff;" : "=r"(r) : "r"(v)); return r; }

#define TL(T, L, i)

__device__ __forceinline__ void wg_gemm_n128(float (&d)[64], uint64_t desca, uint64_t desc) {
    asm volatile("{\n.reg .pred p;\nsetp.ne.b32 p, 1, 0;\n"
        "wgmma.mma_async.sync.aligned.m64n128k16.f32.bf16.bf16 "
        "{%0,%1,%2,%3,%4,%5,%6,%7,%8,%9,%10,%11,%12,%13,%14,%15,%16,%17,%18,%19,%20,%21,%22,%23,%24,%25,%26,%27,%28,%29,%30,%31,%32,%33,%34,%35,%36,%37,%38,%39,%40,%41,%42,%43,%44,%45,%46,%47,%48,%49,%50,%51,%52,%53,%54,%55,%56,%57,%58,%59,%60,%61,%62,%63}, "
        "%64, %65, p, 1, 1, 0, 1;\n}\n"
        : "+f"(d[0]), "+f"(d[1]), "+f"(d[2]), "+f"(d[3]), "+f"(d[4]), "+f"(d[5]), "+f"(d[6]), "+f"(d[7]),
          "+f"(d[8]), "+f"(d[9]), "+f"(d[10]), "+f"(d[11]), "+f"(d[12]), "+f"(d[13]), "+f"(d[14]), "+f"(d[15]),
          "+f"(d[16]), "+f"(d[17]), "+f"(d[18]), "+f"(d[19]), "+f"(d[20]), "+f"(d[21]), "+f"(d[22]), "+f"(d[23]),
          "+f"(d[24]), "+f"(d[25]), "+f"(d[26]), "+f"(d[27]), "+f"(d[28]), "+f"(d[29]), "+f"(d[30]), "+f"(d[31]),
          "+f"(d[32]), "+f"(d[33]), "+f"(d[34]), "+f"(d[35]), "+f"(d[36]), "+f"(d[37]), "+f"(d[38]), "+f"(d[39]),
          "+f"(d[40]), "+f"(d[41]), "+f"(d[42]), "+f"(d[43]), "+f"(d[44]), "+f"(d[45]), "+f"(d[46]), "+f"(d[47]),
          "+f"(d[48]), "+f"(d[49]), "+f"(d[50]), "+f"(d[51]), "+f"(d[52]), "+f"(d[53]), "+f"(d[54]), "+f"(d[55]),
          "+f"(d[56]), "+f"(d[57]), "+f"(d[58]), "+f"(d[59]), "+f"(d[60]), "+f"(d[61]), "+f"(d[62]), "+f"(d[63])
        : "l"(desca), "l"(desc));
}
__device__ __forceinline__ void wg_gemm_n128_init(float (&d)[64], uint64_t desca, uint64_t desc) {
    asm volatile("{\n.reg .pred p;\nsetp.ne.b32 p, 0, 0;\n"
        "wgmma.mma_async.sync.aligned.m64n128k16.f32.bf16.bf16 "
        "{%0,%1,%2,%3,%4,%5,%6,%7,%8,%9,%10,%11,%12,%13,%14,%15,%16,%17,%18,%19,%20,%21,%22,%23,%24,%25,%26,%27,%28,%29,%30,%31,%32,%33,%34,%35,%36,%37,%38,%39,%40,%41,%42,%43,%44,%45,%46,%47,%48,%49,%50,%51,%52,%53,%54,%55,%56,%57,%58,%59,%60,%61,%62,%63}, "
        "%64, %65, p, 1, 1, 0, 1;\n}\n"
        : "=f"(d[0]), "=f"(d[1]), "=f"(d[2]), "=f"(d[3]), "=f"(d[4]), "=f"(d[5]), "=f"(d[6]), "=f"(d[7]),
          "=f"(d[8]), "=f"(d[9]), "=f"(d[10]), "=f"(d[11]), "=f"(d[12]), "=f"(d[13]), "=f"(d[14]), "=f"(d[15]),
          "=f"(d[16]), "=f"(d[17]), "=f"(d[18]), "=f"(d[19]), "=f"(d[20]), "=f"(d[21]), "=f"(d[22]), "=f"(d[23]),
          "=f"(d[24]), "=f"(d[25]), "=f"(d[26]), "=f"(d[27]), "=f"(d[28]), "=f"(d[29]), "=f"(d[30]), "=f"(d[31]),
          "=f"(d[32]), "=f"(d[33]), "=f"(d[34]), "=f"(d[35]), "=f"(d[36]), "=f"(d[37]), "=f"(d[38]), "=f"(d[39]),
          "=f"(d[40]), "=f"(d[41]), "=f"(d[42]), "=f"(d[43]), "=f"(d[44]), "=f"(d[45]), "=f"(d[46]), "=f"(d[47]),
          "=f"(d[48]), "=f"(d[49]), "=f"(d[50]), "=f"(d[51]), "=f"(d[52]), "=f"(d[53]), "=f"(d[54]), "=f"(d[55]),
          "=f"(d[56]), "=f"(d[57]), "=f"(d[58]), "=f"(d[59]), "=f"(d[60]), "=f"(d[61]), "=f"(d[62]), "=f"(d[63])
        : "l"(desca), "l"(desc));
}
__device__ __forceinline__ void wg_gemm_n192(float (&d)[96], uint64_t desca, uint64_t desc) {
    asm volatile("{\n.reg .pred p;\nsetp.ne.b32 p, 1, 0;\n"
        "wgmma.mma_async.sync.aligned.m64n192k16.f32.bf16.bf16 "
        "{%0,%1,%2,%3,%4,%5,%6,%7,%8,%9,%10,%11,%12,%13,%14,%15,%16,%17,%18,%19,%20,%21,%22,%23,%24,%25,%26,%27,%28,%29,%30,%31,%32,%33,%34,%35,%36,%37,%38,%39,%40,%41,%42,%43,%44,%45,%46,%47,%48,%49,%50,%51,%52,%53,%54,%55,%56,%57,%58,%59,%60,%61,%62,%63,%64,%65,%66,%67,%68,%69,%70,%71,%72,%73,%74,%75,%76,%77,%78,%79,%80,%81,%82,%83,%84,%85,%86,%87,%88,%89,%90,%91,%92,%93,%94,%95}, "
        "%96, %97, p, 1, 1, 0, 1;\n}\n"
        : "+f"(d[0]), "+f"(d[1]), "+f"(d[2]), "+f"(d[3]), "+f"(d[4]), "+f"(d[5]), "+f"(d[6]), "+f"(d[7]),
          "+f"(d[8]), "+f"(d[9]), "+f"(d[10]), "+f"(d[11]), "+f"(d[12]), "+f"(d[13]), "+f"(d[14]), "+f"(d[15]),
          "+f"(d[16]), "+f"(d[17]), "+f"(d[18]), "+f"(d[19]), "+f"(d[20]), "+f"(d[21]), "+f"(d[22]), "+f"(d[23]),
          "+f"(d[24]), "+f"(d[25]), "+f"(d[26]), "+f"(d[27]), "+f"(d[28]), "+f"(d[29]), "+f"(d[30]), "+f"(d[31]),
          "+f"(d[32]), "+f"(d[33]), "+f"(d[34]), "+f"(d[35]), "+f"(d[36]), "+f"(d[37]), "+f"(d[38]), "+f"(d[39]),
          "+f"(d[40]), "+f"(d[41]), "+f"(d[42]), "+f"(d[43]), "+f"(d[44]), "+f"(d[45]), "+f"(d[46]), "+f"(d[47]),
          "+f"(d[48]), "+f"(d[49]), "+f"(d[50]), "+f"(d[51]), "+f"(d[52]), "+f"(d[53]), "+f"(d[54]), "+f"(d[55]),
          "+f"(d[56]), "+f"(d[57]), "+f"(d[58]), "+f"(d[59]), "+f"(d[60]), "+f"(d[61]), "+f"(d[62]), "+f"(d[63]),
          "+f"(d[64]), "+f"(d[65]), "+f"(d[66]), "+f"(d[67]), "+f"(d[68]), "+f"(d[69]), "+f"(d[70]), "+f"(d[71]),
          "+f"(d[72]), "+f"(d[73]), "+f"(d[74]), "+f"(d[75]), "+f"(d[76]), "+f"(d[77]), "+f"(d[78]), "+f"(d[79]),
          "+f"(d[80]), "+f"(d[81]), "+f"(d[82]), "+f"(d[83]), "+f"(d[84]), "+f"(d[85]), "+f"(d[86]), "+f"(d[87]),
          "+f"(d[88]), "+f"(d[89]), "+f"(d[90]), "+f"(d[91]), "+f"(d[92]), "+f"(d[93]), "+f"(d[94]), "+f"(d[95])
        : "l"(desca), "l"(desc));
}
__device__ __forceinline__ void wg_gemm_n192_init(float (&d)[96], uint64_t desca, uint64_t desc) {
    asm volatile("{\n.reg .pred p;\nsetp.ne.b32 p, 0, 0;\n"
        "wgmma.mma_async.sync.aligned.m64n192k16.f32.bf16.bf16 "
        "{%0,%1,%2,%3,%4,%5,%6,%7,%8,%9,%10,%11,%12,%13,%14,%15,%16,%17,%18,%19,%20,%21,%22,%23,%24,%25,%26,%27,%28,%29,%30,%31,%32,%33,%34,%35,%36,%37,%38,%39,%40,%41,%42,%43,%44,%45,%46,%47,%48,%49,%50,%51,%52,%53,%54,%55,%56,%57,%58,%59,%60,%61,%62,%63,%64,%65,%66,%67,%68,%69,%70,%71,%72,%73,%74,%75,%76,%77,%78,%79,%80,%81,%82,%83,%84,%85,%86,%87,%88,%89,%90,%91,%92,%93,%94,%95}, "
        "%96, %97, p, 1, 1, 0, 1;\n}\n"
        : "=f"(d[0]), "=f"(d[1]), "=f"(d[2]), "=f"(d[3]), "=f"(d[4]), "=f"(d[5]), "=f"(d[6]), "=f"(d[7]),
          "=f"(d[8]), "=f"(d[9]), "=f"(d[10]), "=f"(d[11]), "=f"(d[12]), "=f"(d[13]), "=f"(d[14]), "=f"(d[15]),
          "=f"(d[16]), "=f"(d[17]), "=f"(d[18]), "=f"(d[19]), "=f"(d[20]), "=f"(d[21]), "=f"(d[22]), "=f"(d[23]),
          "=f"(d[24]), "=f"(d[25]), "=f"(d[26]), "=f"(d[27]), "=f"(d[28]), "=f"(d[29]), "=f"(d[30]), "=f"(d[31]),
          "=f"(d[32]), "=f"(d[33]), "=f"(d[34]), "=f"(d[35]), "=f"(d[36]), "=f"(d[37]), "=f"(d[38]), "=f"(d[39]),
          "=f"(d[40]), "=f"(d[41]), "=f"(d[42]), "=f"(d[43]), "=f"(d[44]), "=f"(d[45]), "=f"(d[46]), "=f"(d[47]),
          "=f"(d[48]), "=f"(d[49]), "=f"(d[50]), "=f"(d[51]), "=f"(d[52]), "=f"(d[53]), "=f"(d[54]), "=f"(d[55]),
          "=f"(d[56]), "=f"(d[57]), "=f"(d[58]), "=f"(d[59]), "=f"(d[60]), "=f"(d[61]), "=f"(d[62]), "=f"(d[63]),
          "=f"(d[64]), "=f"(d[65]), "=f"(d[66]), "=f"(d[67]), "=f"(d[68]), "=f"(d[69]), "=f"(d[70]), "=f"(d[71]),
          "=f"(d[72]), "=f"(d[73]), "=f"(d[74]), "=f"(d[75]), "=f"(d[76]), "=f"(d[77]), "=f"(d[78]), "=f"(d[79]),
          "=f"(d[80]), "=f"(d[81]), "=f"(d[82]), "=f"(d[83]), "=f"(d[84]), "=f"(d[85]), "=f"(d[86]), "=f"(d[87]),
          "=f"(d[88]), "=f"(d[89]), "=f"(d[90]), "=f"(d[91]), "=f"(d[92]), "=f"(d[93]), "=f"(d[94]), "=f"(d[95])
        : "l"(desca), "l"(desc));
}
__device__ __forceinline__ void wg_qk_init(uint32_t (&d)[32], uint64_t desca, uint64_t desc) {
    asm volatile("{\n.reg .pred p;\nsetp.ne.b32 p, 0, 0;\n"
        "wgmma.mma_async.sync.aligned.m64n128k16.f16.f16.f16 "
        "{%0,%1,%2,%3,%4,%5,%6,%7,%8,%9,%10,%11,%12,%13,%14,%15,%16,%17,%18,%19,%20,%21,%22,%23,%24,%25,%26,%27,%28,%29,%30,%31}, "
        "%32, %33, p, 1, 1, 0, 0;\n}\n"
        : "=r"(d[0]), "=r"(d[1]), "=r"(d[2]), "=r"(d[3]), "=r"(d[4]), "=r"(d[5]), "=r"(d[6]), "=r"(d[7]),
          "=r"(d[8]), "=r"(d[9]), "=r"(d[10]), "=r"(d[11]), "=r"(d[12]), "=r"(d[13]), "=r"(d[14]), "=r"(d[15]),
          "=r"(d[16]), "=r"(d[17]), "=r"(d[18]), "=r"(d[19]), "=r"(d[20]), "=r"(d[21]), "=r"(d[22]), "=r"(d[23]),
          "=r"(d[24]), "=r"(d[25]), "=r"(d[26]), "=r"(d[27]), "=r"(d[28]), "=r"(d[29]), "=r"(d[30]), "=r"(d[31])
        : "l"(desca), "l"(desc));
}
__device__ __forceinline__ void wg_qk_acc(uint32_t (&d)[32], uint64_t desca, uint64_t desc) {
    asm volatile("{\n.reg .pred p;\nsetp.ne.b32 p, 1, 0;\n"
        "wgmma.mma_async.sync.aligned.m64n128k16.f16.f16.f16 "
        "{%0,%1,%2,%3,%4,%5,%6,%7,%8,%9,%10,%11,%12,%13,%14,%15,%16,%17,%18,%19,%20,%21,%22,%23,%24,%25,%26,%27,%28,%29,%30,%31}, "
        "%32, %33, p, 1, 1, 0, 0;\n}\n"
        : "+r"(d[0]), "+r"(d[1]), "+r"(d[2]), "+r"(d[3]), "+r"(d[4]), "+r"(d[5]), "+r"(d[6]), "+r"(d[7]),
          "+r"(d[8]), "+r"(d[9]), "+r"(d[10]), "+r"(d[11]), "+r"(d[12]), "+r"(d[13]), "+r"(d[14]), "+r"(d[15]),
          "+r"(d[16]), "+r"(d[17]), "+r"(d[18]), "+r"(d[19]), "+r"(d[20]), "+r"(d[21]), "+r"(d[22]), "+r"(d[23]),
          "+r"(d[24]), "+r"(d[25]), "+r"(d[26]), "+r"(d[27]), "+r"(d[28]), "+r"(d[29]), "+r"(d[30]), "+r"(d[31])
        : "l"(desca), "l"(desc));
}
__device__ __forceinline__ void wg_pv_init(uint32_t (&d)[10], uint32_t a0, uint32_t a1, uint32_t a2, uint32_t a3, uint64_t desc) {
    asm volatile("{\n.reg .pred p;\nsetp.ne.b32 p, 0, 0;\n"
        "wgmma.mma_async.sync.aligned.m64n40k16.f16.f16.f16 "
        "{%0,%1,%2,%3,%4,%5,%6,%7,%8,%9}, "
        "{%10,%11,%12,%13}, %14, p, 1, 1, 1;\n}\n"
        : "=r"(d[0]), "=r"(d[1]), "=r"(d[2]), "=r"(d[3]), "=r"(d[4]), "=r"(d[5]), "=r"(d[6]), "=r"(d[7]),
          "=r"(d[8]), "=r"(d[9])
        : "r"(a0), "r"(a1), "r"(a2), "r"(a3), "l"(desc));
}
__device__ __forceinline__ void wg_pv_acc(uint32_t (&d)[10], uint32_t a0, uint32_t a1, uint32_t a2, uint32_t a3, uint64_t desc) {
    asm volatile("{\n.reg .pred p;\nsetp.ne.b32 p, 1, 0;\n"
        "wgmma.mma_async.sync.aligned.m64n40k16.f16.f16.f16 "
        "{%0,%1,%2,%3,%4,%5,%6,%7,%8,%9}, "
        "{%10,%11,%12,%13}, %14, p, 1, 1, 1;\n}\n"
        : "+r"(d[0]), "+r"(d[1]), "+r"(d[2]), "+r"(d[3]), "+r"(d[4]), "+r"(d[5]), "+r"(d[6]), "+r"(d[7]),
          "+r"(d[8]), "+r"(d[9])
        : "r"(a0), "r"(a1), "r"(a2), "r"(a3), "l"(desc));
}

constexpr int Q_ABYTES = 256 * 64 * 2, Q_STB = Q_ABYTES + 192 * 64 * 2;
constexpr int OFF_SIDE = 3 * Q_STB;
constexpr int OFF_XS = OFF_SIDE + 49152;
constexpr int OFF_CS = OFF_XS + 4096;
constexpr int OFF_RC = OFF_CS + 768;
constexpr int OFF_FIX = OFF_RC + 2048;
constexpr int A_WIN = KV_WIN + 4096;
constexpr int OFF_QA = 3 * A_WIN;
constexpr int OFF_LC = OFF_QA + 32768;
constexpr int OFF_FE = 147456;
constexpr int OFF_XT = 196608;
__host__ __device__ constexpr uint32_t o_stage(uint32_t s) { return s == 3 ? OFF_QA : s == 2 ? 0 : (s + 1) * A_WIN; }
__host__ __device__ constexpr uint32_t gu_piece(uint32_t i) { return i < 3 ? OFF_FE + i * 16384 : i < 6 ? (i - 1) * 16384 : (i - 6) * 16384; }
constexpr int OFF_FD = 5 * 16384;
constexpr int OFF_BAR = OFF_XT + 32768;
constexpr int OFF_PART = OFF_BAR + 384;
constexpr int OFF_RED = OFF_PART + 2048;
constexpr int OFF_RT = OFF_RED + 96;
constexpr int OFF_M = OFF_RT + 144;
constexpr int OFF_WR = OFF_M + 72;
constexpr int K_SMEM = OFF_WR + 264;
static_assert(K_SMEM <= 232448 && OFF_FIX + 768 <= OFF_BAR && OFF_QA + 32768 <= OFF_FE, "smem");
constexpr uint32_t CH_OK = 0x38003800u;
constexpr int M_SC = 0,
              M_IVS = 24,
              M_ISC = 32,
              M_OK = 40,
              M_WS = 48,
              M_RIDX = 60,
              M_ORDY = 64;
constexpr uint32_t BB = SB + OFF_BAR;
constexpr uint32_t B_QF = BB, B_EPI = BB + 24, B_RES2 = BB + 56, B_AF = BB + 64, B_RES = BB + 120, B_OF = BB + 128,
                   B_FE = BB + 160, B_FL = BB + 168, B_FD = BB + 184, B_PR = BB + 192, B_FW = B_PR, B_SW = BB + 216,
                   B_QE = BB + 224, B_QAF = BB + 248, B_OE = BB + 288, B_AE = BB + 320, B_KV0 = BB + 376;

constexpr int N_OST = 5, N_XST = 9, N_RT = 11, N_KV1 = 12, N_FW = 13, N_GD = 14, N_DD = 15;

struct Maps { CUtensorMap xa0, wqkv, xa, x0, x, out, w64, wo, r, g, u, d, xs; };

__device__ __forceinline__ float2 ln_coef(const uint4& s) {
    const float mean = __uint_as_float(s.x) * (1.f / D_);
    return make_float2(rsq(fmaxf(fmaf(-mean, mean, fmaf(__uint_as_float(s.y), 1.f / D_, LN_EPS)), LN_EPS)), mean);
}
__device__ __forceinline__ uint32_t order_bits(float r) { const uint32_t u = __float_as_uint(r); return (u & 0x80000000u) ? ~u : (u | 0x80000000u); }
__device__ __forceinline__ uint4 warp_best(const uint4& e) {
    const uint32_t m = redux_max(e.x), row = redux_min(e.x == m ? e.y : 0x7FFFFFFFu);
    const int src = __ffs(__ballot_sync(0xffffffffu, e.y == row)) - 1;
    return make_uint4(m, row, __shfl_sync(0xffffffffu, e.z, src), __shfl_sync(0xffffffffu, e.w, src));
}
__device__ __forceinline__ RouteOut route_out(const uint4& e) {
    RouteOut rt;
    rt.idx = e.y; rt.r = __uint_as_float((e.x & 0x80000000u) ? e.x & 0x7FFFFFFFu : ~e.x); rt.mean = __uint_as_float(e.z); rt.rstd = __uint_as_float(e.w);
    return rt;
}

__device__ __forceinline__ void prep_work(const bf16* __restrict__ x0, const CUtensorMap* tmW, int t) {
    const int c = blockIdx.x, lane = t & 31, warp = warp_uniform(t >> 5);
    const int ki = c >> 4, n = c & 15;
    constexpr uint32_t red = SB + OFF_SIDE, xs = red + 4096;
    if (warp == 0) {
        mbar_expect_tx(B_PR, 32768);
        bulk_load(xs, x0 + (size_t)c * 16 * D_, 32768, B_PR);
        mbar_expect_tx(B_PR + 8, 16384);
        tma_load(xs + 32768, tmW, 2 * D_ + n * 64, ki * 128, B_PR + 8);
        tma_load(xs + 32768 + 8192, tmW, 2 * D_ + n * 64, ki * 128 + 64, B_PR + 8);
    }
    const uint4 sent = make_uint4(SENT, SENT, SENT, SENT);
    for (int i = t; i < 2 * NFC * 2; i += 96) reinterpret_cast<uint4*>(&g_ypart[0][0][0])[c * (2 * NFC * 2) + i] = sent;
    if (t < 64) reinterpret_cast<uint4*>(&g_acc[0][0][0])[c * 64 + t] = make_uint4(0u, 0u, 0u, 0u);
    if (t >= 64 && t < 80) g_sums[c * 16 + t - 64] = sent;
    if (t < 2) reinterpret_cast<uint4*>(g_x2row)[c * 2 + t] = sent;
    else if (t < 8) reinterpret_cast<uint4*>(g_fix)[c * 6 + t - 2] = sent;
    else if (t < 12) (&g_kvc[0][0][0])[c * 4 + t - 8] = 0u;
    else if (t >= 24 && t < 32) (&g_oc[0][0][0][0])[c * 8 + t - 24] = 0u;
    else if (t == 13 && c < 16) (&g_xc[0][0])[c] = 0u;
    else if (t >= 16 && t < 20) (&g_tab[0][0][0][0])[c * 4 + t - 16] = sent;
    else if (t >= 32 && t < 64) reinterpret_cast<uint4*>(&g_xrow[0][0][0])[c * 32 + t - 32] = sent;
    mbar_wait(B_PR, 0);
    #pragma unroll 1
    for (int r = warp; r < 16; r += 3) {
        float s = 0.f, q = 0.f;
        #pragma unroll
        for (int i = 0; i < 4; i++) {
            const uint4 u = lds128(xs + r * 2048 + (lane + 32 * i) * 16);
            const float f[8] = {bf_lo(u.x), bf_hi(u.x), bf_lo(u.y), bf_hi(u.y), bf_lo(u.z), bf_hi(u.z), bf_lo(u.w), bf_hi(u.w)};
            #pragma unroll
            for (int e = 0; e < 8; e++) { s += f[e]; q = fmaf(f[e], f[e], q); }
        }
        #pragma unroll
        for (int o = 16; o > 0; o >>= 1) { s += __shfl_xor_sync(0xffffffffu, s, o); q += __shfl_xor_sync(0xffffffffu, q, o); }
        const float mean = s * (1.f / D_);
        const float var = fmaxf(q * (1.f / D_) - mean * mean, 0.f);
        if (lane == 0) g_rs0[c * 16 + r] = make_float2(rsqrtf(var + LN_EPS), mean);
    }
    named_sync(2, 96);
    if (warp == 0) {
        mbar_expect_tx(B_PR + 16, 32768);
        #pragma unroll
        for (int b = 0; b < 4; b++) tma_load(xs + b * 8192, tmW, (b >> 1) * D_ + n * 64, ki * 128 + (b & 1) * 64, B_PR + 16);
    }
    const int j = t & 7, rg = t >> 3;
    #pragma unroll 1
    for (int blk = 0; blk < 3; blk++) {
        const int type = blk == 0 ? 2 : blk - 1;
        const uint32_t wb = xs + type * 16384;
        if (blk < 2) mbar_wait(B_PR + 8 + 8 * blk, 0);
        float cs[8];
        uint32_t z2[4] = {0u, 0u, 0u, 0u};
        #pragma unroll
        for (int i = 0; i < 8; i++) cs[i] = 0.f;
        #pragma unroll 4
        for (int r = rg; r < 128; r += 12) {
            const uint4 u = lds128(wb + r * 128 + ((j ^ (r & 7)) << 4));
            cs[0] += bf_lo(u.x); cs[1] += bf_hi(u.x); cs[2] += bf_lo(u.y); cs[3] += bf_hi(u.y);
            cs[4] += bf_lo(u.z); cs[5] += bf_hi(u.z); cs[6] += bf_lo(u.w); cs[7] += bf_hi(u.w);
            asm("fma.rn.bf16x2 %0, %1, %1, %0;" : "+r"(z2[0]) : "r"(u.x));
            asm("fma.rn.bf16x2 %0, %1, %1, %0;" : "+r"(z2[1]) : "r"(u.y));
            asm("fma.rn.bf16x2 %0, %1, %1, %0;" : "+r"(z2[2]) : "r"(u.z));
            asm("fma.rn.bf16x2 %0, %1, %1, %0;" : "+r"(z2[3]) : "r"(u.w));
        }
        #pragma unroll
        for (int i = 0; i < 8; i++) { cs[i] += __shfl_xor_sync(0xffffffffu, cs[i], 8); cs[i] += __shfl_xor_sync(0xffffffffu, cs[i], 16); }
        float z = ((bf_lo(z2[0]) + bf_hi(z2[0])) + (bf_lo(z2[1]) + bf_hi(z2[1]))) + ((bf_lo(z2[2]) + bf_hi(z2[2])) + (bf_lo(z2[3]) + bf_hi(z2[3])));
        z += __shfl_xor_sync(0xffffffffu, z, 1); z += __shfl_xor_sync(0xffffffffu, z, 2);
        z += __shfl_xor_sync(0xffffffffu, z, 8); z += __shfl_xor_sync(0xffffffffu, z, 16);
        if (lane < 8) {
            #pragma unroll
            for (int i = 0; i < 8; i++) stsf(red + (warp * 200 + type * 64 + j * 8 + i) * 4, cs[i]);
            if ((lane & 3) == 0) stsf(red + (warp * 200 + 192 + type * 2 + (lane >> 2)) * 4, z);
        }
    }
    named_sync(2, 96);
    for (int i = t; i < 198; i += 96) {
        const float v = ldsf(red + i * 4) + ldsf(red + (200 + i) * 4) + ldsf(red + (400 + i) * 4);
        if (i < 192) g_csum[ki * (3 * D_) + (i >> 6) * D_ + n * 64 + (i & 63)] = v;
        else g_wsq[ki * 96 + ((i - 192) >> 1) * 32 + n * 2 + (i & 1)] = v;
    }
    named_sync(2, 96);
    if (warp == 0) { ctr_arrive(&g_c0); ctr_wait(&g_c0, 128); }
    named_sync(2, 96);
}

__device__ __forceinline__ float pow2_inv(float b) {
    const int e = min(max((int)(__float_as_uint(b) >> 23) + 1, 20), 234);
    return __uint_as_float((uint32_t)(254 - e) << 23);
}
__device__ __forceinline__ void epi_inputs(int L) {
    const int t = tid_now() - 288, mt = cta_now() >> 4, nt = cta_now() & 15;
    float p[2][8], r0[3], r1[3];
    #pragma unroll
    for (int k = 0; k < 2; k++)
        #pragma unroll
        for (int q = 0; q < 8; q++) p[k][q] = __ldcg(g_csum + q * (3 * D_) + ((t + 96 * k) >> 6) * D_ + nt * 64 + ((t + 96 * k) & 63));
    #pragma unroll
    for (int k = 0; k < 2; k++) stsf(SB + OFF_CS + (t + 96 * k) * 4, ((p[k][0] + p[k][1]) + (p[k][2] + p[k][3])) + ((p[k][4] + p[k][5]) + (p[k][6] + p[k][7])));
    bool wait;
    uint32_t n = 0;
    do {
        wait = false;
        #pragma unroll
        for (int k = 0; k < 3; k++) {
            const int row = mt * 256 + min(t + 96 * k, 255);
            if (L == 0) { const float2 s = __ldcg(&g_rs0[row]); r0[k] = s.x; r1[k] = s.y; }
            else { const uint4 s = ld_relaxed4(&g_sums[row]); r0[k] = __uint_as_float(s.x); r1[k] = __uint_as_float(s.y); wait = wait || has_sent(s); }
        }
    } while (wait && ++n < SPIN_MAX);
    #pragma unroll
    for (int k = 0; k < 3; k++) {
        if (L != 0) {
            const float mean = r0[k] * (1.f / D_);
            const float var = fmaxf(r1[k] * (1.f / D_) - mean * mean, 0.f);
            const float a = 1.f + rsqrtf(var + LN_EPS);
            r0[k] = a * rsqrtf(a * a * var + LN_EPS); r1[k] = mean;
        }
        if (t + 96 * k < 256) sts64f(SB + OFF_RC + (t + 96 * k) * 8, r0[k], r1[k]);
    }
    if (L == 0 && t < 32) {
        float z = 0.f;
        if (t < 6) {
            #pragma unroll
            for (int q = 0; q < 8; q++) z += __ldcg(g_wsq + q * 96 + (t >> 1) * 32 + nt * 2 + (t & 1));
        }
        const float b = sqrtf(z) * (t < 2 ? 34.f * QSCALE : 34.f);
        const float sc = t < 4 ? fminf(pow2_inv(b) * 32768.f, 1.f) : pow2_inv(b);
        const float bk = __shfl_down_sync(0xffffffffu, b, 2), sk = __shfl_down_sync(0xffffffffu, sc, 2);
        if (t < 6) stsf(SB + OFF_M + M_SC + t * 4, t < 2 ? sc * QSCALE : sc);
        if (t < 2) { stsf(SB + OFF_M + M_ISC + t * 4, 1.f / (sc * sk)); sts32(SB + OFF_M + M_OK + t * 4, sc == 1.f && sk == 1.f && b * bk < 60000.f ? CH_OK : 0u); }
        if (t == 4 || t == 5) stsf(SB + OFF_M + M_IVS + (t - 4) * 4, 1.f / sc);
    }
}

__device__ __forceinline__ int ypos_col(int p) { return (p >> 7) * 128 + ((p >> 1) & 7) * 16 + (p & 1) * 8 + ((p >> 4) & 7); }

template <int NT>
__device__ __forceinline__ float ffn_finish(int L, const RouteOut& rt, int t, uint32_t red, int bid) {
    constexpr int NL = (2 * NFC + NT - 1) / NT;
    const int c = cta_now(), col = ypos_col(c * 8 + (t & 7));
    const uint32_t* src = &g_ypart[L][t >> 1][c * 8 + (t & 1) * 4];
    uint32_t n = 0, xp;
    do { xp = ld_relaxed(&g_xrow[L][rt.idx >> 7][((col >> 5) & 7) * 64 + (col >> 8) * 16 + (col & 6) * 2 + ((col >> 3) & 3)]); } while (xp == SENT && ++n < SPIN_MAX);
    uint4 v[NL];
    #pragma unroll
    for (int i = 0; i < NL; i++) v[i] = t + NT * i < 2 * NFC ? ld_relaxed4(src + i * (NT / 2) * D_) : make_uint4(0u, 0u, 0u, 0u);
    const float xv = (col & 1) ? bf_hi(xp) : bf_lo(xp);
    float rsel = bf_round(rcp(1.f + ex2(bf_round(rt.r) * -1.4426950408889634f))), xn = bf_round((xv - rt.mean) * rt.rstd);
    asm volatile("" : "+f"(rsel), "+f"(xn));
    while (true) {
        bool wait = false;
        #pragma unroll
        for (int i = 0; i < NL; i++) wait = wait || has_sent(v[i]);
        if (!wait || ++n >= SPIN_MAX) break;
        #pragma unroll
        for (int i = 0; i < NL; i++) if (t + NT * i < 2 * NFC) v[i] = ld_relaxed4(src + i * (NT / 2) * D_);
    }
    spin_check(n);
    __syncwarp();
    float a[4] = {0.f, 0.f, 0.f, 0.f};
    #pragma unroll
    for (int i = 0; i < NL; i++) { a[0] += __uint_as_float(v[i].x); a[1] += __uint_as_float(v[i].y); a[2] += __uint_as_float(v[i].z); a[3] += __uint_as_float(v[i].w); }
    const bool b1 = t & 2, b2 = t & 4;
    a[0] = (b1 ? a[1] : a[0]) + __shfl_xor_sync(0xffffffffu, b1 ? a[0] : a[1], 2);
    a[2] = (b1 ? a[3] : a[2]) + __shfl_xor_sync(0xffffffffu, b1 ? a[2] : a[3], 2);
    a[0] = (b2 ? a[2] : a[0]) + __shfl_xor_sync(0xffffffffu, b2 ? a[0] : a[2], 4);
    a[0] += __shfl_xor_sync(0xffffffffu, a[0], 8); a[0] += __shfl_xor_sync(0xffffffffu, a[0], 16);
    if ((t & 31) < 8) stsf(red + (t >> 5) * 32 + (t & 1) * 16 + (t & 6) * 2, a[0]);
    named_sync(bid, NT);
    float y = 0.f, y2 = 0.f;
    #pragma unroll
    for (int i = 0; i < NT / 32; i++) { const float p = ldsf(red + (t & 7) * 4 + i * 32); if (i & 1) y2 += p; else y += p; }
    y += y2;
    return bf_round(xv + bf_round(xn + bf_round(bf_round(y) * rsel)));
}

__device__ __forceinline__ void routed_qkv(int ridx) {
    const int t = tid_now() - 288, c = cta_now(), lane = t & 31, warp = t >> 5;
    constexpr uint32_t red = SB + OFF_RED;
    {
        uint4 v[3];
        uint32_t n = 0;
        do {
            v[0] = ld_relaxed4(g_x2row + t * 4); v[1] = ld_relaxed4(g_x2row + (t + 96) * 4);
            v[2] = t < 64 ? ld_relaxed4(g_x2row + (t + 192) * 4) : make_uint4(0u, 0u, 0u, 0u);
        } while ((has_sent(v[0]) || has_sent(v[1]) || has_sent(v[2])) && ++n < SPIN_MAX);
        spin_check(n);
        __syncwarp();
        TL(288, 0, 21);
        float f[12];
        float s = 0.f;
        #pragma unroll
        for (int i = 0; i < 3; i++) { f[4*i] = __uint_as_float(v[i].x); f[4*i+1] = __uint_as_float(v[i].y); f[4*i+2] = __uint_as_float(v[i].z); f[4*i+3] = __uint_as_float(v[i].w); }
        #pragma unroll
        for (int i = 0; i < 12; i++) s += f[i];
        s = warp_sum(s);
        if (lane == 0) stsf(red + warp * 4, s);
        named_sync(2, 96);
        const float mean = (ldsf(red) + ldsf(red + 4) + ldsf(red + 8)) * (1.f / D_);
        float q = 0.f;
        #pragma unroll
        for (int i = 0; i < 12; i++) { f[i] -= mean; if (i < 8 || t < 64) q = fmaf(f[i], f[i], q); }
        q = warp_sum(q);
        if (lane == 0) stsf(red + 16 + warp * 4, q);
        named_sync(2, 96);
        const float rstd = rsqrtf((ldsf(red + 16) + ldsf(red + 20) + ldsf(red + 24)) * (1.f / D_) + LN_EPS);
        #pragma unroll
        for (int i = 0; i < 3; i++)
            if (i < 2 || t < 64) sts128(SB + OFF_XS + (t + 96 * i) * 16, make_uint4(pack_bf16(0.f, f[4*i] * rstd), pack_bf16(0.f, f[4*i+1] * rstd), pack_bf16(0.f, f[4*i+2] * rstd), pack_bf16(0.f, f[4*i+3] * rstd)));
    }
    named_sync(2, 96);
    TL(288, 0, 22);
    mbar_wait(B_SW, 0);
    TL(288, 0, 23);
    float a[8];
    #pragma unroll
    for (int i = 0; i < 8; i++) a[i] = 0.f;
    const uint32_t wa = SB + OFF_SIDE + t * 16, xa = SB + OFF_XS + (t / 3) * 4;
    #pragma unroll 4
    for (int i = 0; i < 32; i++) {
        const uint4 u = lds128(wa + i * 1536);
        const float xv = ldsf(xa + i * 128);
        a[0] = fmaf(xv, bf_lo(u.x), a[0]); a[1] = fmaf(xv, bf_hi(u.x), a[1]); a[2] = fmaf(xv, bf_lo(u.y), a[2]); a[3] = fmaf(xv, bf_hi(u.y), a[3]);
        a[4] = fmaf(xv, bf_lo(u.z), a[4]); a[5] = fmaf(xv, bf_hi(u.z), a[5]); a[6] = fmaf(xv, bf_lo(u.w), a[6]); a[7] = fmaf(xv, bf_hi(u.w), a[7]);
    }
    named_sync(2, 96);
    TL(288, 0, 41);
    sts128(SB + OFF_SIDE + t * 32, make_uint4(__float_as_uint(a[0]), __float_as_uint(a[1]), __float_as_uint(a[2]), __float_as_uint(a[3])));
    sts128(SB + OFF_SIDE + t * 32 + 16, make_uint4(__float_as_uint(a[4]), __float_as_uint(a[5]), __float_as_uint(a[6]), __float_as_uint(a[7])));
    named_sync(2, 96);
    {
        float y = 0.f;
        #pragma unroll
        for (int i = 0; i < 8; i++) y += ldsf(SB + OFF_SIDE + ((t & 3) * 8 + i) * 96 + (t >> 2) * 4);
        y += __shfl_xor_sync(0xffffffffu, y, 1); y += __shfl_xor_sync(0xffffffffu, y, 2);
        if ((t & 3) == 0) st_relaxed(g_fix + c * 24 + (t >> 2), not_sent(y));
    }
    if ((ridx >> 8) == (c >> 4) && t < 24) {
        const uint32_t* src = g_fix + (t >> 3) * D_ + (c & 15) * 64 + (t & 7) * 8;
        uint4 a, b;
        uint32_t n = 0;
        do { a = ld_relaxed4(src); b = ld_relaxed4(src + 4); } while ((has_sent(a) || has_sent(b)) && ++n < SPIN_MAX);
        spin_check(n);
        const int hh = t >> 2, ch = t & 3, lr = ridx & 255;
        const float hs = ldsf(SB + OFF_M + M_SC + hh * 4);
        sts128(SB + OFF_FIX + t * 16, make_uint4(pack_f16(__uint_as_float(a.x) * hs, __uint_as_float(a.y) * hs), pack_f16(__uint_as_float(a.z) * hs, __uint_as_float(a.w) * hs),
                                                 pack_f16(__uint_as_float(b.x) * hs, __uint_as_float(b.y) * hs), pack_f16(__uint_as_float(b.z) * hs, __uint_as_float(b.w) * hs)));
        sts32(SB + OFF_FIX + 512 + t * 4, SB + (hh < 2 ? OFF_QA + hh * 16384 + (lr >> 6) * 4096 + ch * 1024 + (lr & 63) * 16
                                                        : (hh & 1) * OFF_FE + (hh >> 2) * 16384 + ch * 4096 + lr * 16));
    }
    __syncwarp();
}

#define XP0 2
#define XP1 7
#define FW_NS 1000
__device__ __forceinline__ void ffn_load(const Maps& mp, int i, uint32_t dst, uint32_t bar, bool last_use) {
    if (i < 8) tma_load_h(dst, (i & 1) ? &mp.u : &mp.g, blockIdx.x * 32, (i >> 1) * 256, bar, last_use);
    else tma_load3_h(dst, &mp.d, 0, blockIdx.x * 32, (i - 8) * 4, bar, last_use);
}
__device__ __forceinline__ void side_role(const Maps& mp, const bf16* __restrict__ x0, const bf16* __restrict__ wo, const bf16* __restrict__ w_r) {
    prep_work(x0, &mp.w64, threadIdx.x - 288);
    epi_inputs(0);
    #pragma unroll 1
    for (int L = 0; L < 2; L++) {
        const int t = tid_now() - 288, lane = t & 31, sw = warp_uniform(t >> 5);
        const int c = blockIdx.x, mt = c >> 4, nt = c & 15;
        named_sync(2, 96);
        if (t == 0) mbar_arrive(B_EPI);
        TL(288, L, 5);
        if (L == 0) {
            float ws = 0.f;
            for (int i = t; i < D_ / 8; i += 96) {
                const uint4 v = reinterpret_cast<const uint4*>(w_r)[i];
                ws += ((bf_lo(v.x) + bf_hi(v.x)) + (bf_lo(v.y) + bf_hi(v.y))) + ((bf_lo(v.z) + bf_hi(v.z)) + (bf_lo(v.w) + bf_hi(v.w)));
            }
            ws = warp_sum(ws);
            if (lane == 0) stsf(SB + OFF_M + M_WS + sw * 4, ws);
            if (t >= 94) sts32(SB + OFF_M + M_ORDY + (t - 94) * 4, 0u);
            if (t < 66) sts32(SB + OFF_WR + t * 4, t < 64 ? reinterpret_cast<const uint32_t*>(w_r)[(nt >> 1) * 64 + (t >> 3) * 8 + (t & 1) * 4 + ((t >> 1) & 3)] : 0x3F803F80u);
        }
        __syncwarp();
        if (sw == 0) {
            char* kv = g_kv + (size_t)(nt * 16 + mt) * KV_WIN;
            mbar_wait(B_KV0, L);
            bulk_store(kv, SB, KV_WIN);
            bulk_commit();
            publish(&g_kvc[L][nt * 2][mt]);
            TL(288, L, 6);
            named_sync(N_KV1, 64);
            bulk_store(kv + 8 * KV_WIN, SB + OFF_FE, KV_WIN);
            bulk_commit();
            publish(&g_kvc[L][nt * 2 + 1][mt]);
        }
        if (sw < 2) {
            #pragma unroll 1
            for (int p = 0; p < 2; p++) {
                named_sync(N_OST + 2 * p + sw, p > sw ? 192 : 160);
                TL(p ? -1 : 288, L, 30); TL(p ? 288 : -1, L, 31);
                if (p == 1) mbar_arrive_elect(B_QAF);
                ctr_arrive(&g_oc[L][mt * 2 + sw][p][nt]);
            }
        } else {
            named_sync(N_FW, 64);
            mbar_expect_tx(B_RES, 32768);
            #pragma unroll
            for (int i = 0; i < 4; i++) tma_load_h(SB + OFF_XT + i * 8192, L == 0 ? &mp.x0 : &mp.x, (nt >> 1) * 128 + (i >> 1) * 64, mt * 256 + (nt & 1) * 128 + (i & 1) * 64, B_RES, true);
            if (c < NFC) {
                #pragma unroll 1
                for (int r = 0; r < 4; r++) {
                    __nanosleep(FW_NS);
                    if (r > 0) mbar_wait(B_FW, (r + L) & 1);
                    const uint32_t bar = r < 3 ? B_FW : B_FE;
                    mbar_expect_tx(bar, 3 * 16384);
                    #pragma unroll 1
                    for (int b = 0; b < 3; b++) ffn_load(mp, 9 - 3 * r + b, SB + OFF_FE + b * 16384, bar, r == 3);
                }
            }
        }
        if (sw == 2) {
            l2_prefetch(reinterpret_cast<const char*>(wo) + (size_t)c * 16384, 16384);
            mbar_wait(B_RES, L);
            const uint32_t lr = lds32(SB + OFF_M + M_RIDX) - (mt * 256 + (nt & 1) * 128);
            if (L == 1 && lr < 128u && lane < 16) {
                const uint4 a = ld_relaxed4(g_x2row + (nt >> 1) * 128 + lane * 8), b = ld_relaxed4(g_x2row + (nt >> 1) * 128 + lane * 8 + 4);
                sts128(SB + OFF_XT + (lane >> 3) * 16384 + lr * 128 + (((lane & 7) ^ (lr & 7)) << 4),
                       make_uint4(__byte_perm(a.x, a.y, 0x7632), __byte_perm(a.z, a.w, 0x7632), __byte_perm(b.x, b.y, 0x7632), __byte_perm(b.z, b.w, 0x7632)));
            }
            if (L == 1) {
                #pragma unroll
                for (int i = 0; i < 4; i++) {
                    const float2 r = ln_coef(ld_relaxed4(&g_sums[mt * 256 + (nt & 1) * 128 + i * 32 + lane]));
                    const float a = i * 32 + lane == lr ? 0.f : r.x;
                    sts64f(SB + OFF_LC + (i * 32 + lane) * 8, a, -a * r.y);
                }
            }
            __syncwarp();
            mbar_arrive_elect(B_RES2);
            named_sync(N_OST + 2, 192);
            l2_prefetch(&g_ypart[L][0][0] + c * (NFC * 8), NFC * 32);
            l2_prefetch(&g_acc[L][c * 16][0], 512);
            l2_prefetch(&g_sums[c * 16], 256);
            l2_prefetch(&g_xrow[L][0][0] + c * 64, 256);
            l2_prefetch(&g_tab[L][0][0][0] + c * 2, 32);
            l2_prefetch(c < 32 ? &g_x2row[c * 32] : c < 40 ? &g_kvc[1][(c - 32) * 4][0] : &g_xc[0][0], c < 40 ? 128 : 64);
            l2_prefetch(&g_fix[c * 24], 96);
            uint32_t ready, n = 0;
            do {
                ready = __ballot_sync(0xffffffffu, ld_acquire(&g_oc[L][mt * 2 + (nt & 1)][1][lane & 15]) != 0);
                fence_async_global();
                if (lane == 0) sts_release(SB + OFF_M + M_ORDY + 4 * L, ready & ready >> 1);
            } while (ready != 0xFFFFFFFFu && ++n < SPIN_MAX);
            spin_check(n);
        }
        if (sw < 2) {
            named_sync(N_XST + sw, 160);
            const int row0 = mt * 256 + (nt & 1) * 128 + sw * 64, col0 = (nt >> 1) * 128;
            #pragma unroll 1
            for (int h = 0; h < 8; h++) {
                if (L == 0) bulk_wait_n<XP0>(); else bulk_wait_n<XP1>();
                tma_store(L == 0 ? &mp.xs : &mp.out, SB + OFF_XT + (h & 1) * 16384 + sw * 8192 + (h >> 1) * 2048, col0 + (h & 1) * 64, row0 + (h >> 1) * 16);
                bulk_commit();
            }
            publish(&g_xc[L][mt]);
            TL(288, L, 14);
        }
        if (L == 0) {
            __syncwarp();
            named_sync(N_RT, 128);
            const RouteOut rt = route_out(lds128(SB + OFF_RT + 128));
            if (t == 0) { sts32(SB + OFF_M + M_RIDX, rt.idx); if (c == 0) g_c0 = 0u; }
            epi_inputs(1);
            const float v = ffn_finish<96>(0, rt, t, SB + OFF_RED, 2);
            TL(288, L, 20);
            if (t < 8) st_relaxed(g_x2row + ypos_col(c * 8 + t), not_sent(v));
            routed_qkv(rt.idx);
        }
    }
}

struct EpiIn { float2 c2[4]; float hs; };
template <int HH>
__device__ __forceinline__ EpiIn qkv_epi_in(int t) {
    EpiIn e;
    #pragma unroll
    for (int jj = 0; jj < 4; jj++) e.c2[jj] = lds64f(SB + OFF_CS + (HH * 32 + jj * 8) * 4 + t * 8);
    e.hs = ldsf(SB + OFF_M + M_SC + HH * 4);
    return e;
}
template <int HH, int NEXT>
__device__ __forceinline__ void qkv_epi_head(const float (&acc0)[96], const float (&acc1)[96], const float (&cf)[4], const float (&nm)[4], EpiIn& in, uint32_t dst, int t) {
    const EpiIn e = in;
    #pragma unroll
    for (int i = 0; i < 4; i++) {
        const float* a = (i >> 1) ? acc1 : acc0;
        const float sc = cf[i] * e.hs;
        uint32_t pk[4];
        #pragma unroll
        for (int jj = 0; jj < 4; jj++)
            pk[jj] = pack_f16(fmaf(nm[i], e.c2[jj].x, a[4 * (4 * HH + jj) + 2 * (i & 1)]) * sc, fmaf(nm[i], e.c2[jj].y, a[4 * (4 * HH + jj) + 2 * (i & 1) + 1]) * sc);
        stsm4(dst + (i >> 1) * (HH < 2 ? 4096 : 1024) + (i & 1) * 128, pk[0], pk[1], pk[2], pk[3]);
        if (i == 1 && NEXT >= 0) in = qkv_epi_in<NEXT < 0 ? 0 : NEXT>(t);
    }
}
__device__ __forceinline__ void qkv_patch(int lane, uint32_t mask) {
    const uint4 v = lds128(SB + OFF_FIX + lane * 16);
    const uint32_t dst = lds32(SB + OFF_FIX + 512 + lane * 4);
    __syncwarp();
    asm volatile("{\n.reg .pred q;\nsetp.ne.u32 q, %5, 0;\n@q st.shared.v4.b32 [%0], {%1, %2, %3, %4};\n}"
                 :: "r"(dst), "r"(v.x), "r"(v.y), "r"(v.z), "r"(v.w), "r"((mask >> lane) & 1) : "memory");
}

template <bool INIT>
__device__ __forceinline__ void qkv_step(float (&acc0)[96], float (&acc1)[96], uint32_t st, int wg) {
    const uint64_t da = desc_sw128(SB, 16, 1024) + ((st * Q_STB + wg * 16384) >> 4);
    const uint64_t db = desc_sw128(SB + Q_ABYTES, 8192, 1024) + ((st * Q_STB) >> 4);
    wg_fence();
    if (INIT) { wg_gemm_n192_init(acc0, da, db); wg_gemm_n192_init(acc1, da + (8192 >> 4), db); }
    #pragma unroll
    for (int kk = INIT ? 1 : 0; kk < 4; kk++) {
        wg_gemm_n192(acc0, da + kk * 2, db + kk * 128);
        wg_gemm_n192(acc1, da + (8192 >> 4) + kk * 2, db + kk * 128);
    }
    wg_commit();
}
__device__ __forceinline__ void qkv_phase(int L, int wg) {
    const uint32_t rb = L * 32;
    float acc0[96], acc1[96];
    const bool leader = (tid_now() & 127) == 0;
    mbar_wait(rb + B_QF, 0);
    TL(0, L, 1);
    qkv_step<true>(acc0, acc1, 0, wg);
    uint32_t st = 1, ph = 0;
    #pragma unroll 1
    for (int k = 1; k < 16; k++) {
        mbar_wait(rb + B_QF + 8 * st, ph);
        qkv_step<false>(acc0, acc1, st, wg);
        wg_wait<1>();
        if (leader) mbar_arrive(rb + B_QE + 8 * (st == 0 ? 2 : st - 1));
        if (++st == 3) { st = 0; ph ^= 1; }
    }
    const int tid = tid_now(), lane = tid & 31, w = (tid >> 5) & 3, g = lane >> 2, t = lane & 3;
    mbar_wait(B_EPI, L);
    float cf[4], nm[4];
    #pragma unroll
    for (int i = 0; i < 4; i++) { const float2 r = lds64f(SB + OFF_RC + (wg * 128 + w * 16 + g + (i >> 1) * 64 + (i & 1) * 8) * 8); cf[i] = r.x; nm[i] = -r.y; }
    const int d = (int)lds32(SB + OFF_M + M_RIDX) - (cta_now() >> 4) * 256;
    const bool own = L == 1 && (d >> 7) == wg && ((d >> 4) & 3) == w;
    EpiIn in = qkv_epi_in<2>(t);
    wg_wait<0>();
    TL(0, L, 2);
    TL(128, L, 40);
    named_sync(1, 256);
    const uint32_t dk = SB + wg * 2048 + (lane >> 3) * 4096 + (w * 16 + (lane & 7)) * 16;
    const uint32_t dq = SB + OFF_QA + wg * 8192 + (lane >> 3) * 1024 + (w * 16 + (lane & 7)) * 16;
    qkv_epi_head<2, 4>(acc0, acc1, cf, nm, in, dk, t);
    qkv_epi_head<4, 0>(acc0, acc1, cf, nm, in, dk + 16384, t);
    if (own) qkv_patch(lane, 0x0F0F00u);
    #pragma unroll
    for (int s = 0; s < 3; s++) sts128(SB + s * A_WIN + KV_WIN + tid * 16, make_uint4(0x3C003C00u, 0x3C003C00u, 0x3C003C00u, 0x3C003C00u));
    fence_async_smem();
    __syncwarp();
    mbar_arrive_elect(B_KV0);
    TL(0, L, 4);
    qkv_epi_head<0, 1>(acc0, acc1, cf, nm, in, dq, t);
    qkv_epi_head<1, 3>(acc0, acc1, cf, nm, in, dq + 16384, t);
    qkv_epi_head<3, 5>(acc0, acc1, cf, nm, in, dk + OFF_FE, t);
    qkv_epi_head<5, -1>(acc0, acc1, cf, nm, in, dk + OFF_FE + 16384, t);
    if (own) qkv_patch(lane, 0xF0F0FFu);
    fence_async_smem();
    named_sync(3 + wg, 128);
    TL(0, L, 3);
}

struct Unit {
    uint32_t o[8];
    uint32_t l, bz, sc;
    uint32_t ch[2];
};
template <int H> __device__ __forceinline__ uint32_t hdup(uint32_t v) {
    uint32_t r;
    if (H) asm("{.reg .b16 l, h; mov.b32 {l, h}, %1; mov.b32 %0, {h, h};}" : "=r"(r) : "r"(v));
    else asm("{.reg .b16 l, h; mov.b32 {l, h}, %1; mov.b32 %0, {l, l};}" : "=r"(r) : "r"(v));
    return r;
}
__device__ __forceinline__ uint32_t hmax2(uint32_t a, uint32_t b) { uint32_t r; asm("max.f16x2 %0, %1, %2;" : "=r"(r) : "r"(a), "r"(b)); return r; }
__device__ __forceinline__ uint32_t hadd2(uint32_t a, uint32_t b) { uint32_t r; asm("add.rn.f16x2 %0, %1, %2;" : "=r"(r) : "r"(a), "r"(b)); return r; }
__device__ __forceinline__ uint32_t hsub2(uint32_t a, uint32_t b) { uint32_t r; asm("sub.rn.f16x2 %0, %1, %2;" : "=r"(r) : "r"(a), "r"(b)); return r; }
__device__ __forceinline__ uint32_t hfma2(uint32_t a, uint32_t b, uint32_t c) { uint32_t r; asm("fma.rn.f16x2 %0, %1, %2, %3;" : "=r"(r) : "r"(a), "r"(b), "r"(c)); return r; }
__device__ __forceinline__ uint32_t exp2_h2(uint32_t s, uint32_t bz, uint32_t& ch) {
    uint32_t z, w, d;
    asm("fma.rn.relu.f16x2 %0, %1, %2, %3;" : "=r"(z) : "r"(s), "r"(0x00400040u), "r"(bz));
    asm("lop3.b32 %0, %1, 0x003F003F, %0, 0xC2;" : "+r"(ch) : "r"(z));
    asm("fma.rn.f16x2 %0, %1, %2, %3;" : "=r"(w) : "r"(ch), "r"(0x30A630A6u), "r"(0xACCCACCCu));
    asm("{.reg .b32 n; neg.f16x2 n, %1; fma.rn.relu.f16x2 %0, n, %1, %2;}" : "=r"(d) : "r"(w), "r"(0x00580058u));
    return (z << 4) - d;
}
__device__ __forceinline__ void exp_tile(uint32_t (&p)[32], const uint32_t (&s)[32], Unit& u) {
    #pragma unroll
    for (int i = 0; i < 32; i++) p[i] = exp2_h2(s[i], (i & 1) ? hdup<1>(u.bz) : hdup<0>(u.bz), u.ch[i & 1]);
}
__device__ __forceinline__ void issue_qk(uint32_t (&s)[32], uint64_t dq, uint64_t dk) {
    wg_qk_init(s, dq, dk); wg_qk_acc(s, dq + (2048 >> 4), dk + (8192 >> 4));
    wg_commit();
}
template <bool INIT>
__device__ __forceinline__ void issue_pv(uint32_t (&h)[10], const uint32_t (&p)[32], uint64_t dv) {
    #pragma unroll
    for (int k = 0; k < 8; k++) {
        if (INIT && k == 0) wg_pv_init(h, p[0], p[1], p[2], p[3], dv);
        else wg_pv_acc(h, p[4*k], p[4*k+1], p[4*k+2], p[4*k+3], dv + k * 16);
    }
    wg_commit();
}
__device__ __forceinline__ void unit_init(Unit& u, const uint32_t (&s)[32], uint32_t ok) {
    uint32_t m0 = s[0], m1 = s[1];
    #pragma unroll
    for (int i = 1; i < 16; i++) { m0 = hmax2(m0, s[2 * i]); m1 = hmax2(m1, s[2 * i + 1]); }
    uint32_t m = hmax2(__byte_perm(m0, m1, 0x5410), __byte_perm(m0, m1, 0x7632));
    m = hmax2(m, __shfl_xor_sync(0xffffffffu, m, 1)); m = hmax2(m, __shfl_xor_sync(0xffffffffu, m, 2));
    float f0, f1; h2_unpack(m, f0, f1);
    u.ch[0] = fabsf(f0) < 380.f ? ok : 0u; u.ch[1] = fabsf(f1) < 380.f ? ok : 0u;
    f0 = (63.f - ceilf(f0 * 4.f)) * 9.5367431640625e-07f; f1 = (63.f - ceilf(f1 * 4.f)) * 9.5367431640625e-07f;
    u.bz = pack_f16(f0, f1); u.sc = 0u; u.l = 0u;
    #pragma unroll
    for (int i = 0; i < 8; i++) u.o[i] = 0u;
}
template <bool MORE>
__device__ __forceinline__ void unit_flush(Unit& u, const uint32_t (&h)[10]) {
    u.l = hfma2(u.l, u.sc, __byte_perm(h[8], h[9], 0x5410));
    #pragma unroll
    for (int i = 0; i < 8; i++) u.o[i] = hfma2(u.o[i], (i & 1) ? hdup<1>(u.sc) : hdup<0>(u.sc), h[i]);
    if (MORE) {
        const uint32_t ex = u.l & 0x7C007C00u;
        u.sc = 0x84008400u - ex;
        u.bz = hsub2(hadd2(u.bz, 0x04800480u), ex >> 4);
    }
}
__device__ __forceinline__ char* o_block(int wg, int pass) { const int c = cta_now(); return g_o + (size_t)((((c >> 4) * 2 + wg) * 2 + pass) * 16 + (c & 15)) * 8192; }
__device__ __forceinline__ uint32_t unit_store(const Unit& u, char* dst, float ivs) {
    uint32_t bad = 0;
    float lf[2]; h2_unpack(u.l, lf[0], lf[1]);
    #pragma unroll
    for (int h = 0; h < 2; h++) {
        uint32_t b = __ballot_sync(0xffffffffu, (~u.ch[h] & CH_OK) != 0 || !(lf[h] >= 2.f && lf[h] <= 65504.f));
        b |= b >> 1; b = (b | b >> 2) & 0x11111111u;
        const float inv = ivs * rcp(lf[h]);
        #pragma unroll
        for (int j = 0; j < 4; j++) { float x, y; h2_unpack(u.o[2 * j + h], x, y); *reinterpret_cast<uint32_t*>(dst + j * 1024 + h * 128) = pack_bf16(x * inv, y * inv); }
        bad |= b << h;
    }
    return bad;
}
__device__ __noinline__ void exact_rows(int L, int pass, int wg, uint32_t bad) {
    const int tid = tid_now() & 127, lane = tid & 31, w = tid >> 5, t = lane & 3;
    const int head = (cta_now() & 15) * 2 + pass;
    const uint32_t scr = SB + OFF_PART + wg * 1024;
    if (lane == 0) sts32(scr + w * 4, bad);
    ctr_wait_all(&g_kvc[L][head][lane & 7], 1);
    named_sync(3 + wg, 128);
    const float isc = ldsf(SB + OFF_M + M_ISC + pass * 4), ivs = ldsf(SB + OFF_M + M_IVS + pass * 4);
    const char* kv = g_kv + (size_t)(head * 8 + w * 2) * KV_WIN + t * 4096 + (lane >> 2) * 16;
    #pragma unroll 1
    for (int ww = 0; ww < 4; ww++)
    #pragma unroll 1
    for (uint32_t m = lds32(scr + ww * 4); m; m &= m - 1) {
        const int bit = __ffs(m) - 1;
        const uint32_t ro = (bit & 2) * 2048 + (ww * 16 + (bit & 1) * 8 + (bit >> 2)) * 16;
        const uint4 q = lds128(SB + OFF_QA + pass * 16384 + wg * 8192 + ro + t * 1024);
        float a[9], mx = -INFINITY;
        #pragma unroll
        for (int i = 0; i < 9; i++) a[i] = 0.f;
        #pragma unroll 1
        for (int it = 0; it < 8; it++) {
            uint4 k[8], v[8];
            #pragma unroll
            for (int i = 0; i < 8; i++) {
                const char* p = kv + (it >> 2) * KV_WIN + (it & 3) * 1024 + i * 128;
                k[i] = __ldcg(reinterpret_cast<const uint4*>(p)); v[i] = __ldcg(reinterpret_cast<const uint4*>(p + 16384));
            }
            float s[8], mn = mx;
            #pragma unroll
            for (int i = 0; i < 8; i += 2) {
                float c[4] = {0.f, 0.f, 0.f, 0.f};
                mma_f16(c, k[i].x, k[i + 1].x, k[i].y, k[i + 1].y, q.x, q.y);
                mma_f16(c, k[i].z, k[i + 1].z, k[i].w, k[i + 1].w, q.z, q.w);
                s[i] = c[0]; s[i + 1] = c[2];
                mn = fmaxf(mn, fmaxf(c[0], c[2]));
            }
            const float al = ex2((mx - mn) * isc);
            mx = mn;
            #pragma unroll
            for (int i = 0; i < 9; i++) a[i] *= al;
            #pragma unroll
            for (int i = 0; i < 8; i++) {
                const float p = ex2((s[i] - mx) * isc);
                const uint32_t u[4] = {v[i].x, v[i].y, v[i].z, v[i].w};
                a[8] += p;
                #pragma unroll
                for (int e = 0; e < 4; e++) { float x, y; h2_unpack(u[e], x, y); a[2 * e] = fmaf(p, x, a[2 * e]); a[2 * e + 1] = fmaf(p, y, a[2 * e + 1]); }
            }
        }
        #pragma unroll 1
        for (int o = 4; o < 32; o <<= 1) {
            const float mn = fmaxf(mx, __shfl_xor_sync(0xffffffffu, mx, o)), al = ex2((mx - mn) * isc);
            mx = mn;
            #pragma unroll
            for (int i = 0; i < 9; i++) { a[i] *= al; a[i] += __shfl_xor_sync(0xffffffffu, a[i], o); }
        }
        named_sync(3 + wg, 128);
        const uint32_t mine = scr + 16 + w * 144;
        sts128(mine + t * 32, make_uint4(__float_as_uint(a[0]), __float_as_uint(a[1]), __float_as_uint(a[2]), __float_as_uint(a[3])));
        sts128(mine + t * 32 + 16, make_uint4(__float_as_uint(a[4]), __float_as_uint(a[5]), __float_as_uint(a[6]), __float_as_uint(a[7])));
        sts64f(mine + 128, a[8], mx);
        named_sync(3 + wg, 128);
        float o = 0.f, l = 0.f;
        mx = -INFINITY;
        #pragma unroll 1
        for (int i = 0; i < 4; i++) {
            const float2 e = lds64f(scr + 16 + i * 144 + 128);
            const float mn = fmaxf(mx, e.y), al = ex2((mx - mn) * isc), be = ex2((e.y - mn) * isc);
            mx = mn;
            o = fmaf(o, al, be * ldsf(scr + 16 + i * 144 + lane * 4)); l = fmaf(l, al, be * e.x);
        }
        if (w == 0) *reinterpret_cast<unsigned short*>(o_block(wg, pass) + ro + (lane >> 3) * 1024 + (lane & 7) * 2) = (unsigned short)pack_bf16(o * ivs * rcp(l), 0.f);
    }
}

__device__ __forceinline__ void attention_phase(int L, int wg) {
    const uint32_t rb = L * 32;
    constexpr uint64_t dk0 = desc_plain(SB, 4096, 128), dv0 = desc_plain(SB + 16384, 128, 4096);
    constexpr int T1 = 2048 >> 4;
    uint32_t st = 0, ph = 0;
    #pragma unroll 1
    for (int pass = 0; pass < 2; pass++) {
        const uint64_t dqa = desc_plain(SB + OFF_QA, 1024, 128) + (pass * 4 + wg * 2) * (4096 >> 4), dqc = dqa + (4096 >> 4);
        Unit a, c;
        st = warp_uniform(st); ph = warp_uniform(ph);
        uint32_t SA[32], SC[32], PA[32], PC[32], ha[10], hc[10], bad;
        #pragma unroll
        for (int i = 0; i < 10; i++) hc[i] = 0u;
        #pragma unroll
        for (int i = 0; i < 32; i++) PC[i] = 0u;
        const uint32_t ok = lds32(SB + OFF_M + M_OK + pass * 4);
        mbar_wait(rb + B_AF + 8 * st, ph);
        wg_fence();
        issue_qk(SA, dqa, dk0 + st * (A_WIN >> 4));
        issue_qk(SC, dqc, dk0 + st * (A_WIN >> 4));
        wg_wait<1>();
        unit_init(a, SA, ok);
        exp_tile(PA, SA, a);
        wg_wait<0>();
        unit_init(c, SC, ok);
        uint32_t eb = 0;
        #pragma unroll 1
        for (int s = 0;; s++) {
            const uint64_t dkb = dk0 + st * (A_WIN >> 4), dvb = dv0 + st * (A_WIN >> 4);
            if (__builtin_expect(s == 8 * gridDim.y, 0)) {
                wg_wait<0>();
                bad = 0;
                #pragma unroll
                for (int i = 0; i < 32; i++) bad |= PC[i];
                break;
            }
            wg_fence();
            issue_pv<true>(ha, PA, dvb); issue_qk(SA, dqa, dkb + T1);
            wg_wait<2>();
            if (s > 0) { mbar_arrive_elect(eb); unit_flush<true>(c, hc); }
            exp_tile(PC, SC, c);
            wg_fence();
            issue_pv<true>(hc, PC, dvb); issue_qk(SC, dqc, dkb + T1);
            wg_wait<2>();
            exp_tile(PA, SA, a);
            eb = rb + B_AE + 8 * st;
            if (++st == 3) { st = 0; ph ^= 1; }
            if (s == 7) {
                wg_fence(); issue_pv<false>(ha, PA, dvb + T1);
                wg_wait<1>();
                exp_tile(PC, SC, c);
                wg_fence(); issue_pv<false>(hc, PC, dvb + T1);
                wg_wait<1>();
                const int tid = tid_now();
                const float ivs = ldsf(SB + OFF_M + M_IVS + pass * 4);
                char* dst = o_block(wg, pass) + (tid & 96) * 8 + (tid & 31) * 4;
                unit_flush<false>(a, ha);
                bad = unit_store(a, dst, ivs);
                wg_wait<0>();
                mbar_arrive_elect(eb);
                unit_flush<false>(c, hc);
                bad |= unit_store(c, dst + 4096, ivs) << 2;
                break;
            }
            const uint64_t dkn = dk0 + st * (A_WIN >> 4);
            mbar_wait(rb + B_AF + 8 * st, ph);
            wg_fence();
            issue_pv<false>(ha, PA, dvb + T1); issue_qk(SA, dqa, dkn);
            wg_wait<2>();
            exp_tile(PC, SC, c);
            wg_fence();
            issue_pv<false>(hc, PC, dvb + T1); issue_qk(SC, dqc, dkn);
            wg_wait<2>();
            unit_flush<true>(a, ha);
            exp_tile(PA, SA, a);
        }
        if (__builtin_expect(named_any(bad != 0, 3 + wg), 0)) {
            exact_rows(L, pass, wg, bad);
        }
        named_arrive(N_OST + 2 * pass + wg, pass > wg ? 192 : 160);
        TL(pass ? -1 : 0, L, 8); TL(pass ? 0 : -1, L, 9);
    }
}

#define XS0 0
#define OW0 1
#define OUNR 1
#define GDP 0
#define DDP 1

template <bool INIT>
__device__ __forceinline__ void oproj_step(float (&acc)[64], uint32_t s, int wg) {
    const uint64_t da = desc_plain(SB, 1024, 128) + ((o_stage(s) + wg * 4096) >> 4);
    const uint64_t db = desc_sw128(SB + 16384, 8192, 1024) + (o_stage(s) >> 4);
    wg_fence();
    if (INIT) wg_gemm_n128_init(acc, da, db);
    #pragma unroll
    for (int kk = INIT ? 1 : 0; kk < 4; kk++) wg_gemm_n128(acc, da + (kk >> 1) * 512 + (kk & 1) * 128, db + kk * 128);
    wg_commit();
}
__device__ __forceinline__ void oproj_phase(int L, int wg, bf16* __restrict__ out) {
    const int c = cta_now(), tid = tid_now(), lane = tid & 31, W = tid >> 5, g = lane >> 2, t = lane & 3;
    const int row0 = (c >> 4) * 256 + (c & 1) * 128, col0 = ((c & 15) >> 1) * 128;
    float acc[64];
    mbar_wait(B_OF, 0);
    TL(0, L, 10);
    oproj_step<true>(acc, 0, wg);
    const uint32_t xa = SB + OFF_XT + (W * 16 + ((lane >> 3) & 1) * 8 + (lane & 7)) * 128, xs = (lane >> 4) ^ (lane & 7);
    mbar_wait(B_RES2, L);
    const float2 c0 = lds64f(SB + OFF_LC + (W * 16 + g) * 8), c1 = lds64f(SB + OFF_LC + (W * 16 + g + 8) * 8);
    constexpr int ounr = OUNR;
    #pragma unroll ounr
    for (int k = 1; k < 16; k++) {
        if (OW0) { wg_wait<0>(); if ((tid & 127) == 0) mbar_arrive(B_OE + 8 * ((k - 1) & 3)); }
        mbar_wait(B_OF + 8 * (k & 3), (k >> 2) & 1);
        TL(k == 8 ? 0 : -1, L, 11);
        oproj_step<false>(acc, k & 3, wg);
        if (!OW0) { wg_wait<1>(); if ((tid & 127) == 0) mbar_arrive(B_OE + 8 * ((k - 1) & 3)); }
        if (L == 1 && (k & 1)) {
            const uint32_t a = xa + (k & 8) * 2048 + ((xs ^ (k & 6)) << 4);
            uint32_t v0, v1, v2, v3;
            ldsm4(v0, v1, v2, v3, a);
            stsm4(a, add_ln2(v0, c0.x, c0.y), add_ln2(v1, c1.x, c1.y), add_ln2(v2, c0.x, c0.y), add_ln2(v3, c1.x, c1.y));
        }
    }
    uint32_t x[32];
    const uint32_t wra = SB + OFF_WR + (g == 4 ? t * 8 : 256), wrs = g == 4 ? 32 : 0;
    float2 wb[8];
    #pragma unroll
    for (int ks = 0; ks < 8; ks++) {
        ldsm4(x[4*ks], x[4*ks+1], x[4*ks+2], x[4*ks+3], xa + (ks >> 2) * 16384 + ((xs ^ ((ks & 3) * 2)) << 4));
        wb[ks] = lds64f(wra + ks * wrs);
    }
    wg_wait<0>();
    if ((tid & 127) == 0) mbar_arrive(B_OE + 24);
    TL(0, L, 12);
    {
        float sd[4] = {0.f, 0.f, 0.f, 0.f}, z0[4] = {0.f, 0.f, 0.f, 0.f}, z1[4] = {0.f, 0.f, 0.f, 0.f};
        #pragma unroll
        for (int ks = 0; ks < 8; ks++) {
            #pragma unroll
            for (int i = 0; i < 4; i++) x[4*ks + i] = badd2(x[4*ks + i], pack_bf16(acc[8*ks + 2*i], acc[8*ks + 2*i + 1]));
            mma_bf16(sd, x[4*ks], x[4*ks+1], x[4*ks+2], x[4*ks+3], __float_as_uint(wb[ks].x), __float_as_uint(wb[ks].y));
            mma_bf16(z0, x[4*ks], x[4*ks+1], x[4*ks+2], x[4*ks+3], x[4*ks], x[4*ks+2]);
            mma_bf16(z1, x[4*ks], x[4*ks+1], x[4*ks+2], x[4*ks+3], x[4*ks+1], x[4*ks+3]);
        }
        const float s0 = __shfl_sync(0xffffffffu, (g & 1) ? z0[1] : z0[0], 4 * g + (g >> 1));
        const float s1 = __shfl_sync(0xffffffffu, (g & 1) ? z1[3] : z1[2], 4 * g + (g >> 1));
        double* p = &g_acc[L][row0 + W * 16 + g][t];
        asm volatile("red.relaxed.gpu.global.add.f64 [%0], %1;" :: "l"(p), "d"((double)sel4(t, sd[0], s0, sd[0], 1.f)) : "memory");
        asm volatile("red.relaxed.gpu.global.add.f64 [%0], %1;" :: "l"(p + 32), "d"((double)sel4(t, sd[2], s1, sd[2], 1.f)) : "memory");
    }
    TL(0, L, 13);
    if (L == 0) {
        #pragma unroll
        for (int ks = 0; ks < 8; ks++) stsm4(xa + (ks >> 2) * 16384 + ((xs ^ ((ks & 3) * 2)) << 4), x[4*ks], x[4*ks+1], x[4*ks+2], x[4*ks+3]);
        fence_async_smem();
        if (XS0 == 0) named_arrive(N_XST + wg, 160);
    }
    const bool ffn = c < NFC;
    uint4 fa[32], fd[16];
    const uint32_t ga = SB + W * 2048 + ((lane >> 4) * 8 + (lane & 7)) * 64 + ((((lane >> 3) & 1) ^ ((lane >> 1) & 3)) << 4);
    if (ffn) mbar_wait(B_FE, L);
    #pragma unroll
    for (int i = 0; i < 12; i++) ldsm4t(fa[i].x, fa[i].y, fa[i].z, fa[i].w, (ga ^ ((i & 1) * 32)) + gu_piece(i >> 2) + (i & 2) * 512);
    float2 r0, r1;
    {
        const float ws = ldsf(SB + OFF_M + M_WS) + ldsf(SB + OFF_M + M_WS + 4) + ldsf(SB + OFF_M + M_WS + 8);
        const uint32_t row = row0 + W * 16 + g;
        const bool odd = t & 1, up = t & 2;
        const uint32_t me = row + (odd ? 8 : 0);
        uint4 v;
        uint32_t n = 0;
        do { v = ld_relaxed4(&g_acc[L][me][t & 2]); } while (__any_sync(0xffffffffu, up && v.w != 0x40200000u) && ++n < SPIN_MAX);
        spin_check(n);
        TL(0, L, 46);
        if (XS0 == 1 && L == 0) named_arrive(N_XST + wg, 160);
        const float f0 = (float)__hiloint2double(v.y, v.x), f1 = (float)__hiloint2double(v.w, v.z);
        const float e0 = __shfl_xor_sync(0xffffffffu, f0, 2), e1 = __shfl_xor_sync(0xffffffffu, f1, 2);
        const float a[3] = {up ? e0 : f0, up ? e1 : f1, up ? f0 : e0};
        const uint4 tot = make_uint4(not_sent(a[0]), not_sent(a[1]), 0u, 0u);
        st_relaxed4_if(&g_sums[me], tot, L == 0 && col0 == 0 && t < 2);
        const float2 r = ln_coef(tot), ro = make_float2(__shfl_xor_sync(0xffffffffu, r.x, 1), __shfl_xor_sync(0xffffffffu, r.y, 1));
        r0 = odd ? ro : r; r1 = odd ? r : ro;
        const uint32_t k = min(order_bits(r.x * fmaf(-r.y, ws, a[2])), SENT - 1);
        const uint32_t m = redux_max(k), mrow = redux_min(k == m ? me : 0x7FFFFFFFu);
        if (me == mrow) sts128(SB + OFF_RT + W * 16, make_uint4(k, me, not_sent(r.y), not_sent(r.x)));
    }
    named_sync(1, 256);
    {
        const uint4 e = lds128(SB + OFF_RT + (lane & 7) * 16);
        const uint32_t m = redux_max(e.x), row = redux_min(e.x == m ? e.y : 0x7FFFFFFFu);
        const int lr = row - row0;
        st_relaxed4_if(&g_tab[L][(c & 15) >> 1][row0 >> 7][(lane >> 3) & 1], e, W == ((lr >> 4) ^ 1) && e.y == row && lane < 16);
        if ((lr >> 4) == W) {
            const bool hi = lr & 8;
            uint32_t* dst = &g_xrow[L][row0 >> 7][(col0 & 128) * 2 + (col0 >> 8) * 16 + t * 4];
            #pragma unroll
            for (int i = 0; i < 4; i++)
                st_relaxed4_if(dst + i * 64, make_uint4(min(hi ? x[8*i+1] : x[8*i], SENT - 1), min(hi ? x[8*i+3] : x[8*i+2], SENT - 1),
                               min(hi ? x[8*i+5] : x[8*i+4], SENT - 1), min(hi ? x[8*i+7] : x[8*i+6], SENT - 1)), g == (lr & 7));
        }
        __syncwarp();
    }
    TL(0, L, 15);
    if (XS0 == 2 && L == 0) named_arrive(N_XST + wg, 160);
    if (L == 1) {
        const float b0 = -r0.x * r0.y, b1 = -r1.x * r1.y;
        #pragma unroll
        for (int ks = 0; ks < 8; ks++)
            stsm4(xa + (ks >> 2) * 16384 + ((xs ^ ((ks & 3) * 2)) << 4), add_ln2(x[4*ks], r0.x, b0), add_ln2(x[4*ks+1], r1.x, b1),
                  add_ln2(x[4*ks+2], r0.x, b0), add_ln2(x[4*ks+3], r1.x, b1));
        TL(0, L, 47);
        fence_async_smem();
        named_arrive(N_XST + wg, 160);
    }
    TL(0, L, 45);
    RouteOut rt;
    {
        const uint4* tp = &g_tab[L][(c & 15) >> 1][lane & 15][0];
        uint4 e = ld_relaxed4(tp);
        if (ffn) mbar_wait(B_FL, L);
        #pragma unroll
        for (int i = 12; i < 32; i++) ldsm4t(fa[i].x, fa[i].y, fa[i].z, fa[i].w, (ga ^ ((i & 1) * 32)) + gu_piece(i >> 2) + (i & 2) * 512);
        TL(0, L, 44);
        if (L == 0 && GDP == 0) named_arrive(N_GD, 288);
        uint32_t n = 0;
        while (has_sent(e) && ++n < SPIN_MAX) e = ld_relaxed4(tp);
        spin_check(n);
        __syncwarp();
        e = warp_best(e);
        rt = route_out(e);
        if (W == 7 && L == 0) { sts128(SB + OFF_RT + 128, e); named_arrive(N_RT, 128); }
    }
    TL(0, L, 16);
    uint2 xrow;
    {
        const uint32_t* xp = &g_xrow[L][rt.idx >> 7][W * 64 + (g >> 1) * 16 + t * 4 + (g & 1) * 2];
        xrow = ld_relaxed2(xp);
        if (ffn) mbar_wait(B_FD, L);
        const uint32_t wa = SB + OFF_FD + W * 8192 + ((lane >> 4) * 8 + (lane & 7)) * 128 + ((((lane >> 3) & 1) ^ (lane & 7)) << 4);
        #pragma unroll
        for (int i = 0; i < 16; i++) ldsm4t(fd[i].x, fd[i].y, fd[i].z, fd[i].w, (wa ^ (((i >> 1) & 3) * 32)) + (i >> 3) * 4096 + (i & 1) * 2048);
        if (L == 0 && GDP == 1) named_arrive(N_GD, 288);
        if (L == 0 && DDP == 1) named_arrive(N_DD, 288);
        uint32_t n = 0;
        while ((xrow.x == SENT || xrow.y == SENT) && ++n < SPIN_MAX) xrow = ld_relaxed2(xp);
        spin_check(n);
        __syncwarp();
    }
    if (L == 0 && GDP == 2) named_arrive(N_GD, 288);
    if (L == 0 && DDP == 2) named_arrive(N_DD, 288);
    TL(0, L, 17);
    {
        const float nb = -rt.mean * rt.rstd;
        const uint32_t n0 = pack_bf16(fmaf(bf_lo(xrow.x), rt.rstd, nb), fmaf(bf_hi(xrow.x), rt.rstd, nb));
        const uint32_t n1 = pack_bf16(fmaf(bf_lo(xrow.y), rt.rstd, nb), fmaf(bf_hi(xrow.y), rt.rstd, nb));
        float gu[4][4];
        #pragma unroll
        for (int i = 0; i < 4; i++) { gu[i][0] = 0.f; gu[i][1] = 0.f; gu[i][2] = 0.f; gu[i][3] = 0.f; }
        #pragma unroll
        for (int ks = 0; ks < 8; ks++) {
            const uint32_t b0 = __shfl_sync(0xffffffffu, n0, 4 * ks + t), b1 = __shfl_sync(0xffffffffu, n1, 4 * ks + t);
            #pragma unroll
            for (int i = 0; i < 4; i++) {
                const uint4& a = fa[(ks >> 1) * 8 + (i >> 1) * 4 + (ks & 1) * 2 + (i & 1)];
                mma_bf16(gu[i], a.x, a.y, a.z, a.w, b0, b1);
            }
        }
        stsf(SB + OFF_PART + (W * 64 + t * 16 + g) * 4, sel4(t, gu[0][0], gu[1][0], gu[2][0], gu[3][0]));
        stsf(SB + OFF_PART + (W * 64 + t * 16 + g + 8) * 4, sel4(t, gu[0][2], gu[1][2], gu[2][2], gu[3][2]));
    }
    named_sync(1, 256);
    TL(0, L, 18);
    {
        float gp[8], up[8];
        #pragma unroll
        for (int i = 0; i < 8; i++) gp[i] = ldsf(SB + OFF_PART + (i * 64 + lane) * 4);
        #pragma unroll
        for (int i = 0; i < 8; i++) up[i] = ldsf(SB + OFF_PART + (i * 64 + 32 + lane) * 4);
        const float gv = bf_round(((gp[0] + gp[1]) + (gp[2] + gp[3])) + ((gp[4] + gp[5]) + (gp[6] + gp[7])));
        const float uv = bf_round(((up[0] + up[1]) + (up[2] + up[3])) + ((up[4] + up[5]) + (up[6] + up[7])));
        const float hv = bf_round(gv * rcp(1.f + ex2(gv * -1.4426950408889634f))) * uv;
        const uint32_t hp = pack_bf16(hv, __shfl_down_sync(0xffffffffu, hv, 1));
        uint32_t hb[4];
        #pragma unroll
        for (int i = 0; i < 4; i++) hb[i] = __shfl_sync(0xffffffffu, hp, 8 * i + 2 * t);
        float y[8][4];
        #pragma unroll
        for (int mb = 0; mb < 8; mb++) {
            y[mb][0] = 0.f; y[mb][1] = 0.f; y[mb][2] = 0.f; y[mb][3] = 0.f;
            #pragma unroll
            for (int ks = 0; ks < 2; ks++) mma_bf16(y[mb], fd[2*mb + ks].x, fd[2*mb + ks].y, fd[2*mb + ks].z, fd[2*mb + ks].w, hb[2 * ks], hb[2 * ks + 1]);
        }
        st_relaxed4_if(&g_ypart[L][min(c, NFC - 1)][tid * 4], make_uint4(not_sent(sel4(t, y[0][0], y[2][0], y[4][0], y[6][0])), not_sent(sel4(t, y[0][2], y[2][2], y[4][2], y[6][2])),
                       not_sent(sel4(t, y[1][0], y[3][0], y[5][0], y[7][0])), not_sent(sel4(t, y[1][2], y[3][2], y[5][2], y[7][2]))), ffn);
    }
    if (L == 0 && DDP == 3) named_arrive(N_DD, 288);
    TL(0, L, 19);
    if (L == 1) {
        if (W == 7) ctr_wait(&g_xc[1][rt.idx >> 8], 32);
        unsigned short* dst = reinterpret_cast<unsigned short*>(out) + (size_t)rt.idx * D_ + ypos_col(c * 8 + (tid & 7));
        asm volatile("" : "+l"(dst));
        const float v = ffn_finish<256>(1, rt, tid, SB + OFF_FE, 1);
        if (tid < 8) asm volatile("st.global.u16 [%0], %1;" :: "l"(dst), "h"((unsigned short)(__float_as_uint(v) >> 16)) : "memory");
        TL(0, L, 20);
    }
}

#define FW0 9
#define RK0 7
#define BAL 1500
#define KW1 4
static_assert(FW0 >= 8 && KW1 >= 3 && KW1 < 7, "buffer reuse");
__device__ __forceinline__ void qkv_fill(const CUtensorMap* tx, const CUtensorMap* tw, uint32_t bar, int st, int k) {
    const uint32_t sa = SB + st * Q_STB;
    mbar_expect_tx(bar, Q_STB);
    tma_load(sa, tx, k * 64, (blockIdx.x >> 4) * 256, bar);
    tma_load3(sa + Q_ABYTES, tw, (blockIdx.x & 15) * 64, k * 64, 0, bar);
}
__device__ __forceinline__ void oproj_fill(const Maps& mp, const char* osrc, int s, int par, int pair, int L, int k) {
    const uint32_t fb = B_OF + 8 * s, sa = SB + o_stage(s);
    mbar_expect_tx(fb, 32768);
    bulk_load(sa, osrc + (par * 16 + pair) * 8192, 16384, fb);
    tma_load5(sa + 16384, &mp.wo, 0, 0, par, pair, blockIdx.x & 14, fb);
}
__device__ __forceinline__ void producer_role(const Maps& mp) {
    const int c = blockIdx.x, mt = c >> 4, nt = c & 15, lane = threadIdx.x & 31;
    #pragma unroll 1
    for (int i = 2; i < 13; i++) tm_prefetch(&mp.xa0 + i);
    #pragma unroll 1
    for (int L = 0; L < 2; L++) {
        const uint32_t rb = L * 32;
        uint32_t st = 0, ph = L;
        #pragma unroll 1
        for (int k = L == 0 ? 3 : 0; k < 16; k++) {
            if (k == 0) { ctr_wait_all(&g_xc[0][mt], 32); fence_async_global(); named_sync(N_GD, 288); }
            if (k == 1) named_sync(N_DD, 288);
            mbar_wait(rb + B_QE + 8 * st, ph);
            TL(k == 3 ? 256 : -1, L, 28);
            qkv_fill(L == 0 ? &mp.xa0 : &mp.xa, &mp.wqkv, rb + B_QF + 8 * st, st, k);
            if (L == 1 && k >= RK0 && k < RK0 + 4) {
                if (k == RK0) mbar_expect_tx(B_SW, 4 * 12288);
                tma_load(SB + OFF_SIDE + (k - RK0) * 12288, &mp.r, c * 24, (k - RK0) * 256, B_SW);
            }
            if (++st == 3) { st = 0; ph ^= 1; }
        }
        mbar_wait(B_KV0, L);
        mbar_arrive_elect(rb + B_AF);
        TL(256, L, 29);
        st = 1; ph = 1;
        #pragma unroll 1
        for (int w = 1; w < 16; w++) {
            const int win = nt * 16 + (w & 8) + ((mt + w) & 7);
            if (w <= 3 || w == 8) {
                ctr_wait_all(&g_kvc[L][0][0] + (w < 3 ? win : (win & ~7) + (lane & 7)), 1);
                fence_async_global();
            }
            TL(w == 1 ? 256 : -1, L, 7);
            mbar_wait(rb + B_AE + 8 * st, ph);
            mbar_expect_tx(rb + B_AF + 8 * st, KV_WIN);
            bulk_load(SB + st * A_WIN, g_kv + (size_t)win * KV_WIN, KV_WIN, rb + B_AF + 8 * st);
            if (w == KW1 || w == FW0) named_arrive(w == FW0 ? N_FW : N_KV1, 64);
            if (++st == 3) { st = 0; ph ^= 1; }
        }
        ctr_wait_all(&g_oc[L][mt * 2 + (nt & 1)][0][lane & 15], 1);
        fence_async_global();
        const char* osrc = g_o + (size_t)(mt * 2 + (nt & 1)) * 32 * 8192;
        #pragma unroll
        for (int k = 0; k < 4; k++) {
            mbar_wait(k < 2 ? rb + B_AE + 8 + 8 * k : k == 2 ? rb + B_AE : B_QAF, k < 2 ? 0 : k == 2 ? 1 : L);
            oproj_fill(mp, osrc, k, 0, 2 * k, L, k);
        }
        uint32_t ready = 0xFFFFu;
        #pragma unroll 1
        for (int k4 = 1; k4 < 4; k4++) {
            #pragma unroll
            for (int s = 0; s < 4; s++) {
                const int p = k4 * 8 + 2 * s;
                if (!((ready >> p) & 1)) {
                    ready = smem_wait_any(SB + OFF_M + M_ORDY + 4 * L, 1u << p);
                    fence_async_global();
                }
                mbar_wait(B_OE + 8 * s, (k4 - 1) & 1);
                oproj_fill(mp, osrc, s, p >> 4, p & 15, L, k4 * 4 + s);
            }
        }
        if (c < NFC) {
            mbar_expect_tx(B_FL, 5 * 16384);
            mbar_expect_tx(B_FD, 4 * 16384);
            #pragma unroll 1
            for (int i = 3; i < 12; i++) {
                mbar_wait(B_OE + (i < 5 ? 0 : i == 5 ? 8 : i < 9 ? 16 : 24), 1);
                TL(i == 9 ? 256 : -1, L, 32);
                ffn_load(mp, i, SB + (i < 8 ? gu_piece(i) : OFF_FD + (i - 8) * 16384), i < 8 ? B_FL : B_FD, true);
            }
        }
    }
}

__global__ void __launch_bounds__(384, 1) k_all(const bf16* __restrict__ x0, const bf16* __restrict__ wo, const bf16* __restrict__ w_r, bf16* __restrict__ out,
                                                const __grid_constant__ Maps mp) {
    extern __shared__ __align__(1024) char smem[];
    if (smem_u32(smem) != SB) __trap();
    const int warp = warp_uniform(threadIdx.x >> 5), wg = warp >> 2;
    TL(0, 0, 0);
    {
        const int grp = warp >= 8 ? warp - 8 : warp + 4;
        #pragma unroll
        for (int i = 0; i < 4; i++) mbar_init(BB + grp * 32 + i * 8, grp < 7 ? 1 : grp < 10 ? 2 : 8);
        fence_mbar_init();
    }
    if (warp == 8) {
        #pragma unroll 1
        for (int s = 0; s < 3; s++) qkv_fill(&mp.xa0, &mp.wqkv, B_QF + 8 * s, s, s);
    }
    __syncthreads();
    if (wg == 2) {
        reg_dec<40>();
        if (warp == 8) producer_role(mp);
        else side_role(mp, x0, wo, w_r);
        if (gridDim.y == 2) {
            uint32_t v = threadIdx.x;
            #pragma unroll
            for (int i = 0; i < BAL; i++) asm volatile("fma.rn.f16x2 %0, %0, %0, %0;" : "+r"(v));
            sts32(SB, v);
        }
    } else {
        reg_inc<232>();
        #pragma unroll 1
        for (int L = 0; L < 2; L++) {
            qkv_phase(L, wg);
            attention_phase(L, wg);
            oproj_phase(L, wg, out);
        }
    }
}

typedef CUresult (*EncodeFn)(CUtensorMap*, CUtensorMapDataType, cuuint32_t, void*, const cuuint64_t*, const cuuint64_t*, const cuuint32_t*,
                             const cuuint32_t*, CUtensorMapInterleave, CUtensorMapSwizzle, CUtensorMapL2promotion, CUtensorMapFloatOOBfill);

void make_map(EncodeFn enc, CUtensorMap* tm, const void* ptr, int rank, const cuuint64_t* dims, const cuuint64_t* strides, const cuuint32_t* box, CUtensorMapSwizzle sw) {
    const cuuint32_t es[5] = {1, 1, 1, 1, 1};
    enc(tm, CU_TENSOR_MAP_DATA_TYPE_BFLOAT16, rank, const_cast<void*>(ptr), dims, strides, box, es, CU_TENSOR_MAP_INTERLEAVE_NONE, sw,
        box[0] == 64 ? CU_TENSOR_MAP_L2_PROMOTION_L2_128B : CU_TENSOR_MAP_L2_PROMOTION_NONE, CU_TENSOR_MAP_FLOAT_OOB_FILL_NONE);
}
void make_map2(EncodeFn enc, CUtensorMap* tm, const void* ptr, uint64_t cols, uint64_t rows, uint32_t bc, uint32_t br, CUtensorMapSwizzle sw) {
    const cuuint64_t dims[2] = {cols, rows}, strides[1] = {cols * 2};
    const cuuint32_t box[2] = {bc, br};
    make_map(enc, tm, ptr, 2, dims, strides, box, sw);
}

}

extern "C" void kernel_launch(void* const* d_in, const int* in_sizes, int n_in, void* d_out, int out_size) {
    const bf16* x0 = (const bf16*)d_in[0];
    const bf16* wqkv = (const bf16*)d_in[1];
    const bf16* wo = (const bf16*)d_in[2];
    const bf16* w_r = (const bf16*)d_in[4];
    const bf16* w_gate = (const bf16*)d_in[5];
    const bf16* w_up = (const bf16*)d_in[6];
    const bf16* w_down = (const bf16*)d_in[7];

    EncodeFn enc = nullptr;
    cudaDriverEntryPointQueryResult qr;
    cudaGetDriverEntryPoint("cuTensorMapEncodeTiled", (void**)&enc, cudaEnableDefault, &qr);
    void* p_x;
    cudaGetSymbolAddress(&p_x, g_x);
    Maps mp;
    const CUtensorMapSwizzle S128 = CU_TENSOR_MAP_SWIZZLE_128B;
    make_map2(enc, &mp.x0, x0, D_, S_, 64, 64, S128);
    make_map2(enc, &mp.x, p_x, D_, S_, 64, 64, S128);
    make_map2(enc, &mp.out, d_out, D_, S_, 64, 16, S128);
    make_map2(enc, &mp.xs, p_x, D_, S_, 64, 16, S128);
    make_map2(enc, &mp.xa0, x0, D_, S_, 64, 256, S128);
    make_map2(enc, &mp.xa, p_x, D_, S_, 64, 256, S128);
    make_map2(enc, &mp.w64, wqkv, 3 * D_, D_, 64, 64, S128);
    {
        const cuuint64_t dims[3] = {D_, D_, 3}, strides[2] = {3 * D_ * 2, D_ * 2};
        const cuuint32_t box[3] = {64, 64, 3};
        make_map(enc, &mp.wqkv, wqkv, 3, dims, strides, box, S128);
    }
    make_map2(enc, &mp.r, wqkv, 3 * D_, D_, 24, 256, CU_TENSOR_MAP_SWIZZLE_NONE);
    make_map2(enc, &mp.g, w_gate, FF, D_, 32, 256, CU_TENSOR_MAP_SWIZZLE_64B);
    make_map2(enc, &mp.u, w_up, FF, D_, 32, 256, CU_TENSOR_MAP_SWIZZLE_64B);
    {
        const cuuint64_t dims[5] = {64, 32, 2, 16, 16}, strides[4] = {D_ * 2, 32 * D_ * 2, 64 * D_ * 2, 128};
        const cuuint32_t box[5] = {64, 32, 1, 2, 2};
        make_map(enc, &mp.wo, wo, 5, dims, strides, box, S128);
    }
    {
        const cuuint64_t dims[3] = {64, FF, 16}, strides[2] = {D_ * 2, 128};
        const cuuint32_t box[3] = {64, 32, 4};
        make_map(enc, &mp.d, w_down, 3, dims, strides, box, S128);
    }
    cudaFuncSetAttribute(k_all, cudaFuncAttributeMaxDynamicSharedMemorySize, K_SMEM);
    k_all<<<128, 384, K_SMEM, cudaStreamPerThread>>>(x0, wo, w_r, (bf16*)d_out, mp);
}
```

```cpp
#include <cuda_runtime.h>
#include <cuda_bf16.h>
#include <cuda_fp16.h>
#include <cuda.h>
#include <cudaTypedefs.h>
#include <stdint.h>

namespace {

typedef __nv_bfloat16 bf16;

constexpr int S_ = 2048, D_ = 1024, NH = 32, FF = 3584, NFC = FF / 32;
constexpr float LN_EPS = 1e-5f;
constexpr float QSCALE = 0.17677669529663687f * 1.4426950408889634f;
constexpr uint32_t SENT = 0xFFFFFFFFu;

constexpr int KV_WIN = 32768;
__device__ __align__(1024) char g_kv[NH * 8 * KV_WIN];
__device__ __align__(1024) char g_o[32 * 2 * 16 * 4096];
__device__ __align__(1024) bf16 g_x[S_ * D_];
__device__ float g_csum[8 * 3 * D_];
__device__ float g_wsq[8 * 96];
__device__ float2 g_rs0[S_];
__device__ __align__(128) double g_acc[2][S_][4];
__device__ __align__(128) uint4 g_sums[S_];
__device__ __align__(128) uint32_t g_ypart[2][NFC][D_];
__device__ __align__(128) uint4 g_tab[2][8][16][2];
__device__ __align__(128) uint32_t g_xrow[2][16][D_ / 2];
__device__ __align__(128) uint32_t g_x2row[D_];
__device__ __align__(128) uint32_t g_fix[3 * D_];
__device__ uint32_t g_c0;
__device__ __align__(128) uint32_t g_kvc[2][NH][8];
__device__ __align__(128) uint32_t g_oc[2][16][2][16];
__device__ __align__(128) uint32_t g_xc[2][8];
struct RouteOut { int idx; float r; float mean; float rstd; };

constexpr uint32_t SB = 1024;

__device__ __forceinline__ uint32_t smem_u32(const void* p) { return (uint32_t)__cvta_generic_to_shared(p); }
__device__ __forceinline__ void mbar_arrive(uint32_t bar) { asm volatile("mbarrier.arrive.shared::cta.b64 _, [%0];" :: "r"(bar) : "memory"); }
__device__ __forceinline__ void mbar_wait(uint32_t bar, uint32_t parity) {
    asm volatile("{\n.reg .pred p;\n.reg .u32 n;\nmov.u32 n, 0;\n"
                 "LAB_WAIT:\nmbarrier.try_wait.parity.shared::cta.b64 p, [%0], %1, 2000;\n@p bra LAB_DONE;\n"
                 "add.u32 n, n, 1;\nsetp.lt.u32 p, n, 0x200000;\n@p bra LAB_WAIT;\ntrap;\nLAB_DONE:\n}" :: "r"(bar), "r"(parity) : "memory");
}
__device__ __forceinline__ void mbar_arrive_elect(uint32_t bar) {
    asm volatile("{\n.reg .pred p;\nelect.sync _|p, 0xffffffff;\n@p mbarrier.arrive.shared::cta.b64 _, [%0];\n}" :: "r"(bar) : "memory");
}
__device__ __forceinline__ int tid_now() { int v; asm volatile("mov.u32 %0, %%tid.x;" : "=r"(v)); return v; }
__device__ __forceinline__ int cta_now() { int v; asm volatile("mov.u32 %0, %%ctaid.x;" : "=r"(v)); return v; }
__device__ __forceinline__ int warp_uniform(int v) { return __shfl_sync(0xffffffffu, v, 0); }
__device__ __forceinline__ void fence_mbar_init() { asm volatile("fence.mbarrier_init.release.cluster;" ::: "memory"); }
__device__ __forceinline__ void fence_async_smem() { asm volatile("fence.proxy.async.shared::cta;" ::: "memory"); }
__device__ __forceinline__ void fence_async_global() { asm volatile("fence.proxy.async.global;" ::: "memory"); }
__device__ __forceinline__ void named_sync(int id, int n) { asm volatile("bar.sync %0, %1;" :: "r"(id), "r"(n) : "memory"); }
__device__ __forceinline__ void named_arrive(int id, int n) { asm volatile("bar.arrive %0, %1;" :: "r"(id), "r"(n) : "memory"); }
__device__ __forceinline__ bool named_any(bool p, int id) {
    uint32_t r;
    asm volatile("{\n.reg .pred a, b;\nsetp.ne.u32 a, %1, 0;\nbarrier.cta.red.or.pred b, %2, 128, a;\nselp.u32 %0, 1, 0, b;\n}" : "=r"(r) : "r"((uint32_t)p), "r"(id) : "memory");
    return r != 0;
}
#define ELECT(op) "{\n.reg .pred e;\nelect.sync _|e, 0xffffffff;\n@e " op "\n}"
__device__ __forceinline__ void mbar_init(uint32_t bar, int cnt) { asm volatile(ELECT("mbarrier.init.shared::cta.b64 [%0], %1;") :: "r"(bar), "r"(cnt) : "memory"); }
__device__ __forceinline__ void mbar_expect_tx(uint32_t bar, uint32_t bytes) { asm volatile(ELECT("mbarrier.arrive.expect_tx.shared::cta.b64 _, [%0], %1;") :: "r"(bar), "r"(bytes) : "memory"); }
__device__ __forceinline__ void bulk_load(uint32_t dst, const void* src, uint32_t bytes, uint32_t bar) {
    asm volatile(ELECT("cp.async.bulk.shared::cluster.global.mbarrier::complete_tx::bytes [%0], [%1], %2, [%3];") :: "r"(dst), "l"(src), "r"(bytes), "r"(bar) : "memory");
}
__device__ __forceinline__ void bulk_store(void* dst, uint32_t src, uint32_t bytes) {
    asm volatile(ELECT("cp.async.bulk.global.shared::cta.bulk_group [%0], [%1], %2;") :: "l"(dst), "r"(src), "r"(bytes) : "memory");
}
__device__ __forceinline__ void bulk_commit() { asm volatile("cp.async.bulk.commit_group;" ::: "memory"); }
__device__ __forceinline__ void bulk_wait() { asm volatile("cp.async.bulk.wait_group 0;" ::: "memory"); }
template <int N> __device__ __forceinline__ void bulk_wait_n() { asm volatile("cp.async.bulk.wait_group %0;" :: "n"(N) : "memory"); }
__device__ __forceinline__ void bulk_wait_read() { asm volatile("cp.async.bulk.wait_group.read 0;" ::: "memory"); }
__device__ __forceinline__ void l2_prefetch(const void* src, uint32_t bytes) {
    asm volatile(ELECT("cp.async.bulk.prefetch.L2.global [%0], %1;") :: "l"(src), "r"(bytes) : "memory");
}
__device__ __forceinline__ void tma_load(uint32_t dst, const CUtensorMap* tm, int c0, int c1, uint32_t bar) {
    asm volatile(ELECT("cp.async.bulk.tensor.2d.shared::cluster.global.mbarrier::complete_tx::bytes [%0], [%1, {%3, %4}], [%2];")
                 :: "r"(dst), "l"(tm), "r"(bar), "r"(c0), "r"(c1) : "memory");
}
__device__ __forceinline__ void tma_load3(uint32_t dst, const CUtensorMap* tm, int c0, int c1, int c2, uint32_t bar) {
    asm volatile(ELECT("cp.async.bulk.tensor.3d.shared::cluster.global.mbarrier::complete_tx::bytes [%0], [%1, {%3, %4, %5}], [%2];")
                 :: "r"(dst), "l"(tm), "r"(bar), "r"(c0), "r"(c1), "r"(c2) : "memory");
}
__device__ __forceinline__ uint64_t evict_first() { uint64_t a; asm("createpolicy.fractional.L2::evict_first.b64 %0, 1.0;" : "=l"(a)); return a; }
__device__ __forceinline__ void tma_load_h(uint32_t dst, const CUtensorMap* tm, int c0, int c1, uint32_t bar, bool ef) {
    if (!ef) tma_load(dst, tm, c0, c1, bar);
    else asm volatile(ELECT("cp.async.bulk.tensor.2d.shared::cluster.global.mbarrier::complete_tx::bytes.L2::cache_hint [%0], [%1, {%3, %4}], [%2], %5;")
                      :: "r"(dst), "l"(tm), "r"(bar), "r"(c0), "r"(c1), "l"(evict_first()) : "memory");
}
__device__ __forceinline__ void tma_load3_h(uint32_t dst, const CUtensorMap* tm, int c0, int c1, int c2, uint32_t bar, bool ef) {
    if (!ef) tma_load3(dst, tm, c0, c1, c2, bar);
    else asm volatile(ELECT("cp.async.bulk.tensor.3d.shared::cluster.global.mbarrier::complete_tx::bytes.L2::cache_hint [%0], [%1, {%3, %4, %5}], [%2], %6;")
                      :: "r"(dst), "l"(tm), "r"(bar), "r"(c0), "r"(c1), "r"(c2), "l"(evict_first()) : "memory");
}
__device__ __forceinline__ void tma_load5(uint32_t dst, const CUtensorMap* tm, int c0, int c1, int c2, int c3, int c4, uint32_t bar) {
    asm volatile(ELECT("cp.async.bulk.tensor.5d.shared::cluster.global.mbarrier::complete_tx::bytes [%0], [%1, {%3, %4, %5, %6, %7}], [%2];")
                 :: "r"(dst), "l"(tm), "r"(bar), "r"(c0), "r"(c1), "r"(c2), "r"(c3), "r"(c4) : "memory");
}
__device__ __forceinline__ void tma_store(const CUtensorMap* tm, uint32_t src, int c0, int c1) {
    asm volatile(ELECT("cp.async.bulk.tensor.2d.global.shared::cta.bulk_group [%0, {%2, %3}], [%1];") :: "l"(tm), "r"(src), "r"(c0), "r"(c1) : "memory");
}
__device__ __forceinline__ void tm_prefetch(const CUtensorMap* tm) { asm volatile(ELECT("prefetch.tensormap [%0];") :: "l"(tm) : "memory"); }
__device__ __forceinline__ uint32_t lds32(uint32_t a) { uint32_t v; asm volatile("ld.shared.b32 %0, [%1];" : "=r"(v) : "r"(a) : "memory"); return v; }
__device__ __forceinline__ float ldsf(uint32_t a) { return __uint_as_float(lds32(a)); }
__device__ __forceinline__ float2 lds64f(uint32_t a) { float2 v; asm volatile("ld.shared.v2.f32 {%0, %1}, [%2];" : "=f"(v.x), "=f"(v.y) : "r"(a) : "memory"); return v; }
__device__ __forceinline__ uint4 lds128(uint32_t a) { uint4 v; asm volatile("ld.shared.v4.b32 {%0, %1, %2, %3}, [%4];" : "=r"(v.x), "=r"(v.y), "=r"(v.z), "=r"(v.w) : "r"(a) : "memory"); return v; }
__device__ __forceinline__ void sts32(uint32_t a, uint32_t v) { asm volatile("st.shared.b32 [%0], %1;" :: "r"(a), "r"(v) : "memory"); }
__device__ __forceinline__ void stsf(uint32_t a, float v) { sts32(a, __float_as_uint(v)); }
__device__ __forceinline__ void sts64f(uint32_t a, float x, float y) { asm volatile("st.shared.v2.f32 [%0], {%1, %2};" :: "r"(a), "f"(x), "f"(y) : "memory"); }
__device__ __forceinline__ void sts128(uint32_t a, const uint4& v) { asm volatile("st.shared.v4.b32 [%0], {%1, %2, %3, %4};" :: "r"(a), "r"(v.x), "r"(v.y), "r"(v.z), "r"(v.w) : "memory"); }
__device__ __forceinline__ void stsm4(uint32_t a, uint32_t x, uint32_t y, uint32_t z, uint32_t w) {
    asm volatile("stmatrix.sync.aligned.m8n8.x4.shared.b16 [%0], {%1, %2, %3, %4};" :: "r"(a), "r"(x), "r"(y), "r"(z), "r"(w) : "memory");
}
__device__ __forceinline__ void ldsm4(uint32_t& a0, uint32_t& a1, uint32_t& a2, uint32_t& a3, uint32_t addr) {
    asm volatile("ldmatrix.sync.aligned.m8n8.x4.shared.b16 {%0,%1,%2,%3}, [%4];" : "=r"(a0), "=r"(a1), "=r"(a2), "=r"(a3) : "r"(addr) : "memory");
}
__device__ __forceinline__ void ldsm4t(uint32_t& a0, uint32_t& a1, uint32_t& a2, uint32_t& a3, uint32_t addr) {
    asm volatile("ldmatrix.sync.aligned.m8n8.x4.trans.shared.b16 {%0,%1,%2,%3}, [%4];" : "=r"(a0), "=r"(a1), "=r"(a2), "=r"(a3) : "r"(addr) : "memory");
}
__device__ __forceinline__ void mma_bf16(float (&c)[4], uint32_t a0, uint32_t a1, uint32_t a2, uint32_t a3, uint32_t b0, uint32_t b1) {
    asm("mma.sync.aligned.m16n8k16.row.col.f32.bf16.bf16.f32 {%0,%1,%2,%3}, {%4,%5,%6,%7}, {%8,%9}, {%0,%1,%2,%3};"
        : "+f"(c[0]), "+f"(c[1]), "+f"(c[2]), "+f"(c[3]) : "r"(a0), "r"(a1), "r"(a2), "r"(a3), "r"(b0), "r"(b1));
}
__device__ __forceinline__ void mma_f16(float (&c)[4], uint32_t a0, uint32_t a1, uint32_t a2, uint32_t a3, uint32_t b0, uint32_t b1) {
    asm("mma.sync.aligned.m16n8k16.row.col.f32.f16.f16.f32 {%0,%1,%2,%3}, {%4,%5,%6,%7}, {%8,%9}, {%0,%1,%2,%3};"
        : "+f"(c[0]), "+f"(c[1]), "+f"(c[2]), "+f"(c[3]) : "r"(a0), "r"(a1), "r"(a2), "r"(a3), "r"(b0), "r"(b1));
}
__device__ __forceinline__ uint32_t ld_acquire(const void* p) { uint32_t v; asm volatile("ld.acquire.gpu.global.u32 %0, [%1];" : "=r"(v) : "l"(p) : "memory"); return v; }
__device__ __forceinline__ void sts_release(uint32_t a, uint32_t v) { asm volatile("st.release.cta.shared.u32 [%0], %1;" :: "r"(a), "r"(v) : "memory"); }
__device__ __forceinline__ uint32_t ld_relaxed(const void* p) { uint32_t v; asm volatile("ld.relaxed.gpu.global.u32 %0, [%1];" : "=r"(v) : "l"(p) : "memory"); return v; }
__device__ __forceinline__ uint4 ld_relaxed4(const void* p) {
    uint4 v; asm volatile("ld.relaxed.gpu.global.v4.b32 {%0, %1, %2, %3}, [%4];" : "=r"(v.x), "=r"(v.y), "=r"(v.z), "=r"(v.w) : "l"(p) : "memory"); return v;
}
__device__ __forceinline__ uint2 ld_relaxed2(const void* p) { uint2 v; asm volatile("ld.relaxed.gpu.global.v2.b32 {%0, %1}, [%2];" : "=r"(v.x), "=r"(v.y) : "l"(p) : "memory"); return v; }
__device__ __forceinline__ void st_relaxed(void* p, uint32_t v) { asm volatile("st.relaxed.gpu.global.u32 [%0], %1;" :: "l"(p), "r"(v) : "memory"); }
__device__ __forceinline__ void st_relaxed4_if(void* p, const uint4& v, bool on) {
    asm volatile("{\n.reg .pred q;\nsetp.ne.u32 q, %5, 0;\n@q st.relaxed.gpu.global.v4.b32 [%0], {%1, %2, %3, %4};\n}"
                 :: "l"(p), "r"(v.x), "r"(v.y), "r"(v.z), "r"(v.w), "r"((uint32_t)on) : "memory");
}
__device__ __forceinline__ uint32_t not_sent(float v) { const uint32_t u = __float_as_uint(v); return u == SENT ? 0x7FFFFFFFu : u; }
__device__ __forceinline__ bool has_sent(const uint4& v) { return max(max(v.x, v.y), max(v.z, v.w)) == SENT; }
constexpr uint32_t SPIN_MAX = 1u << 22;
__device__ __forceinline__ void spin_check(uint32_t n) { asm volatile("{\n.reg .pred p;\nsetp.ge.u32 p, %0, %1;\n@p st.global.u32 [%2], %0;\n}" :: "r"(n), "n"(SPIN_MAX), "l"(0ull) : "memory"); }
__device__ __forceinline__ void ctr_arrive(uint32_t* c, uint32_t n = 1) { asm volatile(ELECT("red.release.gpu.global.add.u32 [%0], %1;") :: "l"(c), "r"(n) : "memory"); }
__device__ __forceinline__ void ctr_wait(const uint32_t* c, uint32_t target) {
    asm volatile("{\n.reg .pred p;\n.reg .u32 n, v;\nmov.u32 n, 0;\n"
                 "LAB_WAIT:\nld.acquire.gpu.global.u32 v, [%0];\nsetp.ge.u32 p, v, %1;\n@p bra LAB_DONE;\n"
                 "add.u32 n, n, 1;\nsetp.lt.u32 p, n, 0x400000;\n@p bra LAB_WAIT;\ntrap;\nLAB_DONE:\n}" :: "l"(c), "r"(target) : "memory");
}
__device__ __forceinline__ void ctr_wait_all(const uint32_t* c, uint32_t target) {
    asm volatile("{\n.reg .pred p;\n.reg .u32 n, v;\nmov.u32 n, 0;\n"
                 "LAB_WAIT:\nld.acquire.gpu.global.u32 v, [%0];\nsetp.ge.u32 p, v, %1;\nvote.sync.all.pred p, p, 0xffffffff;\n@p bra.uni LAB_DONE;\n"
                 "add.u32 n, n, 1;\nsetp.lt.u32 p, n, 0x400000;\n@p bra.uni LAB_WAIT;\ntrap;\nLAB_DONE:\n}" :: "l"(c), "r"(target) : "memory");
}
__device__ __forceinline__ uint32_t smem_wait_any(uint32_t a, uint32_t mask) {
    uint32_t v;
    asm volatile("{\n.reg .pred p;\n.reg .u32 n, t;\nmov.u32 n, 0;\n"
                 "LAB_WAIT:\nld.acquire.cta.shared.u32 %0, [%1];\nand.b32 t, %0, %2;\nsetp.ne.u32 p, t, 0;\nvote.sync.all.pred p, p, 0xffffffff;\n@p bra.uni LAB_DONE;\n"
                 "add.u32 n, n, 1;\nsetp.lt.u32 p, n, 0x4000000;\n@p bra.uni LAB_WAIT;\ntrap;\nLAB_DONE:\n}" : "=r"(v) : "r"(a), "r"(mask) : "memory");
    return warp_uniform(v);
}
__device__ __forceinline__ void publish(uint32_t* c, uint32_t n = 1) { bulk_wait(); fence_async_global(); ctr_arrive(c, n); }

__device__ __forceinline__ void wg_fence() { asm volatile("wgmma.fence.sync.aligned;" ::: "memory"); }
__device__ __forceinline__ void wg_commit() { asm volatile("wgmma.commit_group.sync.aligned;" ::: "memory"); }
template <int N> __device__ __forceinline__ void wg_wait() { asm volatile("wgmma.wait_group.sync.aligned %0;" :: "n"(N) : "memory"); }
template <int N> __device__ __forceinline__ void reg_inc() { asm volatile("setmaxnreg.inc.sync.aligned.u32 %0;" :: "n"(N)); }
template <int N> __device__ __forceinline__ void reg_dec() { asm volatile("setmaxnreg.dec.sync.aligned.u32 %0;" :: "n"(N)); }
__host__ __device__ constexpr uint64_t desc_plain(uint32_t addr, uint32_t lbo, uint32_t sbo) {
    return (uint64_t)((addr & 0x3FFFF) >> 4) | ((uint64_t)(lbo >> 4) << 16) | ((uint64_t)(sbo >> 4) << 32);
}
__host__ __device__ constexpr uint64_t desc_sw128(uint32_t addr, uint32_t lbo, uint32_t sbo) { return desc_plain(addr, lbo, sbo) | (1ull << 62); }

__device__ __forceinline__ float ex2(float x) { float y; asm("ex2.approx.ftz.f32 %0, %1;" : "=f"(y) : "f"(x)); return y; }
__device__ __forceinline__ float rcp(float x) { float y; asm("rcp.approx.ftz.f32 %0, %1;" : "=f"(y) : "f"(x)); return y; }
__device__ __forceinline__ float rsq(float x) { float y; asm("rsqrt.approx.ftz.f32 %0, %1;" : "=f"(y) : "f"(x)); return y; }
__device__ __forceinline__ uint32_t pack_bf16(float lo, float hi) { uint32_t r; asm("cvt.rn.bf16x2.f32 %0, %1, %2;" : "=r"(r) : "f"(hi), "f"(lo)); return r; }
__device__ __forceinline__ uint32_t pack_f16(float lo, float hi) { uint32_t r; asm("cvt.rn.f16x2.f32 %0, %1, %2;" : "=r"(r) : "f"(hi), "f"(lo)); return r; }
__device__ __forceinline__ float bf_lo(uint32_t v) { return __uint_as_float(v << 16); }
__device__ __forceinline__ float bf_hi(uint32_t v) { return __uint_as_float(v & 0xFFFF0000u); }
__device__ __forceinline__ float bf_round(float x) { return __uint_as_float(pack_bf16(0.f, x)); }
__device__ __forceinline__ uint32_t badd2(uint32_t a, uint32_t b) { uint32_t r; asm("add.rn.bf16x2 %0, %1, %2;" : "=r"(r) : "r"(a), "r"(b)); return r; }
__device__ __forceinline__ void h2_unpack(uint32_t v, float& lo, float& hi) {
    asm("{.reg .f16 l, h; mov.b32 {l, h}, %2; cvt.f32.f16 %0, l; cvt.f32.f16 %1, h;}" : "=f"(lo), "=f"(hi) : "r"(v));
}
__device__ __forceinline__ uint32_t add_ln2(uint32_t x, float rstd, float nb) { return badd2(x, pack_bf16(fmaf(bf_lo(x), rstd, nb), fmaf(bf_hi(x), rstd, nb))); }
__device__ __forceinline__ float sel4(int t, float a0, float a1, float a2, float a3) {
    float r;
    asm("{\n.reg .pred p, q;\n.reg .f32 x, y;\nsetp.ne.u32 p, %1, 0;\nsetp.ne.u32 q, %2, 0;\nselp.f32 x, %4, %3, p;\nselp.f32 y, %6, %5, p;\nselp.f32 %0, y, x, q;\n}"
        : "=f"(r) : "r"(t & 1), "r"(t & 2), "f"(a0), "f"(a1), "f"(a2), "f"(a3));
    return r;
}
__device__ __forceinline__ float warp_sum(float v) {
    #pragma unroll
    for (int o = 16; o > 0; o >>= 1) v += __shfl_xor_sync(0xffffffffu, v, o);
    return v;
}
__device__ __forceinline__ uint32_t redux_max(uint32_t v) { uint32_t r; asm volatile("redux.sync.max.u32 %0, %1, 0xffffffff;" : "=r"(r) : "r"(v)); return r; }
__device__ __forceinline__ uint32_t redux_min(uint32_t v) { uint32_t r; asm volatile("redux.sync.min.u32 %0, %1, 0xffffffff;" : "=r"(r) : "r"(v)); return r; }

#define TL(T, L, i)

__device__ __forceinline__ void wg_gemm_n128(float (&d)[64], uint64_t desca, uint64_t desc) {
    asm volatile("{\n.reg .pred p;\nsetp.ne.b32 p, 1, 0;\n"
        "wgmma.mma_async.sync.aligned.m64n128k16.f32.bf16.bf16 "
        "{%0,%1,%2,%3,%4,%5,%6,%7,%8,%9,%10,%11,%12,%13,%14,%15,%16,%17,%18,%19,%20,%21,%22,%23,%24,%25,%26,%27,%28,%29,%30,%31,%32,%33,%34,%35,%36,%37,%38,%39,%40,%41,%42,%43,%44,%45,%46,%47,%48,%49,%50,%51,%52,%53,%54,%55,%56,%57,%58,%59,%60,%61,%62,%63}, "
        "%64, %65, p, 1, 1, 0, 1;\n}\n"
        : "+f"(d[0]), "+f"(d[1]), "+f"(d[2]), "+f"(d[3]), "+f"(d[4]), "+f"(d[5]), "+f"(d[6]), "+f"(d[7]),
          "+f"(d[8]), "+f"(d[9]), "+f"(d[10]), "+f"(d[11]), "+f"(d[12]), "+f"(d[13]), "+f"(d[14]), "+f"(d[15]),
          "+f"(d[16]), "+f"(d[17]), "+f"(d[18]), "+f"(d[19]), "+f"(d[20]), "+f"(d[21]), "+f"(d[22]), "+f"(d[23]),
          "+f"(d[24]), "+f"(d[25]), "+f"(d[26]), "+f"(d[27]), "+f"(d[28]), "+f"(d[29]), "+f"(d[30]), "+f"(d[31]),
          "+f"(d[32]), "+f"(d[33]), "+f"(d[34]), "+f"(d[35]), "+f"(d[36]), "+f"(d[37]), "+f"(d[38]), "+f"(d[39]),
          "+f"(d[40]), "+f"(d[41]), "+f"(d[42]), "+f"(d[43]), "+f"(d[44]), "+f"(d[45]), "+f"(d[46]), "+f"(d[47]),
          "+f"(d[48]), "+f"(d[49]), "+f"(d[50]), "+f"(d[51]), "+f"(d[52]), "+f"(d[53]), "+f"(d[54]), "+f"(d[55]),
          "+f"(d[56]), "+f"(d[57]), "+f"(d[58]), "+f"(d[59]), "+f"(d[60]), "+f"(d[61]), "+f"(d[62]), "+f"(d[63])
        : "l"(desca), "l"(desc));
}
__device__ __forceinline__ void wg_gemm_n128_init(float (&d)[64], uint64_t desca, uint64_t desc) {
    asm volatile("{\n.reg .pred p;\nsetp.ne.b32 p, 0, 0;\n"
        "wgmma.mma_async.sync.aligned.m64n128k16.f32.bf16.bf16 "
        "{%0,%1,%2,%3,%4,%5,%6,%7,%8,%9,%10,%11,%12,%13,%14,%15,%16,%17,%18,%19,%20,%21,%22,%23,%24,%25,%26,%27,%28,%29,%30,%31,%32,%33,%34,%35,%36,%37,%38,%39,%40,%41,%42,%43,%44,%45,%46,%47,%48,%49,%50,%51,%52,%53,%54,%55,%56,%57,%58,%59,%60,%61,%62,%63}, "
        "%64, %65, p, 1, 1, 0, 1;\n}\n"
        : "=f"(d[0]), "=f"(d[1]), "=f"(d[2]), "=f"(d[3]), "=f"(d[4]), "=f"(d[5]), "=f"(d[6]), "=f"(d[7]),
          "=f"(d[8]), "=f"(d[9]), "=f"(d[10]), "=f"(d[11]), "=f"(d[12]), "=f"(d[13]), "=f"(d[14]), "=f"(d[15]),
          "=f"(d[16]), "=f"(d[17]), "=f"(d[18]), "=f"(d[19]), "=f"(d[20]), "=f"(d[21]), "=f"(d[22]), "=f"(d[23]),
          "=f"(d[24]), "=f"(d[25]), "=f"(d[26]), "=f"(d[27]), "=f"(d[28]), "=f"(d[29]), "=f"(d[30]), "=f"(d[31]),
          "=f"(d[32]), "=f"(d[33]), "=f"(d[34]), "=f"(d[35]), "=f"(d[36]), "=f"(d[37]), "=f"(d[38]), "=f"(d[39]),
          "=f"(d[40]), "=f"(d[41]), "=f"(d[42]), "=f"(d[43]), "=f"(d[44]), "=f"(d[45]), "=f"(d[46]), "=f"(d[47]),
          "=f"(d[48]), "=f"(d[49]), "=f"(d[50]), "=f"(d[51]), "=f"(d[52]), "=f"(d[53]), "=f"(d[54]), "=f"(d[55]),
          "=f"(d[56]), "=f"(d[57]), "=f"(d[58]), "=f"(d[59]), "=f"(d[60]), "=f"(d[61]), "=f"(d[62]), "=f"(d[63])
        : "l"(desca), "l"(desc));
}
__device__ __forceinline__ void wg_gemm_n192(float (&d)[96], uint64_t desca, uint64_t desc) {
    asm volatile("{\n.reg .pred p;\nsetp.ne.b32 p, 1, 0;\n"
        "wgmma.mma_async.sync.aligned.m64n192k16.f32.bf16.bf16 "
        "{%0,%1,%2,%3,%4,%5,%6,%7,%8,%9,%10,%11,%12,%13,%14,%15,%16,%17,%18,%19,%20,%21,%22,%23,%24,%25,%26,%27,%28,%29,%30,%31,%32,%33,%34,%35,%36,%37,%38,%39,%40,%41,%42,%43,%44,%45,%46,%47,%48,%49,%50,%51,%52,%53,%54,%55,%56,%57,%58,%59,%60,%61,%62,%63,%64,%65,%66,%67,%68,%69,%70,%71,%72,%73,%74,%75,%76,%77,%78,%79,%80,%81,%82,%83,%84,%85,%86,%87,%88,%89,%90,%91,%92,%93,%94,%95}, "
        "%96, %97, p, 1, 1, 0, 1;\n}\n"
        : "+f"(d[0]), "+f"(d[1]), "+f"(d[2]), "+f"(d[3]), "+f"(d[4]), "+f"(d[5]), "+f"(d[6]), "+f"(d[7]),
          "+f"(d[8]), "+f"(d[9]), "+f"(d[10]), "+f"(d[11]), "+f"(d[12]), "+f"(d[13]), "+f"(d[14]), "+f"(d[15]),
          "+f"(d[16]), "+f"(d[17]), "+f"(d[18]), "+f"(d[19]), "+f"(d[20]), "+f"(d[21]), "+f"(d[22]), "+f"(d[23]),
          "+f"(d[24]), "+f"(d[25]), "+f"(d[26]), "+f"(d[27]), "+f"(d[28]), "+f"(d[29]), "+f"(d[30]), "+f"(d[31]),
          "+f"(d[32]), "+f"(d[33]), "+f"(d[34]), "+f"(d[35]), "+f"(d[36]), "+f"(d[37]), "+f"(d[38]), "+f"(d[39]),
          "+f"(d[40]), "+f"(d[41]), "+f"(d[42]), "+f"(d[43]), "+f"(d[44]), "+f"(d[45]), "+f"(d[46]), "+f"(d[47]),
          "+f"(d[48]), "+f"(d[49]), "+f"(d[50]), "+f"(d[51]), "+f"(d[52]), "+f"(d[53]), "+f"(d[54]), "+f"(d[55]),
          "+f"(d[56]), "+f"(d[57]), "+f"(d[58]), "+f"(d[59]), "+f"(d[60]), "+f"(d[61]), "+f"(d[62]), "+f"(d[63]),
          "+f"(d[64]), "+f"(d[65]), "+f"(d[66]), "+f"(d[67]), "+f"(d[68]), "+f"(d[69]), "+f"(d[70]), "+f"(d[71]),
          "+f"(d[72]), "+f"(d[73]), "+f"(d[74]), "+f"(d[75]), "+f"(d[76]), "+f"(d[77]), "+f"(d[78]), "+f"(d[79]),
          "+f"(d[80]), "+f"(d[81]), "+f"(d[82]), "+f"(d[83]), "+f"(d[84]), "+f"(d[85]), "+f"(d[86]), "+f"(d[87]),
          "+f"(d[88]), "+f"(d[89]), "+f"(d[90]), "+f"(d[91]), "+f"(d[92]), "+f"(d[93]), "+f"(d[94]), "+f"(d[95])
        : "l"(desca), "l"(desc));
}
__device__ __forceinline__ void wg_gemm_n192_init(float (&d)[96], uint64_t desca, uint64_t desc) {
    asm volatile("{\n.reg .pred p;\nsetp.ne.b32 p, 0, 0;\n"
        "wgmma.mma_async.sync.aligned.m64n192k16.f32.bf16.bf16 "
        "{%0,%1,%2,%3,%4,%5,%6,%7,%8,%9,%10,%11,%12,%13,%14,%15,%16,%17,%18,%19,%20,%21,%22,%23,%24,%25,%26,%27,%28,%29,%30,%31,%32,%33,%34,%35,%36,%37,%38,%39,%40,%41,%42,%43,%44,%45,%46,%47,%48,%49,%50,%51,%52,%53,%54,%55,%56,%57,%58,%59,%60,%61,%62,%63,%64,%65,%66,%67,%68,%69,%70,%71,%72,%73,%74,%75,%76,%77,%78,%79,%80,%81,%82,%83,%84,%85,%86,%87,%88,%89,%90,%91,%92,%93,%94,%95}, "
        "%96, %97, p, 1, 1, 0, 1;\n}\n"
        : "=f"(d[0]), "=f"(d[1]), "=f"(d[2]), "=f"(d[3]), "=f"(d[4]), "=f"(d[5]), "=f"(d[6]), "=f"(d[7]),
          "=f"(d[8]), "=f"(d[9]), "=f"(d[10]), "=f"(d[11]), "=f"(d[12]), "=f"(d[13]), "=f"(d[14]), "=f"(d[15]),
          "=f"(d[16]), "=f"(d[17]), "=f"(d[18]), "=f"(d[19]), "=f"(d[20]), "=f"(d[21]), "=f"(d[22]), "=f"(d[23]),
          "=f"(d[24]), "=f"(d[25]), "=f"(d[26]), "=f"(d[27]), "=f"(d[28]), "=f"(d[29]), "=f"(d[30]), "=f"(d[31]),
          "=f"(d[32]), "=f"(d[33]), "=f"(d[34]), "=f"(d[35]), "=f"(d[36]), "=f"(d[37]), "=f"(d[38]), "=f"(d[39]),
          "=f"(d[40]), "=f"(d[41]), "=f"(d[42]), "=f"(d[43]), "=f"(d[44]), "=f"(d[45]), "=f"(d[46]), "=f"(d[47]),
          "=f"(d[48]), "=f"(d[49]), "=f"(d[50]), "=f"(d[51]), "=f"(d[52]), "=f"(d[53]), "=f"(d[54]), "=f"(d[55]),
          "=f"(d[56]), "=f"(d[57]), "=f"(d[58]), "=f"(d[59]), "=f"(d[60]), "=f"(d[61]), "=f"(d[62]), "=f"(d[63]),
          "=f"(d[64]), "=f"(d[65]), "=f"(d[66]), "=f"(d[67]), "=f"(d[68]), "=f"(d[69]), "=f"(d[70]), "=f"(d[71]),
          "=f"(d[72]), "=f"(d[73]), "=f"(d[74]), "=f"(d[75]), "=f"(d[76]), "=f"(d[77]), "=f"(d[78]), "=f"(d[79]),
          "=f"(d[80]), "=f"(d[81]), "=f"(d[82]), "=f"(d[83]), "=f"(d[84]), "=f"(d[85]), "=f"(d[86]), "=f"(d[87]),
          "=f"(d[88]), "=f"(d[89]), "=f"(d[90]), "=f"(d[91]), "=f"(d[92]), "=f"(d[93]), "=f"(d[94]), "=f"(d[95])
        : "l"(desca), "l"(desc));
}
__device__ __forceinline__ void wg_qk_init(uint32_t (&d)[32], uint64_t desca, uint64_t desc) {
    asm volatile("{\n.reg .pred p;\nsetp.ne.b32 p, 0, 0;\n"
        "wgmma.mma_async.sync.aligned.m64n128k16.f16.f16.f16 "
        "{%0,%1,%2,%3,%4,%5,%6,%7,%8,%9,%10,%11,%12,%13,%14,%15,%16,%17,%18,%19,%20,%21,%22,%23,%24,%25,%26,%27,%28,%29,%30,%31}, "
        "%32, %33, p, 1, 1, 0, 0;\n}\n"
        : "=r"(d[0]), "=r"(d[1]), "=r"(d[2]), "=r"(d[3]), "=r"(d[4]), "=r"(d[5]), "=r"(d[6]), "=r"(d[7]),
          "=r"(d[8]), "=r"(d[9]), "=r"(d[10]), "=r"(d[11]), "=r"(d[12]), "=r"(d[13]), "=r"(d[14]), "=r"(d[15]),
          "=r"(d[16]), "=r"(d[17]), "=r"(d[18]), "=r"(d[19]), "=r"(d[20]), "=r"(d[21]), "=r"(d[22]), "=r"(d[23]),
          "=r"(d[24]), "=r"(d[25]), "=r"(d[26]), "=r"(d[27]), "=r"(d[28]), "=r"(d[29]), "=r"(d[30]), "=r"(d[31])
        : "l"(desca), "l"(desc));
}
__device__ __forceinline__ void wg_qk_acc(uint32_t (&d)[32], uint64_t desca, uint64_t desc) {
    asm volatile("{\n.reg .pred p;\nsetp.ne.b32 p, 1, 0;\n"
        "wgmma.mma_async.sync.aligned.m64n128k16.f16.f16.f16 "
        "{%0,%1,%2,%3,%4,%5,%6,%7,%8,%9,%10,%11,%12,%13,%14,%15,%16,%17,%18,%19,%20,%21,%22,%23,%24,%25,%26,%27,%28,%29,%30,%31}, "
        "%32, %33, p, 1, 1, 0, 0;\n}\n"
        : "+r"(d[0]), "+r"(d[1]), "+r"(d[2]), "+r"(d[3]), "+r"(d[4]), "+r"(d[5]), "+r"(d[6]), "+r"(d[7]),
          "+r"(d[8]), "+r"(d[9]), "+r"(d[10]), "+r"(d[11]), "+r"(d[12]), "+r"(d[13]), "+r"(d[14]), "+r"(d[15]),
          "+r"(d[16]), "+r"(d[17]), "+r"(d[18]), "+r"(d[19]), "+r"(d[20]), "+r"(d[21]), "+r"(d[22]), "+r"(d[23]),
          "+r"(d[24]), "+r"(d[25]), "+r"(d[26]), "+r"(d[27]), "+r"(d[28]), "+r"(d[29]), "+r"(d[30]), "+r"(d[31])
        : "l"(desca), "l"(desc));
}
__device__ __forceinline__ void wg_pv_init(uint32_t (&d)[10], uint32_t a0, uint32_t a1, uint32_t a2, uint32_t a3, uint64_t desc) {
    asm volatile("{\n.reg .pred p;\nsetp.ne.b32 p, 0, 0;\n"
        "wgmma.mma_async.sync.aligned.m64n40k16.f16.f16.f16 "
        "{%0,%1,%2,%3,%4,%5,%6,%7,%8,%9}, "
        "{%10,%11,%12,%13}, %14, p, 1, 1, 1;\n}\n"
        : "=r"(d[0]), "=r"(d[1]), "=r"(d[2]), "=r"(d[3]), "=r"(d[4]), "=r"(d[5]), "=r"(d[6]), "=r"(d[7]),
          "=r"(d[8]), "=r"(d[9])
        : "r"(a0), "r"(a1), "r"(a2), "r"(a3), "l"(desc));
}
__device__ __forceinline__ void wg_pv_acc(uint32_t (&d)[10], uint32_t a0, uint32_t a1, uint32_t a2, uint32_t a3, uint64_t desc) {
    asm volatile("{\n.reg .pred p;\nsetp.ne.b32 p, 1, 0;\n"
        "wgmma.mma_async.sync.aligned.m64n40k16.f16.f16.f16 "
        "{%0,%1,%2,%3,%4,%5,%6,%7,%8,%9}, "
        "{%10,%11,%12,%13}, %14, p, 1, 1, 1;\n}\n"
        : "+r"(d[0]), "+r"(d[1]), "+r"(d[2]), "+r"(d[3]), "+r"(d[4]), "+r"(d[5]), "+r"(d[6]), "+r"(d[7]),
          "+r"(d[8]), "+r"(d[9])
        : "r"(a0), "r"(a1), "r"(a2), "r"(a3), "l"(desc));
}

constexpr int Q_ABYTES = 256 * 64 * 2, Q_STB = Q_ABYTES + 192 * 64 * 2;
constexpr int OFF_SIDE = 3 * Q_STB;
constexpr int OFF_XS = OFF_SIDE + 49152;
constexpr int OFF_CS = OFF_XS + 4096;
constexpr int OFF_RC = OFF_CS + 768;
constexpr int OFF_FIX = OFF_RC + 2048;
constexpr int A_WIN = KV_WIN + 4096;
constexpr int OFF_QA = 3 * A_WIN;
constexpr int OFF_LC = OFF_QA + 32768;
constexpr int OFF_FE = 147456;
constexpr int OFF_XT = 196608;
__host__ __device__ constexpr uint32_t o_stage(uint32_t s) { return s == 3 ? OFF_QA : s == 2 ? 0 : (s + 1) * A_WIN; }
__host__ __device__ constexpr uint32_t gu_piece(uint32_t i) { return i < 3 ? OFF_FE + i * 16384 : i < 6 ? (i - 1) * 16384 : (i - 6) * 16384; }
constexpr int OFF_FD = 5 * 16384;
constexpr int OFF_BAR = OFF_XT + 32768;
constexpr int OFF_PART = OFF_BAR + 384;
constexpr int OFF_RED = OFF_PART + 2048;
constexpr int OFF_RT = OFF_RED + 96;
constexpr int OFF_M = OFF_RT + 144;
constexpr int OFF_WR = OFF_M + 72;
constexpr int K_SMEM = OFF_WR + 264;
static_assert(K_SMEM <= 232448 && OFF_FIX + 768 <= OFF_BAR && OFF_QA + 32768 <= OFF_FE, "smem");
constexpr uint32_t CH_OK = 0x38003800u;
constexpr int M_SC = 0,
              M_IVS = 24,
              M_ISC = 32,
              M_OK = 40,
              M_WS = 48,
              M_RIDX = 60,
              M_ORDY = 64;
constexpr uint32_t BB = SB + OFF_BAR;
constexpr uint32_t B_QF = BB, B_EPI = BB + 24, B_RES2 = BB + 56, B_AF = BB + 64, B_RES = BB + 120, B_OF = BB + 128,
                   B_FE = BB + 160, B_FL = BB + 168, B_FD = BB + 184, B_PR = BB + 192, B_FW = B_PR, B_SW = BB + 216,
                   B_QE = BB + 224, B_QAF = BB + 248, B_OE = BB + 288, B_AE = BB + 320, B_K0 = BB + 344, B_KV0 = BB + 376;

constexpr int N_OST = 5, N_XST = 9, N_RT = 11, N_KV1 = 12, N_FW = 13, N_GD = 14, N_DD = 15;

struct Maps { CUtensorMap xa0, wqkv, xa, x0, x, out, w64, wo, r, g, u, d, xs; };

__device__ __forceinline__ float2 ln_coef(const uint4& s) {
    const float mean = __uint_as_float(s.x) * (1.f / D_);
    return make_float2(rsq(fmaxf(fmaf(-mean, mean, fmaf(__uint_as_float(s.y), 1.f / D_, LN_EPS)), LN_EPS)), mean);
}
__device__ __forceinline__ uint32_t order_bits(float r) { const uint32_t u = __float_as_uint(r); return (u & 0x80000000u) ? ~u : (u | 0x80000000u); }
__device__ __forceinline__ uint4 warp_best(const uint4& e) {
    const uint32_t m = redux_max(e.x), row = redux_min(e.x == m ? e.y : 0x7FFFFFFFu);
    const int src = __ffs(__ballot_sync(0xffffffffu, e.y == row)) - 1;
    return make_uint4(m, row, __shfl_sync(0xffffffffu, e.z, src), __shfl_sync(0xffffffffu, e.w, src));
}
__device__ __forceinline__ RouteOut route_out(const uint4& e) {
    RouteOut rt;
    rt.idx = e.y; rt.r = __uint_as_float((e.x & 0x80000000u) ? e.x & 0x7FFFFFFFu : ~e.x); rt.mean = __uint_as_float(e.z); rt.rstd = __uint_as_float(e.w);
    return rt;
}

__device__ __forceinline__ void prep_work(const bf16* __restrict__ x0, const CUtensorMap* tmW, int t) {
    const int c = blockIdx.x, lane = t & 31, warp = warp_uniform(t >> 5);
    const int ki = c >> 4, n = c & 15;
    constexpr uint32_t red = SB + OFF_SIDE, xs = red + 4096;
    if (warp == 0) {
        mbar_expect_tx(B_PR, 32768);
        bulk_load(xs, x0 + (size_t)c * 16 * D_, 32768, B_PR);
        mbar_expect_tx(B_PR + 8, 16384);
        tma_load(xs + 32768, tmW, 2 * D_ + n * 64, ki * 128, B_PR + 8);
        tma_load(xs + 32768 + 8192, tmW, 2 * D_ + n * 64, ki * 128 + 64, B_PR + 8);
    }
    const uint4 sent = make_uint4(SENT, SENT, SENT, SENT);
    for (int i = t; i < 2 * NFC * 2; i += 96) reinterpret_cast<uint4*>(&g_ypart[0][0][0])[c * (2 * NFC * 2) + i] = sent;
    if (t < 64) reinterpret_cast<uint4*>(&g_acc[0][0][0])[c * 64 + t] = make_uint4(0u, 0u, 0u, 0u);
    if (t >= 64 && t < 80) g_sums[c * 16 + t - 64] = sent;
    if (t < 2) reinterpret_cast<uint4*>(g_x2row)[c * 2 + t] = sent;
    else if (t < 8) reinterpret_cast<uint4*>(g_fix)[c * 6 + t - 2] = sent;
    else if (t < 12) (&g_kvc[0][0][0])[c * 4 + t - 8] = 0u;
    else if (t >= 24 && t < 32) (&g_oc[0][0][0][0])[c * 8 + t - 24] = 0u;
    else if (t == 13 && c < 16) (&g_xc[0][0])[c] = 0u;
    else if (t >= 16 && t < 20) (&g_tab[0][0][0][0])[c * 4 + t - 16] = sent;
    else if (t >= 32 && t < 64) reinterpret_cast<uint4*>(&g_xrow[0][0][0])[c * 32 + t - 32] = sent;
    mbar_wait(B_PR, 0);
    #pragma unroll 1
    for (int r = warp; r < 16; r += 3) {
        float s = 0.f, q = 0.f;
        #pragma unroll
        for (int i = 0; i < 4; i++) {
            const uint4 u = lds128(xs + r * 2048 + (lane + 32 * i) * 16);
            const float f[8] = {bf_lo(u.x), bf_hi(u.x), bf_lo(u.y), bf_hi(u.y), bf_lo(u.z), bf_hi(u.z), bf_lo(u.w), bf_hi(u.w)};
            #pragma unroll
            for (int e = 0; e < 8; e++) { s += f[e]; q = fmaf(f[e], f[e], q); }
        }
        #pragma unroll
        for (int o = 16; o > 0; o >>= 1) { s += __shfl_xor_sync(0xffffffffu, s, o); q += __shfl_xor_sync(0xffffffffu, q, o); }
        const float mean = s * (1.f / D_);
        const float var = fmaxf(q * (1.f / D_) - mean * mean, 0.f);
        if (lane == 0) g_rs0[c * 16 + r] = make_float2(rsqrtf(var + LN_EPS), mean);
    }
    named_sync(2, 96);
    if (warp == 0) {
        mbar_expect_tx(B_PR + 16, 32768);
        #pragma unroll
        for (int b = 0; b < 4; b++) tma_load(xs + b * 8192, tmW, (b >> 1) * D_ + n * 64, ki * 128 + (b & 1) * 64, B_PR + 16);
    }
    const int j = t & 7, rg = t >> 3;
    #pragma unroll 1
    for (int blk = 0; blk < 3; blk++) {
        const int type = blk == 0 ? 2 : blk - 1;
        const uint32_t wb = xs + type * 16384;
        if (blk < 2) mbar_wait(B_PR + 8 + 8 * blk, 0);
        float cs[8];
        uint32_t z2[4] = {0u, 0u, 0u, 0u};
        #pragma unroll
        for (int i = 0; i < 8; i++) cs[i] = 0.f;
        #pragma unroll 4
        for (int r = rg; r < 128; r += 12) {
            const uint4 u = lds128(wb + r * 128 + ((j ^ (r & 7)) << 4));
            cs[0] += bf_lo(u.x); cs[1] += bf_hi(u.x); cs[2] += bf_lo(u.y); cs[3] += bf_hi(u.y);
            cs[4] += bf_lo(u.z); cs[5] += bf_hi(u.z); cs[6] += bf_lo(u.w); cs[7] += bf_hi(u.w);
            asm("fma.rn.bf16x2 %0, %1, %1, %0;" : "+r"(z2[0]) : "r"(u.x));
            asm("fma.rn.bf16x2 %0, %1, %1, %0;" : "+r"(z2[1]) : "r"(u.y));
            asm("fma.rn.bf16x2 %0, %1, %1, %0;" : "+r"(z2[2]) : "r"(u.z));
            asm("fma.rn.bf16x2 %0, %1, %1, %0;" : "+r"(z2[3]) : "r"(u.w));
        }
        #pragma unroll
        for (int i = 0; i < 8; i++) { cs[i] += __shfl_xor_sync(0xffffffffu, cs[i], 8); cs[i] += __shfl_xor_sync(0xffffffffu, cs[i], 16); }
        float z = ((bf_lo(z2[0]) + bf_hi(z2[0])) + (bf_lo(z2[1]) + bf_hi(z2[1]))) + ((bf_lo(z2[2]) + bf_hi(z2[2])) + (bf_lo(z2[3]) + bf_hi(z2[3])));
        z += __shfl_xor_sync(0xffffffffu, z, 1); z += __shfl_xor_sync(0xffffffffu, z, 2);
        z += __shfl_xor_sync(0xffffffffu, z, 8); z += __shfl_xor_sync(0xffffffffu, z, 16);
        if (lane < 8) {
            #pragma unroll
            for (int i = 0; i < 8; i++) stsf(red + (warp * 200 + type * 64 + j * 8 + i) * 4, cs[i]);
            if ((lane & 3) == 0) stsf(red + (warp * 200 + 192 + type * 2 + (lane >> 2)) * 4, z);
        }
    }
    named_sync(2, 96);
    for (int i = t; i < 198; i += 96) {
        const float v = ldsf(red + i * 4) + ldsf(red + (200 + i) * 4) + ldsf(red + (400 + i) * 4);
        if (i < 192) g_csum[ki * (3 * D_) + (i >> 6) * D_ + n * 64 + (i & 63)] = v;
        else g_wsq[ki * 96 + ((i - 192) >> 1) * 32 + n * 2 + (i & 1)] = v;
    }
    named_sync(2, 96);
    if (warp == 0) { ctr_arrive(&g_c0); ctr_wait(&g_c0, 128); }
    named_sync(2, 96);
}

__device__ __forceinline__ float pow2_inv(float b) {
    const int e = min(max((int)(__float_as_uint(b) >> 23) + 1, 20), 234);
    return __uint_as_float((uint32_t)(254 - e) << 23);
}
__device__ __forceinline__ void epi_inputs(int L) {
    const int t = tid_now() - 288, mt = cta_now() >> 4, nt = cta_now() & 15;
    float p[2][8], r0[3], r1[3];
    #pragma unroll
    for (int k = 0; k < 2; k++)
        #pragma unroll
        for (int q = 0; q < 8; q++) p[k][q] = __ldcg(g_csum + q * (3 * D_) + ((t + 96 * k) >> 6) * D_ + nt * 64 + ((t + 96 * k) & 63));
    #pragma unroll
    for (int k = 0; k < 2; k++) stsf(SB + OFF_CS + (t + 96 * k) * 4, ((p[k][0] + p[k][1]) + (p[k][2] + p[k][3])) + ((p[k][4] + p[k][5]) + (p[k][6] + p[k][7])));
    bool wait;
    uint32_t n = 0;
    do {
        wait = false;
        #pragma unroll
        for (int k = 0; k < 3; k++) {
            const int row = mt * 256 + min(t + 96 * k, 255);
            if (L == 0) { const float2 s = __ldcg(&g_rs0[row]); r0[k] = s.x; r1[k] = s.y; }
            else { const uint4 s = ld_relaxed4(&g_sums[row]); r0[k] = __uint_as_float(s.x); r1[k] = __uint_as_float(s.y); wait = wait || has_sent(s); }
        }
    } while (wait && ++n < SPIN_MAX);
    #pragma unroll
    for (int k = 0; k < 3; k++) {
        if (L != 0) {
            const float mean = r0[k] * (1.f / D_);
            const float var = fmaxf(r1[k] * (1.f / D_) - mean * mean, 0.f);
            const float a = 1.f + rsqrtf(var + LN_EPS);
            r0[k] = a * rsqrtf(a * a * var + LN_EPS); r1[k] = mean;
        }
        if (t + 96 * k < 256) sts64f(SB + OFF_RC + (t + 96 * k) * 8, r0[k], r1[k]);
    }
    if (L == 0 && t < 32) {
        float z = 0.f;
        if (t < 6) {
            #pragma unroll
            for (int q = 0; q < 8; q++) z += __ldcg(g_wsq + q * 96 + (t >> 1) * 32 + nt * 2 + (t & 1));
        }
        const float b = sqrtf(z) * (t < 2 ? 34.f * QSCALE : 34.f);
        const float sc = t < 4 ? fminf(pow2_inv(b) * 32768.f, 1.f) : pow2_inv(b);
        const float bk = __shfl_down_sync(0xffffffffu, b, 2), sk = __shfl_down_sync(0xffffffffu, sc, 2);
        if (t < 6) stsf(SB + OFF_M + M_SC + t * 4, t < 2 ? sc * QSCALE : sc);
        if (t < 2) { stsf(SB + OFF_M + M_ISC + t * 4, 1.f / (sc * sk)); sts32(SB + OFF_M + M_OK + t * 4, sc == 1.f && sk == 1.f && b * bk < 60000.f ? CH_OK : 0u); }
        if (t == 4 || t == 5) stsf(SB + OFF_M + M_IVS + (t - 4) * 4, 1.f / sc);
    }
}

__device__ __forceinline__ int ypos_col(int p) { return (p >> 7) * 128 + ((p >> 1) & 7) * 16 + (p & 1) * 8 + ((p >> 4) & 7); }

template <int NT>
__device__ __forceinline__ float ffn_finish(int L, const RouteOut& rt, int t, uint32_t red, int bid) {
    constexpr int NL = (2 * NFC + NT - 1) / NT;
    const int c = cta_now(), col = ypos_col(c * 8 + (t & 7));
    const uint32_t* src = &g_ypart[L][t >> 1][c * 8 + (t & 1) * 4];
    uint32_t n = 0, xp;
    do { xp = ld_relaxed(&g_xrow[L][rt.idx >> 7][((col >> 5) & 7) * 64 + (col >> 8) * 16 + (col & 6) * 2 + ((col >> 3) & 3)]); } while (xp == SENT && ++n < SPIN_MAX);
    uint4 v[NL];
    #pragma unroll
    for (int i = 0; i < NL; i++) v[i] = t + NT * i < 2 * NFC ? ld_relaxed4(src + i * (NT / 2) * D_) : make_uint4(0u, 0u, 0u, 0u);
    const float xv = (col & 1) ? bf_hi(xp) : bf_lo(xp);
    float rsel = bf_round(rcp(1.f + ex2(bf_round(rt.r) * -1.4426950408889634f))), xn = bf_round((xv - rt.mean) * rt.rstd);
    asm volatile("" : "+f"(rsel), "+f"(xn));
    while (true) {
        bool wait = false;
        #pragma unroll
        for (int i = 0; i < NL; i++) wait = wait || has_sent(v[i]);
        if (!wait || ++n >= SPIN_MAX) break;
        #pragma unroll
        for (int i = 0; i < NL; i++) if (t + NT * i < 2 * NFC) v[i] = ld_relaxed4(src + i * (NT / 2) * D_);
    }
    spin_check(n);
    __syncwarp();
    float a[4] = {0.f, 0.f, 0.f, 0.f};
    #pragma unroll
    for (int i = 0; i < NL; i++) { a[0] += __uint_as_float(v[i].x); a[1] += __uint_as_float(v[i].y); a[2] += __uint_as_float(v[i].z); a[3] += __uint_as_float(v[i].w); }
    const bool b1 = t & 2, b2 = t & 4;
    a[0] = (b1 ? a[1] : a[0]) + __shfl_xor_sync(0xffffffffu, b1 ? a[0] : a[1], 2);
    a[2] = (b1 ? a[3] : a[2]) + __shfl_xor_sync(0xffffffffu, b1 ? a[2] : a[3], 2);
    a[0] = (b2 ? a[2] : a[0]) + __shfl_xor_sync(0xffffffffu, b2 ? a[0] : a[2], 4);
    a[0] += __shfl_xor_sync(0xffffffffu, a[0], 8); a[0] += __shfl_xor_sync(0xffffffffu, a[0], 16);
    if ((t & 31) < 8) stsf(red + (t >> 5) * 32 + (t & 1) * 16 + (t & 6) * 2, a[0]);
    named_sync(bid, NT);
    float y = 0.f, y2 = 0.f;
    #pragma unroll
    for (int i = 0; i < NT / 32; i++) { const float p = ldsf(red + (t & 7) * 4 + i * 32); if (i & 1) y2 += p; else y += p; }
    y += y2;
    return bf_round(xv + bf_round(xn + bf_round(bf_round(y) * rsel)));
}

__device__ __forceinline__ void routed_qkv(int ridx) {
    const int t = tid_now() - 288, c = cta_now(), lane = t & 31, warp = t >> 5;
    constexpr uint32_t red = SB + OFF_RED;
    {
        uint4 v[3];
        uint32_t n = 0;
        do {
            v[0] = ld_relaxed4(g_x2row + t * 4); v[1] = ld_relaxed4(g_x2row + (t + 96) * 4);
            v[2] = t < 64 ? ld_relaxed4(g_x2row + (t + 192) * 4) : make_uint4(0u, 0u, 0u, 0u);
        } while ((has_sent(v[0]) || has_sent(v[1]) || has_sent(v[2])) && ++n < SPIN_MAX);
        spin_check(n);
        __syncwarp();
        TL(288, 0, 21);
        float f[12];
        float s = 0.f;
        #pragma unroll
        for (int i = 0; i < 3; i++) { f[4*i] = __uint_as_float(v[i].x); f[4*i+1] = __uint_as_float(v[i].y); f[4*i+2] = __uint_as_float(v[i].z); f[4*i+3] = __uint_as_float(v[i].w); }
        #pragma unroll
        for (int i = 0; i < 12; i++) s += f[i];
        s = warp_sum(s);
        if (lane == 0) stsf(red + warp * 4, s);
        named_sync(2, 96);
        const float mean = (ldsf(red) + ldsf(red + 4) + ldsf(red + 8)) * (1.f / D_);
        float q = 0.f;
        #pragma unroll
        for (int i = 0; i < 12; i++) { f[i] -= mean; if (i < 8 || t < 64) q = fmaf(f[i], f[i], q); }
        q = warp_sum(q);
        if (lane == 0) stsf(red + 16 + warp * 4, q);
        named_sync(2, 96);
        const float rstd = rsqrtf((ldsf(red + 16) + ldsf(red + 20) + ldsf(red + 24)) * (1.f / D_) + LN_EPS);
        #pragma unroll
        for (int i = 0; i < 3; i++)
            if (i < 2 || t < 64) sts128(SB + OFF_XS + (t + 96 * i) * 16, make_uint4(pack_bf16(0.f, f[4*i] * rstd), pack_bf16(0.f, f[4*i+1] * rstd), pack_bf16(0.f, f[4*i+2] * rstd), pack_bf16(0.f, f[4*i+3] * rstd)));
    }
    named_sync(2, 96);
    TL(288, 0, 22);
    mbar_wait(B_SW, 0);
    TL(288, 0, 23);
    float a[8];
    #pragma unroll
    for (int i = 0; i < 8; i++) a[i] = 0.f;
    const uint32_t wa = SB + OFF_SIDE + t * 16, xa = SB + OFF_XS + (t / 3) * 4;
    #pragma unroll 4
    for (int i = 0; i < 32; i++) {
        const uint4 u = lds128(wa + i * 1536);
        const float xv = ldsf(xa + i * 128);
        a[0] = fmaf(xv, bf_lo(u.x), a[0]); a[1] = fmaf(xv, bf_hi(u.x), a[1]); a[2] = fmaf(xv, bf_lo(u.y), a[2]); a[3] = fmaf(xv, bf_hi(u.y), a[3]);
        a[4] = fmaf(xv, bf_lo(u.z), a[4]); a[5] = fmaf(xv, bf_hi(u.z), a[5]); a[6] = fmaf(xv, bf_lo(u.w), a[6]); a[7] = fmaf(xv, bf_hi(u.w), a[7]);
    }
    named_sync(2, 96);
    TL(288, 0, 41);
    sts128(SB + OFF_SIDE + t * 32, make_uint4(__float_as_uint(a[0]), __float_as_uint(a[1]), __float_as_uint(a[2]), __float_as_uint(a[3])));
    sts128(SB + OFF_SIDE + t * 32 + 16, make_uint4(__float_as_uint(a[4]), __float_as_uint(a[5]), __float_as_uint(a[6]), __float_as_uint(a[7])));
    named_sync(2, 96);
    {
        float y = 0.f;
        #pragma unroll
        for (int i = 0; i < 8; i++) y += ldsf(SB + OFF_SIDE + ((t & 3) * 8 + i) * 96 + (t >> 2) * 4);
        y += __shfl_xor_sync(0xffffffffu, y, 1); y += __shfl_xor_sync(0xffffffffu, y, 2);
        if ((t & 3) == 0) st_relaxed(g_fix + c * 24 + (t >> 2), not_sent(y));
    }
    if ((ridx >> 8) == (c >> 4) && t < 24) {
        const uint32_t* src = g_fix + (t >> 3) * D_ + (c & 15) * 64 + (t & 7) * 8;
        uint4 a, b;
        uint32_t n = 0;
        do { a = ld_relaxed4(src); b = ld_relaxed4(src + 4); } while ((has_sent(a) || has_sent(b)) && ++n < SPIN_MAX);
        spin_check(n);
        const int hh = t >> 2, ch = t & 3, lr = ridx & 255;
        const float hs = ldsf(SB + OFF_M + M_SC + hh * 4);
        sts128(SB + OFF_FIX + t * 16, make_uint4(pack_f16(__uint_as_float(a.x) * hs, __uint_as_float(a.y) * hs), pack_f16(__uint_as_float(a.z) * hs, __uint_as_float(a.w) * hs),
                                                 pack_f16(__uint_as_float(b.x) * hs, __uint_as_float(b.y) * hs), pack_f16(__uint_as_float(b.z) * hs, __uint_as_float(b.w) * hs)));
        sts32(SB + OFF_FIX + 512 + t * 4, SB + (hh < 2 ? OFF_QA + hh * 16384 + (lr >> 6) * 4096 + ch * 1024 + (lr & 63) * 16
                                                        : (hh & 1) * OFF_FE + (hh >> 2) * 16384 + ch * 4096 + lr * 16));
    }
    __syncwarp();
}

#define XP0 2
#define XP1 7
#define FW_NS 1000
__device__ __forceinline__ void ffn_load(const Maps& mp, int c, int i, uint32_t dst, uint32_t bar, bool last_use) {
    if (i < 8) tma_load_h(dst, (i & 1) ? &mp.u : &mp.g, c * 32, (i >> 1) * 256, bar, last_use);
    else tma_load3_h(dst, &mp.d, 0, c * 32, (i - 8) * 4, bar, last_use);
}
__device__ __forceinline__ void side_role(const Maps& mp, const bf16* __restrict__ x0, const bf16* __restrict__ wo, const bf16* __restrict__ w_r) {
    prep_work(x0, &mp.w64, threadIdx.x - 288);
    epi_inputs(0);
    #pragma unroll 1
    for (int L = 0; L < 2; L++) {
        const int t = tid_now() - 288, lane = t & 31, sw = warp_uniform(t >> 5);
        const int c = cta_now(), mt = c >> 4, nt = c & 15;
        named_sync(2, 96);
        if (t == 0) mbar_arrive(B_EPI);
        TL(288, L, 5);
        __syncwarp();
        char* kv = g_kv + (size_t)(nt * 16 + mt) * KV_WIN;
        if (sw < 2) {
            mbar_wait(sw ? B_K0 : B_KV0, L);
            bulk_store(kv + (1 - sw) * 16384, SB + (1 - sw) * 16384, 16384);
            bulk_commit();
            publish(&g_kvc[L][nt * 2][mt], 1 + sw);
            TL(288, L, 6);
        }
        if (sw == 0) {
            named_sync(N_KV1, 64);
            bulk_store(kv + 8 * KV_WIN, SB + OFF_FE, KV_WIN);
            bulk_commit();
            publish(&g_kvc[L][nt * 2 + 1][mt], 3);
        }
        if (sw < 2) {
            #pragma unroll 1
            for (int p = 0; p < 2; p++) {
                named_sync(N_OST + 2 * p + sw, p > sw ? 192 : 160);
                TL(p ? -1 : 288, L, 30); TL(p ? 288 : -1, L, 31);
                if (p == 1) mbar_arrive_elect(B_QAF);
                ctr_arrive(&g_oc[L][mt * 2 + sw][p][nt]);
            }
        } else {
            if (L == 0) {
                float ws = 0.f;
                #pragma unroll
                for (int i = 0; i < 4; i++) {
                    const uint4 v = reinterpret_cast<const uint4*>(w_r)[i * 32 + lane];
                    ws += ((bf_lo(v.x) + bf_hi(v.x)) + (bf_lo(v.y) + bf_hi(v.y))) + ((bf_lo(v.z) + bf_hi(v.z)) + (bf_lo(v.w) + bf_hi(v.w)));
                }
                const uint32_t* wp = reinterpret_cast<const uint32_t*>(w_r) + (nt >> 1) * 64 + (lane >> 2) * 8 + (lane & 3);
                sts64f(SB + OFF_WR + lane * 8, __uint_as_float(wp[0]), __uint_as_float(wp[4]));
                ws = warp_sum(ws);
                if (lane == 0) { stsf(SB + OFF_M + M_WS, ws); sts64f(SB + OFF_M + M_ORDY, 0.f, 0.f); sts64f(SB + OFF_WR + 256, __uint_as_float(0x3F803F80u), __uint_as_float(0x3F803F80u)); }
                __syncwarp();
            }
            named_sync(N_FW, 64);
            mbar_expect_tx(B_RES, 32768);
            #pragma unroll
            for (int i = 0; i < 4; i++) tma_load_h(SB + OFF_XT + i * 8192, L == 0 ? &mp.x0 : &mp.x, (nt >> 1) * 128 + (i >> 1) * 64, mt * 256 + (nt & 1) * 128 + (i & 1) * 64, B_RES, true);
            if (c < NFC) {
                #pragma unroll 1
                for (int r = 0; r < 4; r++) {
                    __nanosleep(FW_NS);
                    if (r > 0) mbar_wait(B_FW, (r + L) & 1);
                    const uint32_t bar = r < 3 ? B_FW : B_FE;
                    mbar_expect_tx(bar, 3 * 16384);
                    #pragma unroll 1
                    for (int b = 0; b < 3; b++) ffn_load(mp, c, 9 - 3 * r + b, SB + OFF_FE + b * 16384, bar, r == 3);
                }
            }
        }
        if (sw == 2) {
            l2_prefetch(reinterpret_cast<const char*>(wo) + (size_t)c * 16384, 16384);
            mbar_wait(B_RES, L);
            const uint32_t lr = lds32(SB + OFF_M + M_RIDX) - (mt * 256 + (nt & 1) * 128);
            if (L == 1 && lr < 128u && lane < 16) {
                const uint4 a = ld_relaxed4(g_x2row + (nt >> 1) * 128 + lane * 8), b = ld_relaxed4(g_x2row + (nt >> 1) * 128 + lane * 8 + 4);
                sts128(SB + OFF_XT + (lane >> 3) * 16384 + lr * 128 + (((lane & 7) ^ (lr & 7)) << 4),
                       make_uint4(__byte_perm(a.x, a.y, 0x7632), __byte_perm(a.z, a.w, 0x7632), __byte_perm(b.x, b.y, 0x7632), __byte_perm(b.z, b.w, 0x7632)));
            }
            if (L == 1) {
                #pragma unroll
                for (int i = 0; i < 4; i++) {
                    const float2 r = ln_coef(ld_relaxed4(&g_sums[mt * 256 + (nt & 1) * 128 + i * 32 + lane]));
                    const float a = i * 32 + lane == lr ? 0.f : r.x;
                    sts64f(SB + OFF_LC + (i * 32 + lane) * 8, a, -a * r.y);
                }
            }
            __syncwarp();
            mbar_arrive_elect(B_RES2);
            named_sync(N_OST + 2, 192);
            l2_prefetch(&g_ypart[L][0][0] + c * (NFC * 8), NFC * 32);
            l2_prefetch(&g_acc[L][c * 16][0], 512);
            l2_prefetch(&g_sums[c * 16], 256);
            l2_prefetch(&g_xrow[L][0][0] + c * 64, 256);
            l2_prefetch(&g_tab[L][0][0][0] + c * 2, 32);
            l2_prefetch(c < 32 ? &g_x2row[c * 32] : c < 40 ? &g_kvc[1][(c - 32) * 4][0] : &g_xc[0][0], c < 40 ? 128 : 64);
            l2_prefetch(&g_fix[c * 24], 96);
            uint32_t ready, n = 0;
            do {
                ready = __ballot_sync(0xffffffffu, ld_acquire(&g_oc[L][mt * 2 + (nt & 1)][1][lane & 15]) != 0);
                fence_async_global();
                if (lane == 0) sts_release(SB + OFF_M + M_ORDY + 4 * L, ready & ready >> 1);
            } while (ready != 0xFFFFFFFFu && ++n < SPIN_MAX);
            spin_check(n);
        }
        if (sw < 2) {
            named_sync(N_XST + sw, 160);
            const int row0 = mt * 256 + (nt & 1) * 128 + sw * 64, col0 = (nt >> 1) * 128;
            #pragma unroll 1
            for (int h = 0; h < 8; h++) {
                if (L == 0) bulk_wait_n<XP0>(); else bulk_wait_n<XP1>();
                tma_store(L == 0 ? &mp.xs : &mp.out, SB + OFF_XT + (h & 1) * 16384 + sw * 8192 + (h >> 1) * 2048, col0 + (h & 1) * 64, row0 + (h >> 1) * 16);
                bulk_commit();
            }
            publish(&g_xc[L][mt]);
            TL(288, L, 14);
        }
        if (L == 0) {
            __syncwarp();
            named_sync(N_RT, 128);
            const RouteOut rt = route_out(lds128(SB + OFF_RT + 128));
            if (t == 0) { sts32(SB + OFF_M + M_RIDX, rt.idx); if (c == 0) g_c0 = 0u; }
            epi_inputs(1);
            const float v = ffn_finish<96>(0, rt, t, SB + OFF_RED, 2);
            TL(288, L, 20);
            if (t < 8) st_relaxed(g_x2row + ypos_col(c * 8 + t), not_sent(v));
            routed_qkv(rt.idx);
        }
    }
}

struct EpiIn { float2 c2[4]; float hs; };
template <int HH>
__device__ __forceinline__ EpiIn qkv_epi_in(int t) {
    EpiIn e;
    #pragma unroll
    for (int jj = 0; jj < 4; jj++) e.c2[jj] = lds64f(SB + OFF_CS + (HH * 32 + jj * 8) * 4 + t * 8);
    e.hs = ldsf(SB + OFF_M + M_SC + HH * 4);
    return e;
}
template <int HH, int NEXT>
__device__ __forceinline__ void qkv_epi_head(const float (&acc0)[96], const float (&acc1)[96], const float (&cf)[4], const float (&nm)[4], EpiIn& in, uint32_t dst, int t) {
    const EpiIn e = in;
    #pragma unroll
    for (int i = 0; i < 4; i++) {
        const float* a = (i >> 1) ? acc1 : acc0;
        const float sc = cf[i] * e.hs;
        uint32_t pk[4];
        #pragma unroll
        for (int jj = 0; jj < 4; jj++)
            pk[jj] = pack_f16(fmaf(nm[i], e.c2[jj].x, a[4 * (4 * HH + jj) + 2 * (i & 1)]) * sc, fmaf(nm[i], e.c2[jj].y, a[4 * (4 * HH + jj) + 2 * (i & 1) + 1]) * sc);
        stsm4(dst + (i >> 1) * (HH < 2 ? 4096 : 1024) + (i & 1) * 128, pk[0], pk[1], pk[2], pk[3]);
        if (i == 1 && NEXT >= 0) in = qkv_epi_in<NEXT < 0 ? 0 : NEXT>(t);
    }
}
__device__ __forceinline__ void qkv_patch(int lane, uint32_t mask) {
    const uint4 v = lds128(SB + OFF_FIX + lane * 16);
    const uint32_t dst = lds32(SB + OFF_FIX + 512 + lane * 4);
    __syncwarp();
    asm volatile("{\n.reg .pred q;\nsetp.ne.u32 q, %5, 0;\n@q st.shared.v4.b32 [%0], {%1, %2, %3, %4};\n}"
                 :: "r"(dst), "r"(v.x), "r"(v.y), "r"(v.z), "r"(v.w), "r"((mask >> lane) & 1) : "memory");
}

template <bool INIT>
__device__ __forceinline__ void qkv_step(float (&acc0)[96], float (&acc1)[96], uint32_t st, int wg) {
    const uint64_t da = desc_sw128(SB, 16, 1024) + ((st * Q_STB + wg * 16384) >> 4);
    const uint64_t db = desc_sw128(SB + Q_ABYTES, 8192, 1024) + ((st * Q_STB) >> 4);
    wg_fence();
    if (INIT) { wg_gemm_n192_init(acc0, da, db); wg_gemm_n192_init(acc1, da + (8192 >> 4), db); }
    #pragma unroll
    for (int kk = INIT ? 1 : 0; kk < 4; kk++) {
        wg_gemm_n192(acc0, da + kk * 2, db + kk * 128);
        wg_gemm_n192(acc1, da + (8192 >> 4) + kk * 2, db + kk * 128);
    }
    wg_commit();
}
__device__ __forceinline__ void qkv_phase(int L, int wg) {
    const uint32_t rb = L * 32;
    float acc0[96], acc1[96];
    const bool leader = (tid_now() & 127) == 0;
    mbar_wait(rb + B_QF, 0);
    TL(0, L, 1);
    qkv_step<true>(acc0, acc1, 0, wg);
    uint32_t st = 1, ph = 0;
    #pragma unroll 1
    for (int k = 1; k < 16; k++) {
        mbar_wait(rb + B_QF + 8 * st, ph);
        qkv_step<false>(acc0, acc1, st, wg);
        wg_wait<1>();
        if (leader) mbar_arrive(rb + B_QE + 8 * (st == 0 ? 2 : st - 1));
        if (++st == 3) { st = 0; ph ^= 1; }
    }
    const int tid = tid_now(), lane = tid & 31, w = (tid >> 5) & 3, g = lane >> 2, t = lane & 3;
    mbar_wait(B_EPI, L);
    float cf[4], nm[4];
    #pragma unroll
    for (int i = 0; i < 4; i++) { const float2 r = lds64f(SB + OFF_RC + (wg * 128 + w * 16 + g + (i >> 1) * 64 + (i & 1) * 8) * 8); cf[i] = r.x; nm[i] = -r.y; }
    const int d = (int)lds32(SB + OFF_M + M_RIDX) - (cta_now() >> 4) * 256;
    const bool own = L == 1 && (d >> 7) == wg && ((d >> 4) & 3) == w;
    EpiIn in = qkv_epi_in<2>(t);
    wg_wait<0>();
    TL(0, L, 2);
    TL(128, L, 40);
    named_sync(1, 256);
    const uint32_t dk = SB + wg * 2048 + (lane >> 3) * 4096 + (w * 16 + (lane & 7)) * 16;
    const uint32_t dq = SB + OFF_QA + wg * 8192 + (lane >> 3) * 1024 + (w * 16 + (lane & 7)) * 16;
    qkv_epi_head<2, 4>(acc0, acc1, cf, nm, in, dk, t);
    if (own) qkv_patch(lane, 0x000F00u);
    fence_async_smem();
    __syncwarp();
    mbar_arrive_elect(B_K0);
    qkv_epi_head<4, 0>(acc0, acc1, cf, nm, in, dk + 16384, t);
    if (own) qkv_patch(lane, 0x0F0000u);
    #pragma unroll
    for (int s = 0; s < 3; s++) sts128(SB + s * A_WIN + KV_WIN + tid * 16, make_uint4(0x3C003C00u, 0x3C003C00u, 0x3C003C00u, 0x3C003C00u));
    fence_async_smem();
    __syncwarp();
    mbar_arrive_elect(B_KV0);
    TL(0, L, 4);
    qkv_epi_head<0, 1>(acc0, acc1, cf, nm, in, dq, t);
    qkv_epi_head<1, 3>(acc0, acc1, cf, nm, in, dq + 16384, t);
    qkv_epi_head<3, 5>(acc0, acc1, cf, nm, in, dk + OFF_FE, t);
    qkv_epi_head<5, -1>(acc0, acc1, cf, nm, in, dk + OFF_FE + 16384, t);
    if (own) qkv_patch(lane, 0xF0F0FFu);
    fence_async_smem();
    named_sync(3 + wg, 128);
    TL(0, L, 3);
}

struct Unit {
    uint32_t o[8];
    uint32_t l, bz, sc;
    uint32_t ch[2];
};
template <int H> __device__ __forceinline__ uint32_t hdup(uint32_t v) {
    uint32_t r;
    if (H) asm("{.reg .b16 l, h; mov.b32 {l, h}, %1; mov.b32 %0, {h, h};}" : "=r"(r) : "r"(v));
    else asm("{.reg .b16 l, h; mov.b32 {l, h}, %1; mov.b32 %0, {l, l};}" : "=r"(r) : "r"(v));
    return r;
}
__device__ __forceinline__ uint32_t hmax2(uint32_t a, uint32_t b) { uint32_t r; asm("max.f16x2 %0, %1, %2;" : "=r"(r) : "r"(a), "r"(b)); return r; }
__device__ __forceinline__ uint32_t hadd2(uint32_t a, uint32_t b) { uint32_t r; asm("add.rn.f16x2 %0, %1, %2;" : "=r"(r) : "r"(a), "r"(b)); return r; }
__device__ __forceinline__ uint32_t hsub2(uint32_t a, uint32_t b) { uint32_t r; asm("sub.rn.f16x2 %0, %1, %2;" : "=r"(r) : "r"(a), "r"(b)); return r; }
__device__ __forceinline__ uint32_t hfma2(uint32_t a, uint32_t b, uint32_t c) { uint32_t r; asm("fma.rn.f16x2 %0, %1, %2, %3;" : "=r"(r) : "r"(a), "r"(b), "r"(c)); return r; }
__device__ __forceinline__ uint32_t exp2_h2(uint32_t s, uint32_t bz, uint32_t& ch) {
    uint32_t z, w, d;
    asm("fma.rn.relu.f16x2 %0, %1, %2, %3;" : "=r"(z) : "r"(s), "r"(0x00400040u), "r"(bz));
    asm("lop3.b32 %0, %1, 0x003F003F, %0, 0xC2;" : "+r"(ch) : "r"(z));
    asm("fma.rn.f16x2 %0, %1, %2, %3;" : "=r"(w) : "r"(ch), "r"(0x30A630A6u), "r"(0xACCCACCCu));
    asm("{.reg .b32 n; neg.f16x2 n, %1; fma.rn.relu.f16x2 %0, n, %1, %2;}" : "=r"(d) : "r"(w), "r"(0x00580058u));
    return (z << 4) - d;
}
__device__ __forceinline__ void exp_tile(uint32_t (&p)[32], const uint32_t (&s)[32], Unit& u) {
    #pragma unroll
    for (int i = 0; i < 32; i++) p[i] = exp2_h2(s[i], (i & 1) ? hdup<1>(u.bz) : hdup<0>(u.bz), u.ch[i & 1]);
}
__device__ __forceinline__ void issue_qk(uint32_t (&s)[32], uint64_t dq, uint64_t dk) {
    wg_qk_init(s, dq, dk); wg_qk_acc(s, dq + (2048 >> 4), dk + (8192 >> 4));
    wg_commit();
}
template <bool INIT>
__device__ __forceinline__ void issue_pv(uint32_t (&h)[10], const uint32_t (&p)[32], uint64_t dv) {
    #pragma unroll
    for (int k = 0; k < 8; k++) {
        if (INIT && k == 0) wg_pv_init(h, p[0], p[1], p[2], p[3], dv);
        else wg_pv_acc(h, p[4*k], p[4*k+1], p[4*k+2], p[4*k+3], dv + k * 16);
    }
    wg_commit();
}
__device__ __forceinline__ void unit_init(Unit& u, const uint32_t (&s)[32], uint32_t ok) {
    uint32_t m0 = s[0], m1 = s[1];
    #pragma unroll
    for (int i = 1; i < 16; i++) { m0 = hmax2(m0, s[2 * i]); m1 = hmax2(m1, s[2 * i + 1]); }
    uint32_t m = hmax2(__byte_perm(m0, m1, 0x5410), __byte_perm(m0, m1, 0x7632));
    m = hmax2(m, __shfl_xor_sync(0xffffffffu, m, 1)); m = hmax2(m, __shfl_xor_sync(0xffffffffu, m, 2));
    float f0, f1; h2_unpack(m, f0, f1);
    u.ch[0] = fabsf(f0) < 380.f ? ok : 0u; u.ch[1] = fabsf(f1) < 380.f ? ok : 0u;
    f0 = (63.f - ceilf(f0 * 4.f)) * 9.5367431640625e-07f; f1 = (63.f - ceilf(f1 * 4.f)) * 9.5367431640625e-07f;
    u.bz = pack_f16(f0, f1); u.sc = 0u; u.l = 0u;
    #pragma unroll
    for (int i = 0; i < 8; i++) u.o[i] = 0u;
}
template <bool MORE>
__device__ __forceinline__ void unit_flush(Unit& u, const uint32_t (&h)[10]) {
    u.l = hfma2(u.l, u.sc, __byte_perm(h[8], h[9], 0x5410));
    #pragma unroll
    for (int i = 0; i < 8; i++) u.o[i] = hfma2(u.o[i], (i & 1) ? hdup<1>(u.sc) : hdup<0>(u.sc), h[i]);
    if (MORE) {
        const uint32_t ex = u.l & 0x7C007C00u;
        u.sc = 0x84008400u - ex;
        u.bz = hsub2(hadd2(u.bz, 0x04800480u), ex >> 4);
    }
}
__device__ __forceinline__ char* o_block(int wg, int pass) { const int c = cta_now(); return g_o + (size_t)((((c >> 4) * 2 + wg) * 2 + pass) * 16 + (c & 15)) * 8192; }
__device__ __forceinline__ uint32_t unit_store(const Unit& u, char* dst, float ivs) {
    uint32_t bad = 0;
    float lf[2]; h2_unpack(u.l, lf[0], lf[1]);
    #pragma unroll
    for (int h = 0; h < 2; h++) {
        uint32_t b = __ballot_sync(0xffffffffu, (~u.ch[h] & CH_OK) != 0 || !(lf[h] >= 2.f && lf[h] <= 65504.f));
        b |= b >> 1; b = (b | b >> 2) & 0x11111111u;
        const float inv = ivs * rcp(lf[h]);
        #pragma unroll
        for (int j = 0; j < 4; j++) { float x, y; h2_unpack(u.o[2 * j + h], x, y); *reinterpret_cast<uint32_t*>(dst + j * 1024 + h * 128) = pack_bf16(x * inv, y * inv); }
        bad |= b << h;
    }
    return bad;
}
__device__ __noinline__ void exact_rows(int L, int pass, int wg, uint32_t bad) {
    const int tid = tid_now() & 127, lane = tid & 31, w = tid >> 5, t = lane & 3;
    const int head = (cta_now() & 15) * 2 + pass;
    const uint32_t scr = SB + OFF_PART + wg * 1024;
    if (lane == 0) sts32(scr + w * 4, bad);
    ctr_wait_all(&g_kvc[L][head][lane & 7], 3);
    named_sync(3 + wg, 128);
    const float isc = ldsf(SB + OFF_M + M_ISC + pass * 4), ivs = ldsf(SB + OFF_M + M_IVS + pass * 4);
    const char* kv = g_kv + (size_t)(head * 8 + w * 2) * KV_WIN + t * 4096 + (lane >> 2) * 16;
    #pragma unroll 1
    for (int ww = 0; ww < 4; ww++)
    #pragma unroll 1
    for (uint32_t m = lds32(scr + ww * 4); m; m &= m - 1) {
        const int bit = __ffs(m) - 1;
        const uint32_t ro = (bit & 2) * 2048 + (ww * 16 + (bit & 1) * 8 + (bit >> 2)) * 16;
        const uint4 q = lds128(SB + OFF_QA + pass * 16384 + wg * 8192 + ro + t * 1024);
        float a[9], mx = -INFINITY;
        #pragma unroll
        for (int i = 0; i < 9; i++) a[i] = 0.f;
        #pragma unroll 1
        for (int it = 0; it < 8; it++) {
            uint4 k[8], v[8];
            #pragma unroll
            for (int i = 0; i < 8; i++) {
                const char* p = kv + (it >> 2) * KV_WIN + (it & 3) * 1024 + i * 128;
                k[i] = __ldcg(reinterpret_cast<const uint4*>(p)); v[i] = __ldcg(reinterpret_cast<const uint4*>(p + 16384));
            }
            float s[8], mn = mx;
            #pragma unroll
            for (int i = 0; i < 8; i += 2) {
                float c[4] = {0.f, 0.f, 0.f, 0.f};
                mma_f16(c, k[i].x, k[i + 1].x, k[i].y, k[i + 1].y, q.x, q.y);
                mma_f16(c, k[i].z, k[i + 1].z, k[i].w, k[i + 1].w, q.z, q.w);
                s[i] = c[0]; s[i + 1] = c[2];
                mn = fmaxf(mn, fmaxf(c[0], c[2]));
            }
            const float al = ex2((mx - mn) * isc);
            mx = mn;
            #pragma unroll
            for (int i = 0; i < 9; i++) a[i] *= al;
            #pragma unroll
            for (int i = 0; i < 8; i++) {
                const float p = ex2((s[i] - mx) * isc);
                const uint32_t u[4] = {v[i].x, v[i].y, v[i].z, v[i].w};
                a[8] += p;
                #pragma unroll
                for (int e = 0; e < 4; e++) { float x, y; h2_unpack(u[e], x, y); a[2 * e] = fmaf(p, x, a[2 * e]); a[2 * e + 1] = fmaf(p, y, a[2 * e + 1]); }
            }
        }
        #pragma unroll 1
        for (int o = 4; o < 32; o <<= 1) {
            const float mn = fmaxf(mx, __shfl_xor_sync(0xffffffffu, mx, o)), al = ex2((mx - mn) * isc);
            mx = mn;
            #pragma unroll
            for (int i = 0; i < 9; i++) { a[i] *= al; a[i] += __shfl_xor_sync(0xffffffffu, a[i], o); }
        }
        named_sync(3 + wg, 128);
        const uint32_t mine = scr + 16 + w * 144;
        sts128(mine + t * 32, make_uint4(__float_as_uint(a[0]), __float_as_uint(a[1]), __float_as_uint(a[2]), __float_as_uint(a[3])));
        sts128(mine + t * 32 + 16, make_uint4(__float_as_uint(a[4]), __float_as_uint(a[5]), __float_as_uint(a[6]), __float_as_uint(a[7])));
        sts64f(mine + 128, a[8], mx);
        named_sync(3 + wg, 128);
        float o = 0.f, l = 0.f;
        mx = -INFINITY;
        #pragma unroll 1
        for (int i = 0; i < 4; i++) {
            const float2 e = lds64f(scr + 16 + i * 144 + 128);
            const float mn = fmaxf(mx, e.y), al = ex2((mx - mn) * isc), be = ex2((e.y - mn) * isc);
            mx = mn;
            o = fmaf(o, al, be * ldsf(scr + 16 + i * 144 + lane * 4)); l = fmaf(l, al, be * e.x);
        }
        if (w == 0) *reinterpret_cast<unsigned short*>(o_block(wg, pass) + ro + (lane >> 3) * 1024 + (lane & 7) * 2) = (unsigned short)pack_bf16(o * ivs * rcp(l), 0.f);
    }
}

__device__ __forceinline__ void attention_phase(int L, int wg) {
    const uint32_t rb = L * 32;
    constexpr uint64_t dk0 = desc_plain(SB, 4096, 128), dv0 = desc_plain(SB + 16384, 128, 4096);
    constexpr int T1 = 2048 >> 4;
    uint32_t st = 0, ph = 0;
    #pragma unroll 1
    for (int pass = 0; pass < 2; pass++) {
        const uint64_t dqa = desc_plain(SB + OFF_QA, 1024, 128) + (pass * 4 + wg * 2) * (4096 >> 4), dqc = dqa + (4096 >> 4);
        Unit a, c;
        st = warp_uniform(st); ph = warp_uniform(ph);
        uint32_t SA[32], SC[32], PA[32], PC[32], ha[10], hc[10], bad;
        #pragma unroll
        for (int i = 0; i < 10; i++) hc[i] = 0u;
        #pragma unroll
        for (int i = 0; i < 32; i++) PC[i] = 0u;
        const uint32_t ok = lds32(SB + OFF_M + M_OK + pass * 4);
        mbar_wait(rb + B_AF + 8 * st, ph);
        wg_fence();
        issue_qk(SA, dqa, dk0 + st * (A_WIN >> 4));
        issue_qk(SC, dqc, dk0 + st * (A_WIN >> 4));
        wg_wait<1>();
        unit_init(a, SA, ok);
        exp_tile(PA, SA, a);
        wg_wait<0>();
        unit_init(c, SC, ok);
        uint32_t eb = 0;
        #pragma unroll 1
        for (int s = 0;; s++) {
            const uint64_t dkb = dk0 + st * (A_WIN >> 4), dvb = dv0 + st * (A_WIN >> 4);
            if (__builtin_expect(s == 8 * gridDim.y, 0)) {
                wg_wait<0>();
                bad = 0;
                #pragma unroll
                for (int i = 0; i < 32; i++) bad |= PC[i];
                break;
            }
            wg_fence();
            issue_pv<true>(ha, PA, dvb); issue_qk(SA, dqa, dkb + T1);
            wg_wait<2>();
            if (s > 0) { mbar_arrive_elect(eb); unit_flush<true>(c, hc); }
            exp_tile(PC, SC, c);
            wg_fence();
            issue_pv<true>(hc, PC, dvb); issue_qk(SC, dqc, dkb + T1);
            wg_wait<2>();
            exp_tile(PA, SA, a);
            eb = rb + B_AE + 8 * st;
            if (++st == 3) { st = 0; ph ^= 1; }
            if (s == 7) {
                wg_fence(); issue_pv<false>(ha, PA, dvb + T1);
                wg_wait<1>();
                exp_tile(PC, SC, c);
                wg_fence(); issue_pv<false>(hc, PC, dvb + T1);
                wg_wait<1>();
                const int tid = tid_now();
                const float ivs = ldsf(SB + OFF_M + M_IVS + pass * 4);
                char* dst = o_block(wg, pass) + (tid & 96) * 8 + (tid & 31) * 4;
                unit_flush<false>(a, ha);
                bad = unit_store(a, dst, ivs);
                wg_wait<0>();
                mbar_arrive_elect(eb);
                unit_flush<false>(c, hc);
                bad |= unit_store(c, dst + 4096, ivs) << 2;
                break;
            }
            const uint64_t dkn = dk0 + st * (A_WIN >> 4);
            mbar_wait(rb + B_AF + 8 * st, ph);
            wg_fence();
            issue_pv<false>(ha, PA, dvb + T1); issue_qk(SA, dqa, dkn);
            wg_wait<2>();
            exp_tile(PC, SC, c);
            wg_fence();
            issue_pv<false>(hc, PC, dvb + T1); issue_qk(SC, dqc, dkn);
            wg_wait<2>();
            unit_flush<true>(a, ha);
            exp_tile(PA, SA, a);
        }
        if (__builtin_expect(named_any(bad != 0, 3 + wg), 0)) {
            exact_rows(L, pass, wg, bad);
        }
        named_arrive(N_OST + 2 * pass + wg, pass > wg ? 192 : 160);
        TL(pass ? -1 : 0, L, 8); TL(pass ? 0 : -1, L, 9);
    }
}

#define XS0 0
#define OW0 1
#define OUNR 1
#define GDP 0
#define DDP 1

template <bool INIT>
__device__ __forceinline__ void oproj_step(float (&acc)[64], uint32_t s, int wg) {
    const uint64_t da = desc_plain(SB, 1024, 128) + ((o_stage(s) + wg * 4096) >> 4);
    const uint64_t db = desc_sw128(SB + 16384, 8192, 1024) + (o_stage(s) >> 4);
    wg_fence();
    if (INIT) wg_gemm_n128_init(acc, da, db);
    #pragma unroll
    for (int kk = INIT ? 1 : 0; kk < 4; kk++) wg_gemm_n128(acc, da + (kk >> 1) * 512 + (kk & 1) * 128, db + kk * 128);
    wg_commit();
}
__device__ __forceinline__ void oproj_phase(int L, int wg, bf16* __restrict__ out) {
    const int c = cta_now(), tid = tid_now(), lane = tid & 31, W = tid >> 5, g = lane >> 2, t = lane & 3;
    const int row0 = (c >> 4) * 256 + (c & 1) * 128, col0 = ((c & 15) >> 1) * 128;
    float acc[64];
    mbar_wait(B_OF, 0);
    TL(0, L, 10);
    oproj_step<true>(acc, 0, wg);
    const uint32_t xa = SB + OFF_XT + (W * 16 + ((lane >> 3) & 1) * 8 + (lane & 7)) * 128, xs = (lane >> 4) ^ (lane & 7);
    mbar_wait(B_RES2, L);
    const float2 c0 = lds64f(SB + OFF_LC + (W * 16 + g) * 8), c1 = lds64f(SB + OFF_LC + (W * 16 + g + 8) * 8);
    constexpr int ounr = OUNR;
    #pragma unroll ounr
    for (int k = 1; k < 16; k++) {
        if (OW0) { wg_wait<0>(); if ((tid & 127) == 0) mbar_arrive(B_OE + 8 * ((k - 1) & 3)); }
        mbar_wait(B_OF + 8 * (k & 3), (k >> 2) & 1);
        TL(k == 8 ? 0 : -1, L, 11);
        oproj_step<false>(acc, k & 3, wg);
        if (!OW0) { wg_wait<1>(); if ((tid & 127) == 0) mbar_arrive(B_OE + 8 * ((k - 1) & 3)); }
        if (L == 1 && (k & 1)) {
            const uint32_t a = xa + (k & 8) * 2048 + ((xs ^ (k & 6)) << 4);
            uint32_t v0, v1, v2, v3;
            ldsm4(v0, v1, v2, v3, a);
            stsm4(a, add_ln2(v0, c0.x, c0.y), add_ln2(v1, c1.x, c1.y), add_ln2(v2, c0.x, c0.y), add_ln2(v3, c1.x, c1.y));
        }
    }
    uint32_t x[32];
    const uint32_t wra = SB + OFF_WR + (g == 4 ? t * 8 : 256), wrs = g == 4 ? 32 : 0;
    float2 wb[8];
    #pragma unroll
    for (int ks = 0; ks < 8; ks++) {
        ldsm4(x[4*ks], x[4*ks+1], x[4*ks+2], x[4*ks+3], xa + (ks >> 2) * 16384 + ((xs ^ ((ks & 3) * 2)) << 4));
        wb[ks] = lds64f(wra + ks * wrs);
    }
    wg_wait<0>();
    if ((tid & 127) == 0) mbar_arrive(B_OE + 24);
    TL(0, L, 12);
    {
        float sd[4] = {0.f, 0.f, 0.f, 0.f}, z0[4] = {0.f, 0.f, 0.f, 0.f}, z1[4] = {0.f, 0.f, 0.f, 0.f};
        #pragma unroll
        for (int ks = 0; ks < 8; ks++) {
            #pragma unroll
            for (int i = 0; i < 4; i++) x[4*ks + i] = badd2(x[4*ks + i], pack_bf16(acc[8*ks + 2*i], acc[8*ks + 2*i + 1]));
            mma_bf16(sd, x[4*ks], x[4*ks+1], x[4*ks+2], x[4*ks+3], __float_as_uint(wb[ks].x), __float_as_uint(wb[ks].y));
            mma_bf16(z0, x[4*ks], x[4*ks+1], x[4*ks+2], x[4*ks+3], x[4*ks], x[4*ks+2]);
            mma_bf16(z1, x[4*ks], x[4*ks+1], x[4*ks+2], x[4*ks+3], x[4*ks+1], x[4*ks+3]);
        }
        const float s0 = __shfl_sync(0xffffffffu, (g & 1) ? z0[1] : z0[0], 4 * g + (g >> 1));
        const float s1 = __shfl_sync(0xffffffffu, (g & 1) ? z1[3] : z1[2], 4 * g + (g >> 1));
        double* p = &g_acc[L][row0 + W * 16 + g][t];
        asm volatile("red.relaxed.gpu.global.add.f64 [%0], %1;" :: "l"(p), "d"((double)sel4(t, sd[0], s0, sd[0], 1.f)) : "memory");
        asm volatile("red.relaxed.gpu.global.add.f64 [%0], %1;" :: "l"(p + 32), "d"((double)sel4(t, sd[2], s1, sd[2], 1.f)) : "memory");
    }
    TL(0, L, 13);
    if (L == 0) {
        #pragma unroll
        for (int ks = 0; ks < 8; ks++) stsm4(xa + (ks >> 2) * 16384 + ((xs ^ ((ks & 3) * 2)) << 4), x[4*ks], x[4*ks+1], x[4*ks+2], x[4*ks+3]);
        fence_async_smem();
        if (XS0 == 0) named_arrive(N_XST + wg, 160);
    }
    const bool ffn = c < NFC;
    uint4 fa[32], fd[16];
    const uint32_t ga = SB + W * 2048 + ((lane >> 4) * 8 + (lane & 7)) * 64 + ((((lane >> 3) & 1) ^ ((lane >> 1) & 3)) << 4);
    if (ffn) mbar_wait(B_FE, L);
    #pragma unroll
    for (int i = 0; i < 12; i++) ldsm4t(fa[i].x, fa[i].y, fa[i].z, fa[i].w, (ga ^ ((i & 1) * 32)) + gu_piece(i >> 2) + (i & 2) * 512);
    float2 r0, r1;
    {
        const float ws = ldsf(SB + OFF_M + M_WS);
        const uint32_t row = row0 + W * 16 + g;
        const bool odd = t & 1, up = t & 2;
        const uint32_t me = row + (odd ? 8 : 0);
        uint4 v;
        uint32_t n = 0;
        do { v = ld_relaxed4(&g_acc[L][me][t & 2]); } while (__any_sync(0xffffffffu, up && v.w != 0x40200000u) && ++n < SPIN_MAX);
        spin_check(n);
        TL(0, L, 46);
        if (XS0 == 1 && L == 0) named_arrive(N_XST + wg, 160);
        const float f0 = (float)__hiloint2double(v.y, v.x), f1 = (float)__hiloint2double(v.w, v.z);
        const float e0 = __shfl_xor_sync(0xffffffffu, f0, 2), e1 = __shfl_xor_sync(0xffffffffu, f1, 2);
        const float a[3] = {up ? e0 : f0, up ? e1 : f1, up ? f0 : e0};
        const uint4 tot = make_uint4(not_sent(a[0]), not_sent(a[1]), 0u, 0u);
        st_relaxed4_if(&g_sums[me], tot, L == 0 && col0 == 0 && t < 2);
        const float2 r = ln_coef(tot), ro = make_float2(__shfl_xor_sync(0xffffffffu, r.x, 1), __shfl_xor_sync(0xffffffffu, r.y, 1));
        r0 = odd ? ro : r; r1 = odd ? r : ro;
        const uint32_t k = min(order_bits(r.x * fmaf(-r.y, ws, a[2])), SENT - 1);
        const uint32_t m = redux_max(k), mrow = redux_min(k == m ? me : 0x7FFFFFFFu);
        if (me == mrow) sts128(SB + OFF_RT + W * 16, make_uint4(k, me, not_sent(r.y), not_sent(r.x)));
    }
    named_sync(1, 256);
    {
        const uint4 e = lds128(SB + OFF_RT + (lane & 7) * 16);
        const uint32_t m = redux_max(e.x), row = redux_min(e.x == m ? e.y : 0x7FFFFFFFu);
        const int lr = row - row0;
        st_relaxed4_if(&g_tab[L][(c & 15) >> 1][row0 >> 7][(lane >> 3) & 1], e, W == ((lr >> 4) ^ 1) && e.y == row && lane < 16);
        if ((lr >> 4) == W) {
            const bool hi = lr & 8;
            uint32_t* dst = &g_xrow[L][row0 >> 7][(col0 & 128) * 2 + (col0 >> 8) * 16 + t * 4];
            #pragma unroll
            for (int i = 0; i < 4; i++)
                st_relaxed4_if(dst + i * 64, make_uint4(min(hi ? x[8*i+1] : x[8*i], SENT - 1), min(hi ? x[8*i+3] : x[8*i+2], SENT - 1),
                               min(hi ? x[8*i+5] : x[8*i+4], SENT - 1), min(hi ? x[8*i+7] : x[8*i+6], SENT - 1)), g == (lr & 7));
        }
        __syncwarp();
    }
    TL(0, L, 15);
    if (XS0 == 2 && L == 0) named_arrive(N_XST + wg, 160);
    if (L == 1) {
        const float b0 = -r0.x * r0.y, b1 = -r1.x * r1.y;
        #pragma unroll
        for (int ks = 0; ks < 8; ks++)
            stsm4(xa + (ks >> 2) * 16384 + ((xs ^ ((ks & 3) * 2)) << 4), add_ln2(x[4*ks], r0.x, b0), add_ln2(x[4*ks+1], r1.x, b1),
                  add_ln2(x[4*ks+2], r0.x, b0), add_ln2(x[4*ks+3], r1.x, b1));
        TL(0, L, 47);
        fence_async_smem();
        named_arrive(N_XST + wg, 160);
    }
    TL(0, L, 45);
    RouteOut rt;
    {
        const uint4* tp = &g_tab[L][(c & 15) >> 1][lane & 15][0];
        uint4 e = ld_relaxed4(tp);
        if (ffn) mbar_wait(B_FL, L);
        #pragma unroll
        for (int i = 12; i < 32; i++) ldsm4t(fa[i].x, fa[i].y, fa[i].z, fa[i].w, (ga ^ ((i & 1) * 32)) + gu_piece(i >> 2) + (i & 2) * 512);
        TL(0, L, 44);
        if (L == 0 && GDP == 0) named_arrive(N_GD, 288);
        uint32_t n = 0;
        while (has_sent(e) && ++n < SPIN_MAX) e = ld_relaxed4(tp);
        spin_check(n);
        __syncwarp();
        e = warp_best(e);
        rt = route_out(e);
        if (W == 7 && L == 0) { sts128(SB + OFF_RT + 128, e); named_arrive(N_RT, 128); }
    }
    TL(0, L, 16);
    uint2 xrow;
    {
        const uint32_t* xp = &g_xrow[L][rt.idx >> 7][W * 64 + (g >> 1) * 16 + t * 4 + (g & 1) * 2];
        xrow = ld_relaxed2(xp);
        if (ffn) mbar_wait(B_FD, L);
        const uint32_t wa = SB + OFF_FD + W * 8192 + ((lane >> 4) * 8 + (lane & 7)) * 128 + ((((lane >> 3) & 1) ^ (lane & 7)) << 4);
        #pragma unroll
        for (int i = 0; i < 16; i++) ldsm4t(fd[i].x, fd[i].y, fd[i].z, fd[i].w, (wa ^ (((i >> 1) & 3) * 32)) + (i >> 3) * 4096 + (i & 1) * 2048);
        if (L == 0 && GDP == 1) named_arrive(N_GD, 288);
        if (L == 0 && DDP == 1) named_arrive(N_DD, 288);
        uint32_t n = 0;
        while ((xrow.x == SENT || xrow.y == SENT) && ++n < SPIN_MAX) xrow = ld_relaxed2(xp);
        spin_check(n);
        __syncwarp();
    }
    if (L == 0 && GDP == 2) named_arrive(N_GD, 288);
    if (L == 0 && DDP == 2) named_arrive(N_DD, 288);
    TL(0, L, 17);
    {
        const float nb = -rt.mean * rt.rstd;
        const uint32_t n0 = pack_bf16(fmaf(bf_lo(xrow.x), rt.rstd, nb), fmaf(bf_hi(xrow.x), rt.rstd, nb));
        const uint32_t n1 = pack_bf16(fmaf(bf_lo(xrow.y), rt.rstd, nb), fmaf(bf_hi(xrow.y), rt.rstd, nb));
        float gu[4][4];
        #pragma unroll
        for (int i = 0; i < 4; i++) { gu[i][0] = 0.f; gu[i][1] = 0.f; gu[i][2] = 0.f; gu[i][3] = 0.f; }
        #pragma unroll
        for (int ks = 0; ks < 8; ks++) {
            const uint32_t b0 = __shfl_sync(0xffffffffu, n0, 4 * ks + t), b1 = __shfl_sync(0xffffffffu, n1, 4 * ks + t);
            #pragma unroll
            for (int i = 0; i < 4; i++) {
                const uint4& a = fa[(ks >> 1) * 8 + (i >> 1) * 4 + (ks & 1) * 2 + (i & 1)];
                mma_bf16(gu[i], a.x, a.y, a.z, a.w, b0, b1);
            }
        }
        stsf(SB + OFF_PART + (W * 64 + t * 16 + g) * 4, sel4(t, gu[0][0], gu[1][0], gu[2][0], gu[3][0]));
        stsf(SB + OFF_PART + (W * 64 + t * 16 + g + 8) * 4, sel4(t, gu[0][2], gu[1][2], gu[2][2], gu[3][2]));
    }
    named_sync(1, 256);
    TL(0, L, 18);
    {
        float gp[8], up[8];
        #pragma unroll
        for (int i = 0; i < 8; i++) gp[i] = ldsf(SB + OFF_PART + (i * 64 + lane) * 4);
        #pragma unroll
        for (int i = 0; i < 8; i++) up[i] = ldsf(SB + OFF_PART + (i * 64 + 32 + lane) * 4);
        const float gv = bf_round(((gp[0] + gp[1]) + (gp[2] + gp[3])) + ((gp[4] + gp[5]) + (gp[6] + gp[7])));
        const float uv = bf_round(((up[0] + up[1]) + (up[2] + up[3])) + ((up[4] + up[5]) + (up[6] + up[7])));
        const float hv = bf_round(gv * rcp(1.f + ex2(gv * -1.4426950408889634f))) * uv;
        const uint32_t hp = pack_bf16(hv, __shfl_down_sync(0xffffffffu, hv, 1));
        uint32_t hb[4];
        #pragma unroll
        for (int i = 0; i < 4; i++) hb[i] = __shfl_sync(0xffffffffu, hp, 8 * i + 2 * t);
        float y[8][4];
        #pragma unroll
        for (int mb = 0; mb < 8; mb++) {
            y[mb][0] = 0.f; y[mb][1] = 0.f; y[mb][2] = 0.f; y[mb][3] = 0.f;
            #pragma unroll
            for (int ks = 0; ks < 2; ks++) mma_bf16(y[mb], fd[2*mb + ks].x, fd[2*mb + ks].y, fd[2*mb + ks].z, fd[2*mb + ks].w, hb[2 * ks], hb[2 * ks + 1]);
        }
        st_relaxed4_if(&g_ypart[L][min(c, NFC - 1)][tid * 4], make_uint4(not_sent(sel4(t, y[0][0], y[2][0], y[4][0], y[6][0])), not_sent(sel4(t, y[0][2], y[2][2], y[4][2], y[6][2])),
                       not_sent(sel4(t, y[1][0], y[3][0], y[5][0], y[7][0])), not_sent(sel4(t, y[1][2], y[3][2], y[5][2], y[7][2]))), ffn);
    }
    if (L == 0 && DDP == 3) named_arrive(N_DD, 288);
    TL(0, L, 19);
    if (L == 1) {
        if (W == 7) ctr_wait(&g_xc[1][rt.idx >> 8], 32);
        unsigned short* dst = reinterpret_cast<unsigned short*>(out) + (size_t)rt.idx * D_ + ypos_col(c * 8 + (tid & 7));
        asm volatile("" : "+l"(dst));
        const float v = ffn_finish<256>(1, rt, tid, SB + OFF_FE, 1);
        if (tid < 8) asm volatile("st.global.u16 [%0], %1;" :: "l"(dst), "h"((unsigned short)(__float_as_uint(v) >> 16)) : "memory");
        TL(0, L, 20);
    }
}

#define FW0 9
#define RK0 7
#define BAL 1500
#define KW1 4
static_assert(FW0 >= 8 && KW1 >= 3 && KW1 < 7, "buffer reuse");
__device__ __forceinline__ void qkv_fill(const CUtensorMap* tx, const CUtensorMap* tw, uint32_t bar, int st, int k) {
    const uint32_t sa = SB + st * Q_STB;
    mbar_expect_tx(bar, Q_STB);
    tma_load(sa, tx, k * 64, (blockIdx.x >> 4) * 256, bar);
    tma_load3(sa + Q_ABYTES, tw, (blockIdx.x & 15) * 64, k * 64, 0, bar);
}
__device__ __forceinline__ void oproj_fill(const Maps& mp, const char* osrc, int s, int par, int pair, int L, int k) {
    const uint32_t fb = B_OF + 8 * s, sa = SB + o_stage(s);
    mbar_expect_tx(fb, 32768);
    bulk_load(sa, osrc + (par * 16 + pair) * 8192, 16384, fb);
    tma_load5(sa + 16384, &mp.wo, 0, 0, par, pair, blockIdx.x & 14, fb);
}
__device__ __forceinline__ void producer_role(const Maps& mp) {
    const int c = blockIdx.x, mt = c >> 4, nt = c & 15, lane = threadIdx.x & 31;
    #pragma unroll 1
    for (int i = 2; i < 13; i++) tm_prefetch(&mp.xa0 + i);
    #pragma unroll 1
    for (int L = 0; L < 2; L++) {
        const uint32_t rb = L * 32;
        uint32_t st = 0, ph = L;
        #pragma unroll 1
        for (int k = L == 0 ? 3 : 0; k < 16; k++) {
            if (k == 0) { ctr_wait_all(&g_xc[0][mt], 32); fence_async_global(); named_sync(N_GD, 288); }
            if (k == 1) named_sync(N_DD, 288);
            mbar_wait(rb + B_QE + 8 * st, ph);
            TL(k == 3 ? 256 : -1, L, 28);
            qkv_fill(L == 0 ? &mp.xa0 : &mp.xa, &mp.wqkv, rb + B_QF + 8 * st, st, k);
            if (L == 1 && k >= RK0 && k < RK0 + 4) {
                if (k == RK0) mbar_expect_tx(B_SW, 4 * 12288);
                tma_load(SB + OFF_SIDE + (k - RK0) * 12288, &mp.r, c * 24, (k - RK0) * 256, B_SW);
            }
            if (++st == 3) { st = 0; ph ^= 1; }
        }
        mbar_wait(B_KV0, L);
        mbar_arrive_elect(rb + B_AF);
        TL(256, L, 29);
        {
            const int win = nt * 16 + ((mt + 1) & 7);
            mbar_expect_tx(rb + B_AF + 8, KV_WIN);
            #pragma unroll 1
            for (int h = 0; h < 2; h++) {
                ctr_wait_all(&g_kvc[L][0][0] + win, 2 + h);
                fence_async_global();
                bulk_load(SB + A_WIN + h * 16384, g_kv + (size_t)win * KV_WIN + h * 16384, 16384, rb + B_AF + 8);
            }
            TL(256, L, 7);
        }
        st = 2; ph = 1;
        #pragma unroll 1
        for (int w = 2; w < 16; w++) {
            const int win = nt * 16 + (w & 8) + ((mt + w) & 7);
            if (w <= 3 || w == 8) {
                ctr_wait_all(&g_kvc[L][0][0] + (w < 3 ? win : (win & ~7) + (lane & 7)), 3);
                fence_async_global();
            }
            mbar_wait(rb + B_AE + 8 * st, ph);
            mbar_expect_tx(rb + B_AF + 8 * st, KV_WIN);
            bulk_load(SB + st * A_WIN, g_kv + (size_t)win * KV_WIN, KV_WIN, rb + B_AF + 8 * st);
            if (w == KW1 || w == FW0) named_arrive(w == FW0 ? N_FW : N_KV1, 64);
            if (++st == 3) { st = 0; ph ^= 1; }
        }
        ctr_wait_all(&g_oc[L][mt * 2 + (nt & 1)][0][lane & 15], 1);
        fence_async_global();
        const char* osrc = g_o + (size_t)(mt * 2 + (nt & 1)) * 32 * 8192;
        #pragma unroll
        for (int k = 0; k < 4; k++) {
            mbar_wait(k < 2 ? rb + B_AE + 8 + 8 * k : k == 2 ? rb + B_AE : B_QAF, k < 2 ? 0 : k == 2 ? 1 : L);
            oproj_fill(mp, osrc, k, 0, 2 * k, L, k);
        }
        uint32_t ready = 0xFFFFu;
        #pragma unroll 1
        for (int k4 = 1; k4 < 4; k4++) {
            #pragma unroll
            for (int s = 0; s < 4; s++) {
                const int p = k4 * 8 + 2 * s;
                if (!((ready >> p) & 1)) {
                    ready = smem_wait_any(SB + OFF_M + M_ORDY + 4 * L, 1u << p);
                    fence_async_global();
                }
                mbar_wait(B_OE + 8 * s, (k4 - 1) & 1);
                oproj_fill(mp, osrc, s, p >> 4, p & 15, L, k4 * 4 + s);
            }
        }
        if (c < NFC) {
            mbar_expect_tx(B_FL, 5 * 16384);
            mbar_expect_tx(B_FD, 4 * 16384);
            #pragma unroll 1
            for (int i = 3; i < 12; i++) {
                mbar_wait(B_OE + (i < 5 ? 0 : i == 5 ? 8 : i < 9 ? 16 : 24), 1);
                if (i == 8) mbar_wait(B_FL, L);
                TL(i == 9 ? 256 : -1, L, 32);
                ffn_load(mp, c, i, SB + (i < 8 ? gu_piece(i) : OFF_FD + (i - 8) * 16384), i < 8 ? B_FL : B_FD, true);
            }
        }
    }
}

__global__ void __launch_bounds__(384, 1) k_all(const bf16* __restrict__ x0, const bf16* __restrict__ wo, const bf16* __restrict__ w_r, bf16* __restrict__ out,
                                                const __grid_constant__ Maps mp) {
    extern __shared__ __align__(1024) char smem[];
    if (smem_u32(smem) != SB) __trap();
    const int warp = warp_uniform(threadIdx.x >> 5), wg = warp >> 2;
    TL(0, 0, 0);
    {
        const int grp = warp >= 8 ? warp - 8 : warp + 4;
        #pragma unroll
        for (int i = 0; i < 4; i++) mbar_init(BB + grp * 32 + i * 8, grp < 7 ? 1 : grp < 10 ? 2 : 8);
        fence_mbar_init();
    }
    if (warp == 8) {
        #pragma unroll 1
        for (int s = 0; s < 3; s++) qkv_fill(&mp.xa0, &mp.wqkv, B_QF + 8 * s, s, s);
    }
    __syncthreads();
    if (wg == 2) {
        reg_dec<40>();
        if (warp == 8) producer_role(mp);
        else side_role(mp, x0, wo, w_r);
        if (gridDim.y == 2) {
            uint32_t v = threadIdx.x;
            #pragma unroll
            for (int i = 0; i < BAL; i++) asm volatile("fma.rn.f16x2 %0, %0, %0, %0;" : "+r"(v));
            sts32(SB, v);
        }
    } else {
        reg_inc<232>();
        #pragma unroll 1
        for (int L = 0; L < 2; L++) {
            qkv_phase(L, wg);
            attention_phase(L, wg);
            oproj_phase(L, wg, out);
        }
    }
}

typedef CUresult (*EncodeFn)(CUtensorMap*, CUtensorMapDataType, cuuint32_t, void*, const cuuint64_t*, const cuuint64_t*, const cuuint32_t*,
                             const cuuint32_t*, CUtensorMapInterleave, CUtensorMapSwizzle, CUtensorMapL2promotion, CUtensorMapFloatOOBfill);

void make_map(EncodeFn enc, CUtensorMap* tm, const void* ptr, int rank, const cuuint64_t* dims, const cuuint64_t* strides, const cuuint32_t* box, CUtensorMapSwizzle sw) {
    const cuuint32_t es[5] = {1, 1, 1, 1, 1};
    enc(tm, CU_TENSOR_MAP_DATA_TYPE_BFLOAT16, rank, const_cast<void*>(ptr), dims, strides, box, es, CU_TENSOR_MAP_INTERLEAVE_NONE, sw,
        box[0] == 64 ? CU_TENSOR_MAP_L2_PROMOTION_L2_128B : CU_TENSOR_MAP_L2_PROMOTION_NONE, CU_TENSOR_MAP_FLOAT_OOB_FILL_NONE);
}
void make_map2(EncodeFn enc, CUtensorMap* tm, const void* ptr, uint64_t cols, uint64_t rows, uint32_t bc, uint32_t br, CUtensorMapSwizzle sw) {
    const cuuint64_t dims[2] = {cols, rows}, strides[1] = {cols * 2};
    const cuuint32_t box[2] = {bc, br};
    make_map(enc, tm, ptr, 2, dims, strides, box, sw);
}

}

extern "C" void kernel_launch(void* const* d_in, const int* in_sizes, int n_in, void* d_out, int out_size) {
    const bf16* x0 = (const bf16*)d_in[0];
    const bf16* wqkv = (const bf16*)d_in[1];
    const bf16* wo = (const bf16*)d_in[2];
    const bf16* w_r = (const bf16*)d_in[4];
    const bf16* w_gate = (const bf16*)d_in[5];
    const bf16* w_up = (const bf16*)d_in[6];
    const bf16* w_down = (const bf16*)d_in[7];

    EncodeFn enc = nullptr;
    cudaDriverEntryPointQueryResult qr;
    cudaGetDriverEntryPoint("cuTensorMapEncodeTiled", (void**)&enc, cudaEnableDefault, &qr);
    void* p_x;
    cudaGetSymbolAddress(&p_x, g_x);
    Maps mp;
    const CUtensorMapSwizzle S128 = CU_TENSOR_MAP_SWIZZLE_128B;
    make_map2(enc, &mp.x0, x0, D_, S_, 64, 64, S128);
    make_map2(enc, &mp.x, p_x, D_, S_, 64, 64, S128);
    make_map2(enc, &mp.out, d_out, D_, S_, 64, 16, S128);
    make_map2(enc, &mp.xs, p_x, D_, S_, 64, 16, S128);
    make_map2(enc, &mp.xa0, x0, D_, S_, 64, 256, S128);
    make_map2(enc, &mp.xa, p_x, D_, S_, 64, 256, S128);
    make_map2(enc, &mp.w64, wqkv, 3 * D_, D_, 64, 64, S128);
    {
        const cuuint64_t dims[3] = {D_, D_, 3}, strides[2] = {3 * D_ * 2, D_ * 2};
        const cuuint32_t box[3] = {64, 64, 3};
        make_map(enc, &mp.wqkv, wqkv, 3, dims, strides, box, S128);
    }
    make_map2(enc, &mp.r, wqkv, 3 * D_, D_, 24, 256, CU_TENSOR_MAP_SWIZZLE_NONE);
    make_map2(enc, &mp.g, w_gate, FF, D_, 32, 256, CU_TENSOR_MAP_SWIZZLE_64B);
    make_map2(enc, &mp.u, w_up, FF, D_, 32, 256, CU_TENSOR_MAP_SWIZZLE_64B);
    {
        const cuuint64_t dims[5] = {64, 32, 2, 16, 16}, strides[4] = {D_ * 2, 32 * D_ * 2, 64 * D_ * 2, 128};
        const cuuint32_t box[5] = {64, 32, 1, 2, 2};
        make_map(enc, &mp.wo, wo, 5, dims, strides, box, S128);
    }
    {
        const cuuint64_t dims[3] = {64, FF, 16}, strides[2] = {D_ * 2, 128};
        const cuuint32_t box[3] = {64, 32, 4};
        make_map(enc, &mp.d, w_down, 3, dims, strides, box, S128);
    }
    cudaFuncSetAttribute(k_all, cudaFuncAttributeMaxDynamicSharedMemorySize, K_SMEM);
    k_all<<<128, 384, K_SMEM, cudaStreamPerThread>>>(x0, wo, w_r, (bf16*)d_out, mp);
}
```

```cpp
#include <cuda_runtime.h>
#include <cuda_bf16.h>
#include <cuda_fp16.h>
#include <cuda.h>
#include <cudaTypedefs.h>
#include <stdint.h>

namespace {

typedef __nv_bfloat16 bf16;

constexpr int S_ = 2048, D_ = 1024, NH = 32, FF = 3584, NFC = FF / 32;
constexpr float LN_EPS = 1e-5f;
constexpr float QSCALE = 0.17677669529663687f * 1.4426950408889634f;
constexpr uint32_t SENT = 0xFFFFFFFFu;

constexpr int KV_WIN = 32768;
__device__ __align__(1024) char g_kv[NH * 8 * KV_WIN];
__device__ __align__(1024) char g_o[32 * 2 * 16 * 4096];
__device__ __align__(1024) bf16 g_x[S_ * D_];
__device__ float g_csum[8 * 3 * D_];
__device__ float g_wsq[8 * 96];
__device__ float2 g_rs0[S_];
__device__ __align__(128) double g_acc[2][S_][4];
__device__ __align__(128) uint4 g_sums[S_];
__device__ __align__(128) uint32_t g_ypart[2][NFC][D_];
__device__ __align__(128) uint4 g_tab[2][8][16][2];
__device__ __align__(128) uint32_t g_xrow[2][16][D_ / 2];
__device__ __align__(128) uint32_t g_x2row[D_];
__device__ __align__(128) uint32_t g_fix[3 * D_];
__device__ uint32_t g_c0;
__device__ __align__(128) uint32_t g_kvc[2][NH][8];
__device__ __align__(128) uint32_t g_oc[2][16][2][16];
__device__ __align__(128) uint32_t g_xc[2][8];
struct RouteOut { int idx; float r; float mean; float rstd; };

constexpr uint32_t SB = 1024;

__device__ __forceinline__ uint32_t smem_u32(const void* p) { return (uint32_t)__cvta_generic_to_shared(p); }
__device__ __forceinline__ void mbar_arrive(uint32_t bar) { asm volatile("mbarrier.arrive.shared::cta.b64 _, [%0];" :: "r"(bar) : "memory"); }
__device__ __forceinline__ void mbar_wait(uint32_t bar, uint32_t parity) {
    asm volatile("{\n.reg .pred p, q;\n.reg .u32 n;\nmov.u32 n, 0;\n"
                 "LAB_WAIT:\nadd.u32 n, n, 1;\nmbarrier.try_wait.parity.shared::cta.b64 p, [%0], %1;\n"
                 "setp.lt.and.u32 q, n, 0x800000, !p;\n@q bra LAB_WAIT;\n@!p st.shared.u32 [n], n;\n}" :: "r"(bar), "r"(parity) : "memory");
}
__device__ __forceinline__ void mbar_arrive_elect(uint32_t bar) {
    asm volatile("{\n.reg .pred p;\nelect.sync _|p, 0xffffffff;\n@p mbarrier.arrive.shared::cta.b64 _, [%0];\n}" :: "r"(bar) : "memory");
}
__device__ __forceinline__ int tid_now() { int v; asm volatile("mov.u32 %0, %%tid.x;" : "=r"(v)); return v; }
__device__ __forceinline__ int cta_now() { int v; asm volatile("mov.u32 %0, %%ctaid.x;" : "=r"(v)); return v; }
__device__ __forceinline__ int warp_uniform(int v) { return __shfl_sync(0xffffffffu, v, 0); }
__device__ __forceinline__ void fence_mbar_init() { asm volatile("fence.mbarrier_init.release.cluster;" ::: "memory"); }
__device__ __forceinline__ void fence_async_smem() { asm volatile("fence.proxy.async.shared::cta;" ::: "memory"); }
__device__ __forceinline__ void fence_async_global() { asm volatile("fence.proxy.async.global;" ::: "memory"); }
__device__ __forceinline__ void named_sync(int id, int n) { asm volatile("bar.sync %0, %1;" :: "r"(id), "r"(n) : "memory"); }
__device__ __forceinline__ void named_arrive(int id, int n) { asm volatile("bar.arrive %0, %1;" :: "r"(id), "r"(n) : "memory"); }
__device__ __forceinline__ bool named_any(bool p, int id) {
    uint32_t r;
    asm volatile("{\n.reg .pred a, b;\nsetp.ne.u32 a, %1, 0;\nbarrier.cta.red.or.pred b, %2, 128, a;\nselp.u32 %0, 1, 0, b;\n}" : "=r"(r) : "r"((uint32_t)p), "r"(id) : "memory");
    return r != 0;
}
#define ELECT(op) "{\n.reg .pred e;\nelect.sync _|e, 0xffffffff;\n@e " op "\n}"
__device__ __forceinline__ void mbar_init(uint32_t bar, int cnt) { asm volatile(ELECT("mbarrier.init.shared::cta.b64 [%0], %1;") :: "r"(bar), "r"(cnt) : "memory"); }
__device__ __forceinline__ void mbar_expect_tx(uint32_t bar, uint32_t bytes) { asm volatile(ELECT("mbarrier.arrive.expect_tx.shared::cta.b64 _, [%0], %1;") :: "r"(bar), "r"(bytes) : "memory"); }
__device__ __forceinline__ void bulk_load(uint32_t dst, const void* src, uint32_t bytes, uint32_t bar) {
    asm volatile(ELECT("cp.async.bulk.shared::cluster.global.mbarrier::complete_tx::bytes [%0], [%1], %2, [%3];") :: "r"(dst), "l"(src), "r"(bytes), "r"(bar) : "memory");
}
__device__ __forceinline__ void bulk_store(void* dst, uint32_t src, uint32_t bytes) {
    asm volatile(ELECT("cp.async.bulk.global.shared::cta.bulk_group [%0], [%1], %2;") :: "l"(dst), "r"(src), "r"(bytes) : "memory");
}
__device__ __forceinline__ void bulk_commit() { asm volatile("cp.async.bulk.commit_group;" ::: "memory"); }
__device__ __forceinline__ void bulk_wait() { asm volatile("cp.async.bulk.wait_group 0;" ::: "memory"); }
template <int N> __device__ __forceinline__ void bulk_wait_n() { asm volatile("cp.async.bulk.wait_group %0;" :: "n"(N) : "memory"); }
__device__ __forceinline__ void bulk_wait_read() { asm volatile("cp.async.bulk.wait_group.read 0;" ::: "memory"); }
__device__ __forceinline__ void l2_prefetch(const void* src, uint32_t bytes) {
    asm volatile(ELECT("cp.async.bulk.prefetch.L2.global [%0], %1;") :: "l"(src), "r"(bytes) : "memory");
}
__device__ __forceinline__ void tma_load(uint32_t dst, const CUtensorMap* tm, int c0, int c1, uint32_t bar) {
    asm volatile(ELECT("cp.async.bulk.tensor.2d.shared::cluster.global.mbarrier::complete_tx::bytes [%0], [%1, {%3, %4}], [%2];")
                 :: "r"(dst), "l"(tm), "r"(bar), "r"(c0), "r"(c1) : "memory");
}
__device__ __forceinline__ void tma_load3(uint32_t dst, const CUtensorMap* tm, int c0, int c1, int c2, uint32_t bar) {
    asm volatile(ELECT("cp.async.bulk.tensor.3d.shared::cluster.global.mbarrier::complete_tx::bytes [%0], [%1, {%3, %4, %5}], [%2];")
                 :: "r"(dst), "l"(tm), "r"(bar), "r"(c0), "r"(c1), "r"(c2) : "memory");
}
__device__ __forceinline__ uint64_t evict_first() { uint64_t a; asm("createpolicy.fractional.L2::evict_first.b64 %0, 1.0;" : "=l"(a)); return a; }
__device__ __forceinline__ void tma_load_h(uint32_t dst, const CUtensorMap* tm, int c0, int c1, uint32_t bar, bool ef) {
    if (!ef) tma_load(dst, tm, c0, c1, bar);
    else asm volatile(ELECT("cp.async.bulk.tensor.2d.shared::cluster.global.mbarrier::complete_tx::bytes.L2::cache_hint [%0], [%1, {%3, %4}], [%2], %5;")
                      :: "r"(dst), "l"(tm), "r"(bar), "r"(c0), "r"(c1), "l"(evict_first()) : "memory");
}
__device__ __forceinline__ void tma_load3_h(uint32_t dst, const CUtensorMap* tm, int c0, int c1, int c2, uint32_t bar, bool ef) {
    if (!ef) tma_load3(dst, tm, c0, c1, c2, bar);
    else asm volatile(ELECT("cp.async.bulk.tensor.3d.shared::cluster.global.mbarrier::complete_tx::bytes.L2::cache_hint [%0], [%1, {%3, %4, %5}], [%2], %6;")
                      :: "r"(dst), "l"(tm), "r"(bar), "r"(c0), "r"(c1), "r"(c2), "l"(evict_first()) : "memory");
}
__device__ __forceinline__ void tma_load5(uint32_t dst, const CUtensorMap* tm, int c0, int c1, int c2, int c3, int c4, uint32_t bar) {
    asm volatile(ELECT("cp.async.bulk.tensor.5d.shared::cluster.global.mbarrier::complete_tx::bytes [%0], [%1, {%3, %4, %5, %6, %7}], [%2];")
                 :: "r"(dst), "l"(tm), "r"(bar), "r"(c0), "r"(c1), "r"(c2), "r"(c3), "r"(c4) : "memory");
}
__device__ __forceinline__ void tma_store(const CUtensorMap* tm, uint32_t src, int c0, int c1) {
    asm volatile(ELECT("cp.async.bulk.tensor.2d.global.shared::cta.bulk_group [%0, {%2, %3}], [%1];") :: "l"(tm), "r"(src), "r"(c0), "r"(c1) : "memory");
}
__device__ __forceinline__ void tm_prefetch(const CUtensorMap* tm) { asm volatile(ELECT("prefetch.tensormap [%0];") :: "l"(tm) : "memory"); }
__device__ __forceinline__ uint32_t lds32(uint32_t a) { uint32_t v; asm volatile("ld.shared.b32 %0, [%1];" : "=r"(v) : "r"(a) : "memory"); return v; }
__device__ __forceinline__ float ldsf(uint32_t a) { return __uint_as_float(lds32(a)); }
__device__ __forceinline__ float2 lds64f(uint32_t a) { float2 v; asm volatile("ld.shared.v2.f32 {%0, %1}, [%2];" : "=f"(v.x), "=f"(v.y) : "r"(a) : "memory"); return v; }
__device__ __forceinline__ uint4 lds128(uint32_t a) { uint4 v; asm volatile("ld.shared.v4.b32 {%0, %1, %2, %3}, [%4];" : "=r"(v.x), "=r"(v.y), "=r"(v.z), "=r"(v.w) : "r"(a) : "memory"); return v; }
__device__ __forceinline__ void sts32(uint32_t a, uint32_t v) { asm volatile("st.shared.b32 [%0], %1;" :: "r"(a), "r"(v) : "memory"); }
__device__ __forceinline__ void stsf(uint32_t a, float v) { sts32(a, __float_as_uint(v)); }
__device__ __forceinline__ void sts64f(uint32_t a, float x, float y) { asm volatile("st.shared.v2.f32 [%0], {%1, %2};" :: "r"(a), "f"(x), "f"(y) : "memory"); }
__device__ __forceinline__ void sts128(uint32_t a, const uint4& v) { asm volatile("st.shared.v4.b32 [%0], {%1, %2, %3, %4};" :: "r"(a), "r"(v.x), "r"(v.y), "r"(v.z), "r"(v.w) : "memory"); }
__device__ __forceinline__ void stsm4(uint32_t a, uint32_t x, uint32_t y, uint32_t z, uint32_t w) {
    asm volatile("stmatrix.sync.aligned.m8n8.x4.shared.b16 [%0], {%1, %2, %3, %4};" :: "r"(a), "r"(x), "r"(y), "r"(z), "r"(w) : "memory");
}
__device__ __forceinline__ void ldsm4(uint32_t& a0, uint32_t& a1, uint32_t& a2, uint32_t& a3, uint32_t addr) {
    asm volatile("ldmatrix.sync.aligned.m8n8.x4.shared.b16 {%0,%1,%2,%3}, [%4];" : "=r"(a0), "=r"(a1), "=r"(a2), "=r"(a3) : "r"(addr) : "memory");
}
__device__ __forceinline__ void ldsm4t(uint32_t& a0, uint32_t& a1, uint32_t& a2, uint32_t& a3, uint32_t addr) {
    asm volatile("ldmatrix.sync.aligned.m8n8.x4.trans.shared.b16 {%0,%1,%2,%3}, [%4];" : "=r"(a0), "=r"(a1), "=r"(a2), "=r"(a3) : "r"(addr) : "memory");
}
__device__ __forceinline__ void mma_bf16(float (&c)[4], uint32_t a0, uint32_t a1, uint32_t a2, uint32_t a3, uint32_t b0, uint32_t b1) {
    asm("mma.sync.aligned.m16n8k16.row.col.f32.bf16.bf16.f32 {%0,%1,%2,%3}, {%4,%5,%6,%7}, {%8,%9}, {%0,%1,%2,%3};"
        : "+f"(c[0]), "+f"(c[1]), "+f"(c[2]), "+f"(c[3]) : "r"(a0), "r"(a1), "r"(a2), "r"(a3), "r"(b0), "r"(b1));
}
__device__ __forceinline__ void mma_f16(float (&c)[4], uint32_t a0, uint32_t a1, uint32_t a2, uint32_t a3, uint32_t b0, uint32_t b1) {
    asm("mma.sync.aligned.m16n8k16.row.col.f32.f16.f16.f32 {%0,%1,%2,%3}, {%4,%5,%6,%7}, {%8,%9}, {%0,%1,%2,%3};"
        : "+f"(c[0]), "+f"(c[1]), "+f"(c[2]), "+f"(c[3]) : "r"(a0), "r"(a1), "r"(a2), "r"(a3), "r"(b0), "r"(b1));
}
__device__ __forceinline__ uint32_t ld_acquire(const void* p) { uint32_t v; asm volatile("ld.acquire.gpu.global.u32 %0, [%1];" : "=r"(v) : "l"(p) : "memory"); return v; }
__device__ __forceinline__ void sts_release(uint32_t a, uint32_t v) { asm volatile("st.release.cta.shared.u32 [%0], %1;" :: "r"(a), "r"(v) : "memory"); }
__device__ __forceinline__ uint32_t ld_relaxed(const void* p) { uint32_t v; asm volatile("ld.relaxed.gpu.global.u32 %0, [%1];" : "=r"(v) : "l"(p) : "memory"); return v; }
__device__ __forceinline__ uint4 ld_relaxed4(const void* p) {
    uint4 v; asm volatile("ld.relaxed.gpu.global.v4.b32 {%0, %1, %2, %3}, [%4];" : "=r"(v.x), "=r"(v.y), "=r"(v.z), "=r"(v.w) : "l"(p) : "memory"); return v;
}
__device__ __forceinline__ uint2 ld_relaxed2(const void* p) { uint2 v; asm volatile("ld.relaxed.gpu.global.v2.b32 {%0, %1}, [%2];" : "=r"(v.x), "=r"(v.y) : "l"(p) : "memory"); return v; }
__device__ __forceinline__ void st_relaxed(void* p, uint32_t v) { asm volatile("st.relaxed.gpu.global.u32 [%0], %1;" :: "l"(p), "r"(v) : "memory"); }
__device__ __forceinline__ void st_relaxed4_if(void* p, const uint4& v, bool on) {
    asm volatile("{\n.reg .pred q;\nsetp.ne.u32 q, %5, 0;\n@q st.relaxed.gpu.global.v4.b32 [%0], {%1, %2, %3, %4};\n}"
                 :: "l"(p), "r"(v.x), "r"(v.y), "r"(v.z), "r"(v.w), "r"((uint32_t)on) : "memory");
}
__device__ __forceinline__ uint32_t not_sent(float v) { const uint32_t u = __float_as_uint(v); return u == SENT ? 0x7FFFFFFFu : u; }
__device__ __forceinline__ bool has_sent(const uint4& v) { return max(max(v.x, v.y), max(v.z, v.w)) == SENT; }
constexpr uint32_t SPIN_MAX = 1u << 22;
__device__ __forceinline__ void spin_check(uint32_t n) { asm volatile("{\n.reg .pred p;\nsetp.ge.u32 p, %0, %1;\n@p st.global.u32 [%2], %0;\n}" :: "r"(n), "n"(SPIN_MAX), "l"(0ull) : "memory"); }
__device__ __forceinline__ void ctr_arrive(uint32_t* c, uint32_t n = 1) { asm volatile(ELECT("red.release.gpu.global.add.u32 [%0], %1;") :: "l"(c), "r"(n) : "memory"); }
__device__ __forceinline__ void ctr_wait(const uint32_t* c, uint32_t target) {
    asm volatile("{\n.reg .pred p;\n.reg .u32 n, v;\nmov.u32 n, 0;\n"
                 "LAB_WAIT:\nld.acquire.gpu.global.u32 v, [%0];\nsetp.ge.u32 p, v, %1;\n@p bra LAB_DONE;\n"
                 "add.u32 n, n, 1;\nsetp.lt.u32 p, n, 0x400000;\n@p bra LAB_WAIT;\ntrap;\nLAB_DONE:\n}" :: "l"(c), "r"(target) : "memory");
}
__device__ __forceinline__ void ctr_wait_all(const uint32_t* c, uint32_t target) {
    asm volatile("{\n.reg .pred p;\n.reg .u32 n, v;\nmov.u32 n, 0;\n"
                 "LAB_WAIT:\nld.acquire.gpu.global.u32 v, [%0];\nsetp.ge.u32 p, v, %1;\nvote.sync.all.pred p, p, 0xffffffff;\n@p bra.uni LAB_DONE;\n"
                 "add.u32 n, n, 1;\nsetp.lt.u32 p, n, 0x400000;\n@p bra.uni LAB_WAIT;\ntrap;\nLAB_DONE:\n}" :: "l"(c), "r"(target) : "memory");
}
__device__ __forceinline__ uint32_t smem_wait_any(uint32_t a, uint32_t mask) {
    uint32_t v;
    asm volatile("{\n.reg .pred p;\n.reg .u32 n, t;\nmov.u32 n, 0;\n"
                 "LAB_WAIT:\nld.acquire.cta.shared.u32 %0, [%1];\nand.b32 t, %0, %2;\nsetp.ne.u32 p, t, 0;\nvote.sync.all.pred p, p, 0xffffffff;\n@p bra.uni LAB_DONE;\n"
                 "add.u32 n, n, 1;\nsetp.lt.u32 p, n, 0x4000000;\n@p bra.uni LAB_WAIT;\ntrap;\nLAB_DONE:\n}" : "=r"(v) : "r"(a), "r"(mask) : "memory");
    return warp_uniform(v);
}
__device__ __forceinline__ void publish(uint32_t* c, uint32_t n = 1) { bulk_wait(); fence_async_global(); ctr_arrive(c, n); }

__device__ __forceinline__ void wg_fence() { asm volatile("wgmma.fence.sync.aligned;" ::: "memory"); }
__device__ __forceinline__ void wg_commit() { asm volatile("wgmma.commit_group.sync.aligned;" ::: "memory"); }
template <int N> __device__ __forceinline__ void wg_wait() { asm volatile("wgmma.wait_group.sync.aligned %0;" :: "n"(N) : "memory"); }
template <int N> __device__ __forceinline__ void reg_inc() { asm volatile("setmaxnreg.inc.sync.aligned.u32 %0;" :: "n"(N)); }
template <int N> __device__ __forceinline__ void reg_dec() { asm volatile("setmaxnreg.dec.sync.aligned.u32 %0;" :: "n"(N)); }
__host__ __device__ constexpr uint64_t desc_plain(uint32_t addr, uint32_t lbo, uint32_t sbo) {
    return (uint64_t)((addr & 0x3FFFF) >> 4) | ((uint64_t)(lbo >> 4) << 16) | ((uint64_t)(sbo >> 4) << 32);
}
__host__ __device__ constexpr uint64_t desc_sw128(uint32_t addr, uint32_t lbo, uint32_t sbo) { return desc_plain(addr, lbo, sbo) | (1ull << 62); }

__device__ __forceinline__ float ex2(float x) { float y; asm("ex2.approx.ftz.f32 %0, %1;" : "=f"(y) : "f"(x)); return y; }
__device__ __forceinline__ float rcp(float x) { float y; asm("rcp.approx.ftz.f32 %0, %1;" : "=f"(y) : "f"(x)); return y; }
__device__ __forceinline__ float rsq(float x) { float y; asm("rsqrt.approx.ftz.f32 %0, %1;" : "=f"(y) : "f"(x)); return y; }
__device__ __forceinline__ uint32_t pack_bf16(float lo, float hi) { uint32_t r; asm("cvt.rn.bf16x2.f32 %0, %1, %2;" : "=r"(r) : "f"(hi), "f"(lo)); return r; }
__device__ __forceinline__ uint32_t pack_f16(float lo, float hi) { uint32_t r; asm("cvt.rn.f16x2.f32 %0, %1, %2;" : "=r"(r) : "f"(hi), "f"(lo)); return r; }
__device__ __forceinline__ uint32_t round8(uint32_t v) { return (v + 0x00040004u) & 0xFFF8FFF8u; }
__device__ __forceinline__ float bf_lo(uint32_t v) { return __uint_as_float(v << 16); }
__device__ __forceinline__ float bf_hi(uint32_t v) { return __uint_as_float(v & 0xFFFF0000u); }
__device__ __forceinline__ float bf_round(float x) { return __uint_as_float(pack_bf16(0.f, x)); }
__device__ __forceinline__ uint32_t badd2(uint32_t a, uint32_t b) { uint32_t r; asm("add.rn.bf16x2 %0, %1, %2;" : "=r"(r) : "r"(a), "r"(b)); return r; }
__device__ __forceinline__ void h2_unpack(uint32_t v, float& lo, float& hi) {
    asm("{.reg .f16 l, h; mov.b32 {l, h}, %2; cvt.f32.f16 %0, l; cvt.f32.f16 %1, h;}" : "=f"(lo), "=f"(hi) : "r"(v));
}
__device__ __forceinline__ uint32_t add_ln2(uint32_t x, float rstd, float nb) { return badd2(x, pack_bf16(fmaf(bf_lo(x), rstd, nb), fmaf(bf_hi(x), rstd, nb))); }
__device__ __forceinline__ float sel4(int t, float a0, float a1, float a2, float a3) {
    float r;
    asm("{\n.reg .pred p, q;\n.reg .f32 x, y;\nsetp.ne.u32 p, %1, 0;\nsetp.ne.u32 q, %2, 0;\nselp.f32 x, %4, %3, p;\nselp.f32 y, %6, %5, p;\nselp.f32 %0, y, x, q;\n}"
        : "=f"(r) : "r"(t & 1), "r"(t & 2), "f"(a0), "f"(a1), "f"(a2), "f"(a3));
    return r;
}
__device__ __forceinline__ float warp_sum(float v) {
    #pragma unroll
    for (int o = 16; o > 0; o >>= 1) v += __shfl_xor_sync(0xffffffffu, v, o);
    return v;
}
__device__ __forceinline__ uint32_t redux_or(uint32_t v) { uint32_t r; asm volatile("redux.sync.or.b32 %0, %1, 0xffffffff;" : "=r"(r) : "r"(v)); return r; }
__device__ __forceinline__ uint32_t redux_max(uint32_t v) { uint32_t r; asm volatile("redux.sync.max.u32 %0, %1, 0xffffffff;" : "=r"(r) : "r"(v)); return r; }
__device__ __forceinline__ uint32_t redux_min(uint32_t v) { uint32_t r; asm volatile("redux.sync.min.u32 %0, %1, 0xffffffff;" : "=r"(r) : "r"(v)); return r; }

#define TL(T, L, i)

__device__ __forceinline__ void wg_gemm_n128(float (&d)[64], uint64_t desca, uint64_t desc) {
    asm volatile("{\n.reg .pred p;\nsetp.ne.b32 p, 1, 0;\n"
        "wgmma.mma_async.sync.aligned.m64n128k16.f32.bf16.bf16 "
        "{%0,%1,%2,%3,%4,%5,%6,%7,%8,%9,%10,%11,%12,%13,%14,%15,%16,%17,%18,%19,%20,%21,%22,%23,%24,%25,%26,%27,%28,%29,%30,%31,%32,%33,%34,%35,%36,%37,%38,%39,%40,%41,%42,%43,%44,%45,%46,%47,%48,%49,%50,%51,%52,%53,%54,%55,%56,%57,%58,%59,%60,%61,%62,%63}, "
        "%64, %65, p, 1, 1, 0, 1;\n}\n"
        : "+f"(d[0]), "+f"(d[1]), "+f"(d[2]), "+f"(d[3]), "+f"(d[4]), "+f"(d[5]), "+f"(d[6]), "+f"(d[7]),
          "+f"(d[8]), "+f"(d[9]), "+f"(d[10]), "+f"(d[11]), "+f"(d[12]), "+f"(d[13]), "+f"(d[14]), "+f"(d[15]),
          "+f"(d[16]), "+f"(d[17]), "+f"(d[18]), "+f"(d[19]), "+f"(d[20]), "+f"(d[21]), "+f"(d[22]), "+f"(d[23]),
          "+f"(d[24]), "+f"(d[25]), "+f"(d[26]), "+f"(d[27]), "+f"(d[28]), "+f"(d[29]), "+f"(d[30]), "+f"(d[31]),
          "+f"(d[32]), "+f"(d[33]), "+f"(d[34]), "+f"(d[35]), "+f"(d[36]), "+f"(d[37]), "+f"(d[38]), "+f"(d[39]),
          "+f"(d[40]), "+f"(d[41]), "+f"(d[42]), "+f"(d[43]), "+f"(d[44]), "+f"(d[45]), "+f"(d[46]), "+f"(d[47]),
          "+f"(d[48]), "+f"(d[49]), "+f"(d[50]), "+f"(d[51]), "+f"(d[52]), "+f"(d[53]), "+f"(d[54]), "+f"(d[55]),
          "+f"(d[56]), "+f"(d[57]), "+f"(d[58]), "+f"(d[59]), "+f"(d[60]), "+f"(d[61]), "+f"(d[62]), "+f"(d[63])
        : "l"(desca), "l"(desc));
}
__device__ __forceinline__ void wg_gemm_n128_init(float (&d)[64], uint64_t desca, uint64_t desc) {
    asm volatile("{\n.reg .pred p;\nsetp.ne.b32 p, 0, 0;\n"
        "wgmma.mma_async.sync.aligned.m64n128k16.f32.bf16.bf16 "
        "{%0,%1,%2,%3,%4,%5,%6,%7,%8,%9,%10,%11,%12,%13,%14,%15,%16,%17,%18,%19,%20,%21,%22,%23,%24,%25,%26,%27,%28,%29,%30,%31,%32,%33,%34,%35,%36,%37,%38,%39,%40,%41,%42,%43,%44,%45,%46,%47,%48,%49,%50,%51,%52,%53,%54,%55,%56,%57,%58,%59,%60,%61,%62,%63}, "
        "%64, %65, p, 1, 1, 0, 1;\n}\n"
        : "=f"(d[0]), "=f"(d[1]), "=f"(d[2]), "=f"(d[3]), "=f"(d[4]), "=f"(d[5]), "=f"(d[6]), "=f"(d[7]),
          "=f"(d[8]), "=f"(d[9]), "=f"(d[10]), "=f"(d[11]), "=f"(d[12]), "=f"(d[13]), "=f"(d[14]), "=f"(d[15]),
          "=f"(d[16]), "=f"(d[17]), "=f"(d[18]), "=f"(d[19]), "=f"(d[20]), "=f"(d[21]), "=f"(d[22]), "=f"(d[23]),
          "=f"(d[24]), "=f"(d[25]), "=f"(d[26]), "=f"(d[27]), "=f"(d[28]), "=f"(d[29]), "=f"(d[30]), "=f"(d[31]),
          "=f"(d[32]), "=f"(d[33]), "=f"(d[34]), "=f"(d[35]), "=f"(d[36]), "=f"(d[37]), "=f"(d[38]), "=f"(d[39]),
          "=f"(d[40]), "=f"(d[41]), "=f"(d[42]), "=f"(d[43]), "=f"(d[44]), "=f"(d[45]), "=f"(d[46]), "=f"(d[47]),
          "=f"(d[48]), "=f"(d[49]), "=f"(d[50]), "=f"(d[51]), "=f"(d[52]), "=f"(d[53]), "=f"(d[54]), "=f"(d[55]),
          "=f"(d[56]), "=f"(d[57]), "=f"(d[58]), "=f"(d[59]), "=f"(d[60]), "=f"(d[61]), "=f"(d[62]), "=f"(d[63])
        : "l"(desca), "l"(desc));
}
__device__ __forceinline__ void wg_gemm_n192(float (&d)[96], uint64_t desca, uint64_t desc) {
    asm volatile("{\n.reg .pred p;\nsetp.ne.b32 p, 1, 0;\n"
        "wgmma.mma_async.sync.aligned.m64n192k16.f32.bf16.bf16 "
        "{%0,%1,%2,%3,%4,%5,%6,%7,%8,%9,%10,%11,%12,%13,%14,%15,%16,%17,%18,%19,%20,%21,%22,%23,%24,%25,%26,%27,%28,%29,%30,%31,%32,%33,%34,%35,%36,%37,%38,%39,%40,%41,%42,%43,%44,%45,%46,%47,%48,%49,%50,%51,%52,%53,%54,%55,%56,%57,%58,%59,%60,%61,%62,%63,%64,%65,%66,%67,%68,%69,%70,%71,%72,%73,%74,%75,%76,%77,%78,%79,%80,%81,%82,%83,%84,%85,%86,%87,%88,%89,%90,%91,%92,%93,%94,%95}, "
        "%96, %97, p, 1, 1, 0, 1;\n}\n"
        : "+f"(d[0]), "+f"(d[1]), "+f"(d[2]), "+f"(d[3]), "+f"(d[4]), "+f"(d[5]), "+f"(d[6]), "+f"(d[7]),
          "+f"(d[8]), "+f"(d[9]), "+f"(d[10]), "+f"(d[11]), "+f"(d[12]), "+f"(d[13]), "+f"(d[14]), "+f"(d[15]),
          "+f"(d[16]), "+f"(d[17]), "+f"(d[18]), "+f"(d[19]), "+f"(d[20]), "+f"(d[21]), "+f"(d[22]), "+f"(d[23]),
          "+f"(d[24]), "+f"(d[25]), "+f"(d[26]), "+f"(d[27]), "+f"(d[28]), "+f"(d[29]), "+f"(d[30]), "+f"(d[31]),
          "+f"(d[32]), "+f"(d[33]), "+f"(d[34]), "+f"(d[35]), "+f"(d[36]), "+f"(d[37]), "+f"(d[38]), "+f"(d[39]),
          "+f"(d[40]), "+f"(d[41]), "+f"(d[42]), "+f"(d[43]), "+f"(d[44]), "+f"(d[45]), "+f"(d[46]), "+f"(d[47]),
          "+f"(d[48]), "+f"(d[49]), "+f"(d[50]), "+f"(d[51]), "+f"(d[52]), "+f"(d[53]), "+f"(d[54]), "+f"(d[55]),
          "+f"(d[56]), "+f"(d[57]), "+f"(d[58]), "+f"(d[59]), "+f"(d[60]), "+f"(d[61]), "+f"(d[62]), "+f"(d[63]),
          "+f"(d[64]), "+f"(d[65]), "+f"(d[66]), "+f"(d[67]), "+f"(d[68]), "+f"(d[69]), "+f"(d[70]), "+f"(d[71]),
          "+f"(d[72]), "+f"(d[73]), "+f"(d[74]), "+f"(d[75]), "+f"(d[76]), "+f"(d[77]), "+f"(d[78]), "+f"(d[79]),
          "+f"(d[80]), "+f"(d[81]), "+f"(d[82]), "+f"(d[83]), "+f"(d[84]), "+f"(d[85]), "+f"(d[86]), "+f"(d[87]),
          "+f"(d[88]), "+f"(d[89]), "+f"(d[90]), "+f"(d[91]), "+f"(d[92]), "+f"(d[93]), "+f"(d[94]), "+f"(d[95])
        : "l"(desca), "l"(desc));
}
__device__ __forceinline__ void wg_gemm_n192_init(float (&d)[96], uint64_t desca, uint64_t desc) {
    asm volatile("{\n.reg .pred p;\nsetp.ne.b32 p, 0, 0;\n"
        "wgmma.mma_async.sync.aligned.m64n192k16.f32.bf16.bf16 "
        "{%0,%1,%2,%3,%4,%5,%6,%7,%8,%9,%10,%11,%12,%13,%14,%15,%16,%17,%18,%19,%20,%21,%22,%23,%24,%25,%26,%27,%28,%29,%30,%31,%32,%33,%34,%35,%36,%37,%38,%39,%40,%41,%42,%43,%44,%45,%46,%47,%48,%49,%50,%51,%52,%53,%54,%55,%56,%57,%58,%59,%60,%61,%62,%63,%64,%65,%66,%67,%68,%69,%70,%71,%72,%73,%74,%75,%76,%77,%78,%79,%80,%81,%82,%83,%84,%85,%86,%87,%88,%89,%90,%91,%92,%93,%94,%95}, "
        "%96, %97, p, 1, 1, 0, 1;\n}\n"
        : "=f"(d[0]), "=f"(d[1]), "=f"(d[2]), "=f"(d[3]), "=f"(d[4]), "=f"(d[5]), "=f"(d[6]), "=f"(d[7]),
          "=f"(d[8]), "=f"(d[9]), "=f"(d[10]), "=f"(d[11]), "=f"(d[12]), "=f"(d[13]), "=f"(d[14]), "=f"(d[15]),
          "=f"(d[16]), "=f"(d[17]), "=f"(d[18]), "=f"(d[19]), "=f"(d[20]), "=f"(d[21]), "=f"(d[22]), "=f"(d[23]),
          "=f"(d[24]), "=f"(d[25]), "=f"(d[26]), "=f"(d[27]), "=f"(d[28]), "=f"(d[29]), "=f"(d[30]), "=f"(d[31]),
          "=f"(d[32]), "=f"(d[33]), "=f"(d[34]), "=f"(d[35]), "=f"(d[36]), "=f"(d[37]), "=f"(d[38]), "=f"(d[39]),
          "=f"(d[40]), "=f"(d[41]), "=f"(d[42]), "=f"(d[43]), "=f"(d[44]), "=f"(d[45]), "=f"(d[46]), "=f"(d[47]),
          "=f"(d[48]), "=f"(d[49]), "=f"(d[50]), "=f"(d[51]), "=f"(d[52]), "=f"(d[53]), "=f"(d[54]), "=f"(d[55]),
          "=f"(d[56]), "=f"(d[57]), "=f"(d[58]), "=f"(d[59]), "=f"(d[60]), "=f"(d[61]), "=f"(d[62]), "=f"(d[63]),
          "=f"(d[64]), "=f"(d[65]), "=f"(d[66]), "=f"(d[67]), "=f"(d[68]), "=f"(d[69]), "=f"(d[70]), "=f"(d[71]),
          "=f"(d[72]), "=f"(d[73]), "=f"(d[74]), "=f"(d[75]), "=f"(d[76]), "=f"(d[77]), "=f"(d[78]), "=f"(d[79]),
          "=f"(d[80]), "=f"(d[81]), "=f"(d[82]), "=f"(d[83]), "=f"(d[84]), "=f"(d[85]), "=f"(d[86]), "=f"(d[87]),
          "=f"(d[88]), "=f"(d[89]), "=f"(d[90]), "=f"(d[91]), "=f"(d[92]), "=f"(d[93]), "=f"(d[94]), "=f"(d[95])
        : "l"(desca), "l"(desc));
}
__device__ __forceinline__ void wg_qk_init(uint32_t (&d)[32], uint32_t a0, uint32_t a1, uint32_t a2, uint32_t a3, uint64_t desc) {
    asm volatile("{\n.reg .pred p;\nsetp.ne.b32 p, 0, 0;\n"
        "wgmma.mma_async.sync.aligned.m64n128k16.f16.f16.f16 "
        "{%0,%1,%2,%3,%4,%5,%6,%7,%8,%9,%10,%11,%12,%13,%14,%15,%16,%17,%18,%19,%20,%21,%22,%23,%24,%25,%26,%27,%28,%29,%30,%31}, "
        "{%32,%33,%34,%35}, %36, p, 1, 1, 0;\n}\n"
        : "=r"(d[0]), "=r"(d[1]), "=r"(d[2]), "=r"(d[3]), "=r"(d[4]), "=r"(d[5]), "=r"(d[6]), "=r"(d[7]),
          "=r"(d[8]), "=r"(d[9]), "=r"(d[10]), "=r"(d[11]), "=r"(d[12]), "=r"(d[13]), "=r"(d[14]), "=r"(d[15]),
          "=r"(d[16]), "=r"(d[17]), "=r"(d[18]), "=r"(d[19]), "=r"(d[20]), "=r"(d[21]), "=r"(d[22]), "=r"(d[23]),
          "=r"(d[24]), "=r"(d[25]), "=r"(d[26]), "=r"(d[27]), "=r"(d[28]), "=r"(d[29]), "=r"(d[30]), "=r"(d[31])
        : "r"(a0), "r"(a1), "r"(a2), "r"(a3), "l"(desc));
}
__device__ __forceinline__ void wg_qk_acc(uint32_t (&d)[32], uint64_t desca, uint64_t desc) {
    asm volatile("{\n.reg .pred p;\nsetp.ne.b32 p, 1, 0;\n"
        "wgmma.mma_async.sync.aligned.m64n128k16.f16.f16.f16 "
        "{%0,%1,%2,%3,%4,%5,%6,%7,%8,%9,%10,%11,%12,%13,%14,%15,%16,%17,%18,%19,%20,%21,%22,%23,%24,%25,%26,%27,%28,%29,%30,%31}, "
        "%32, %33, p, 1, 1, 0, 0;\n}\n"
        : "+r"(d[0]), "+r"(d[1]), "+r"(d[2]), "+r"(d[3]), "+r"(d[4]), "+r"(d[5]), "+r"(d[6]), "+r"(d[7]),
          "+r"(d[8]), "+r"(d[9]), "+r"(d[10]), "+r"(d[11]), "+r"(d[12]), "+r"(d[13]), "+r"(d[14]), "+r"(d[15]),
          "+r"(d[16]), "+r"(d[17]), "+r"(d[18]), "+r"(d[19]), "+r"(d[20]), "+r"(d[21]), "+r"(d[22]), "+r"(d[23]),
          "+r"(d[24]), "+r"(d[25]), "+r"(d[26]), "+r"(d[27]), "+r"(d[28]), "+r"(d[29]), "+r"(d[30]), "+r"(d[31])
        : "l"(desca), "l"(desc));
}
__device__ __forceinline__ void wg_pv_init(uint32_t (&d)[10], uint32_t a0, uint32_t a1, uint32_t a2, uint32_t a3, uint64_t desc) {
    asm volatile("{\n.reg .pred p;\nsetp.ne.b32 p, 0, 0;\n"
        "wgmma.mma_async.sync.aligned.m64n40k16.f16.f16.f16 "
        "{%0,%1,%2,%3,%4,%5,%6,%7,%8,%9}, "
        "{%10,%11,%12,%13}, %14, p, 1, 1, 1;\n}\n"
        : "=r"(d[0]), "=r"(d[1]), "=r"(d[2]), "=r"(d[3]), "=r"(d[4]), "=r"(d[5]), "=r"(d[6]), "=r"(d[7]),
          "=r"(d[8]), "=r"(d[9])
        : "r"(a0), "r"(a1), "r"(a2), "r"(a3), "l"(desc));
}
__device__ __forceinline__ void wg_pv_acc(uint32_t (&d)[10], uint32_t a0, uint32_t a1, uint32_t a2, uint32_t a3, uint64_t desc) {
    asm volatile("{\n.reg .pred p;\nsetp.ne.b32 p, 1, 0;\n"
        "wgmma.mma_async.sync.aligned.m64n40k16.f16.f16.f16 "
        "{%0,%1,%2,%3,%4,%5,%6,%7,%8,%9}, "
        "{%10,%11,%12,%13}, %14, p, 1, 1, 1;\n}\n"
        : "+r"(d[0]), "+r"(d[1]), "+r"(d[2]), "+r"(d[3]), "+r"(d[4]), "+r"(d[5]), "+r"(d[6]), "+r"(d[7]),
          "+r"(d[8]), "+r"(d[9])
        : "r"(a0), "r"(a1), "r"(a2), "r"(a3), "l"(desc));
}

constexpr int Q_ABYTES = 256 * 64 * 2, Q_STB = Q_ABYTES + 192 * 64 * 2;
constexpr int OFF_SIDE = 3 * Q_STB;
constexpr int OFF_XS = OFF_SIDE + 49152;
constexpr int OFF_CS = OFF_XS + 4096;
constexpr int OFF_RC = OFF_CS + 768;
constexpr int OFF_FIX = OFF_RC + 2048;
constexpr int A_WIN = KV_WIN + 4096;
constexpr int OFF_QA = 3 * A_WIN;
constexpr int OFF_LC = OFF_QA + 32768;
constexpr int OFF_FE = 147456;
constexpr int OFF_XT = 196608;
__host__ __device__ constexpr uint32_t o_stage(uint32_t s) { return s == 3 ? OFF_QA : s == 2 ? 0 : (s + 1) * A_WIN; }
__host__ __device__ constexpr uint32_t gu_piece(uint32_t i) { return i < 3 ? OFF_FE + i * 16384 : i < 6 ? (i - 1) * 16384 : (i - 6) * 16384; }
constexpr int OFF_FD = 5 * 16384;
constexpr int OFF_BAR = OFF_XT + 32768;
constexpr int OFF_PART = OFF_BAR + 384;
constexpr int OFF_RED = OFF_PART + 2048;
constexpr int OFF_RT = OFF_RED + 96;
constexpr int OFF_M = OFF_RT + 144;
constexpr int OFF_WR = OFF_M + 72;
constexpr int K_SMEM = OFF_WR + 264;
static_assert(K_SMEM <= 232448 && OFF_FIX + 768 <= OFF_BAR && OFF_QA + 32768 <= OFF_FE, "smem");
constexpr uint32_t CH_OK = 0x38003800u;
constexpr int M_SC = 0,
              M_IVS = 24,
              M_ISC = 32,
              M_OK = 40,
              M_WS = 48,
              M_RIDX = 60,
              M_ORDY = 64;
constexpr uint32_t BB = SB + OFF_BAR;
constexpr uint32_t B_QF = BB, B_EPI = BB + 24, B_RES2 = BB + 56, B_AF = BB + 64, B_RES = BB + 120, B_OF = BB + 128,
                   B_FE = BB + 160, B_FL = BB + 168, B_FD = BB + 184, B_PR = BB + 192, B_FW = B_PR, B_SW = BB + 216,
                   B_QE = BB + 224, B_QAF = BB + 248, B_OE = BB + 288, B_AE = BB + 320, B_K0 = BB + 344, B_KV0 = BB + 376;

constexpr int N_OST = 5, N_XST = 9, N_RT = 11, N_KV1 = 12, N_FW = 13, N_GD = 14, N_DD = 15;

struct Maps { CUtensorMap xa0, wqkv, xa, x0, x, out, w64, wo, r, g, u, d, xs; };

__device__ __forceinline__ float2 ln_coef(const uint4& s) {
    const float mean = __uint_as_float(s.x) * (1.f / D_);
    return make_float2(rsq(fmaxf(fmaf(-mean, mean, fmaf(__uint_as_float(s.y), 1.f / D_, LN_EPS)), LN_EPS)), mean);
}
__device__ __forceinline__ uint32_t order_bits(float r) { const uint32_t u = __float_as_uint(r); return (u & 0x80000000u) ? ~u : (u | 0x80000000u); }
__device__ __forceinline__ uint4 warp_best(const uint4& e) {
    const uint32_t m = redux_max(e.x), row = redux_min(e.x == m ? e.y : 0x7FFFFFFFu);
    const int src = __ffs(__ballot_sync(0xffffffffu, e.y == row)) - 1;
    return make_uint4(m, row, __shfl_sync(0xffffffffu, e.z, src), __shfl_sync(0xffffffffu, e.w, src));
}
__device__ __forceinline__ RouteOut route_out(const uint4& e) {
    RouteOut rt;
    rt.idx = e.y; rt.r = __uint_as_float((e.x & 0x80000000u) ? e.x & 0x7FFFFFFFu : ~e.x); rt.mean = __uint_as_float(e.z); rt.rstd = __uint_as_float(e.w);
    return rt;
}

__device__ __forceinline__ void prep_work(const bf16* __restrict__ x0, const CUtensorMap* tmW, int t) {
    const int c = blockIdx.x, lane = t & 31, warp = warp_uniform(t >> 5);
    const int ki = c >> 4, n = c & 15;
    constexpr uint32_t red = SB + OFF_SIDE, xs = red + 4096;
    if (warp == 0) {
        mbar_expect_tx(B_PR, 32768);
        bulk_load(xs, x0 + (size_t)c * 16 * D_, 32768, B_PR);
        mbar_expect_tx(B_PR + 8, 16384);
        tma_load(xs + 32768, tmW, 2 * D_ + n * 64, ki * 128, B_PR + 8);
        tma_load(xs + 32768 + 8192, tmW, 2 * D_ + n * 64, ki * 128 + 64, B_PR + 8);
    }
    const uint4 sent = make_uint4(SENT, SENT, SENT, SENT);
    for (int i = t; i < 2 * NFC * 2; i += 96) reinterpret_cast<uint4*>(&g_ypart[0][0][0])[c * (2 * NFC * 2) + i] = sent;
    if (t < 64) reinterpret_cast<uint4*>(&g_acc[0][0][0])[c * 64 + t] = make_uint4(0u, 0u, 0u, 0u);
    if (t >= 64 && t < 80) g_sums[c * 16 + t - 64] = sent;
    if (t < 2) reinterpret_cast<uint4*>(g_x2row)[c * 2 + t] = sent;
    else if (t < 8) reinterpret_cast<uint4*>(g_fix)[c * 6 + t - 2] = sent;
    else if (t < 12) (&g_kvc[0][0][0])[c * 4 + t - 8] = 0u;
    else if (t >= 24 && t < 32) (&g_oc[0][0][0][0])[c * 8 + t - 24] = 0u;
    else if (t == 13 && c < 16) (&g_xc[0][0])[c] = 0u;
    else if (t >= 16 && t < 20) (&g_tab[0][0][0][0])[c * 4 + t - 16] = sent;
    else if (t >= 32 && t < 64) reinterpret_cast<uint4*>(&g_xrow[0][0][0])[c * 32 + t - 32] = sent;
    mbar_wait(B_PR, 0);
    #pragma unroll 1
    for (int r = warp; r < 16; r += 3) {
        float s = 0.f, q = 0.f;
        #pragma unroll
        for (int i = 0; i < 4; i++) {
            const uint4 u = lds128(xs + r * 2048 + (lane + 32 * i) * 16);
            const float f[8] = {bf_lo(u.x), bf_hi(u.x), bf_lo(u.y), bf_hi(u.y), bf_lo(u.z), bf_hi(u.z), bf_lo(u.w), bf_hi(u.w)};
            #pragma unroll
            for (int e = 0; e < 8; e++) { s += f[e]; q = fmaf(f[e], f[e], q); }
        }
        #pragma unroll
        for (int o = 16; o > 0; o >>= 1) { s += __shfl_xor_sync(0xffffffffu, s, o); q += __shfl_xor_sync(0xffffffffu, q, o); }
        const float mean = s * (1.f / D_);
        const float var = fmaxf(q * (1.f / D_) - mean * mean, 0.f);
        if (lane == 0) g_rs0[c * 16 + r] = make_float2(rsqrtf(var + LN_EPS), mean);
    }
    named_sync(2, 96);
    if (warp == 0) {
        mbar_expect_tx(B_PR + 16, 32768);
        #pragma unroll
        for (int b = 0; b < 4; b++) tma_load(xs + b * 8192, tmW, (b >> 1) * D_ + n * 64, ki * 128 + (b & 1) * 64, B_PR + 16);
    }
    const int j = t & 7, rg = t >> 3;
    #pragma unroll 1
    for (int blk = 0; blk < 3; blk++) {
        const int type = blk == 0 ? 2 : blk - 1;
        const uint32_t wb = xs + type * 16384;
        if (blk < 2) mbar_wait(B_PR + 8 + 8 * blk, 0);
        float cs[8];
        uint32_t z2[4] = {0u, 0u, 0u, 0u};
        #pragma unroll
        for (int i = 0; i < 8; i++) cs[i] = 0.f;
        #pragma unroll 4
        for (int r = rg; r < 128; r += 12) {
            const uint4 u = lds128(wb + r * 128 + ((j ^ (r & 7)) << 4));
            cs[0] += bf_lo(u.x); cs[1] += bf_hi(u.x); cs[2] += bf_lo(u.y); cs[3] += bf_hi(u.y);
            cs[4] += bf_lo(u.z); cs[5] += bf_hi(u.z); cs[6] += bf_lo(u.w); cs[7] += bf_hi(u.w);
            asm("fma.rn.bf16x2 %0, %1, %1, %0;" : "+r"(z2[0]) : "r"(u.x));
            asm("fma.rn.bf16x2 %0, %1, %1, %0;" : "+r"(z2[1]) : "r"(u.y));
            asm("fma.rn.bf16x2 %0, %1, %1, %0;" : "+r"(z2[2]) : "r"(u.z));
            asm("fma.rn.bf16x2 %0, %1, %1, %0;" : "+r"(z2[3]) : "r"(u.w));
        }
        #pragma unroll
        for (int i = 0; i < 8; i++) { cs[i] += __shfl_xor_sync(0xffffffffu, cs[i], 8); cs[i] += __shfl_xor_sync(0xffffffffu, cs[i], 16); }
        float z = ((bf_lo(z2[0]) + bf_hi(z2[0])) + (bf_lo(z2[1]) + bf_hi(z2[1]))) + ((bf_lo(z2[2]) + bf_hi(z2[2])) + (bf_lo(z2[3]) + bf_hi(z2[3])));
        z += __shfl_xor_sync(0xffffffffu, z, 1); z += __shfl_xor_sync(0xffffffffu, z, 2);
        z += __shfl_xor_sync(0xffffffffu, z, 8); z += __shfl_xor_sync(0xffffffffu, z, 16);
        if (lane < 8) {
            #pragma unroll
            for (int i = 0; i < 8; i++) stsf(red + (warp * 200 + type * 64 + j * 8 + i) * 4, cs[i]);
            if ((lane & 3) == 0) stsf(red + (warp * 200 + 192 + type * 2 + (lane >> 2)) * 4, z);
        }
    }
    named_sync(2, 96);
    for (int i = t; i < 198; i += 96) {
        const float v = ldsf(red + i * 4) + ldsf(red + (200 + i) * 4) + ldsf(red + (400 + i) * 4);
        if (i < 192) g_csum[ki * (3 * D_) + (i >> 6) * D_ + n * 64 + (i & 63)] = v;
        else g_wsq[ki * 96 + ((i - 192) >> 1) * 32 + n * 2 + (i & 1)] = v;
    }
    named_sync(2, 96);
    if (warp == 0) { ctr_arrive(&g_c0); ctr_wait(&g_c0, 128); }
    named_sync(2, 96);
}

__device__ __forceinline__ float pow2_inv(float b) {
    const int e = min(max((int)(__float_as_uint(b) >> 23) + 1, 20), 234);
    return __uint_as_float((uint32_t)(254 - e) << 23);
}
__device__ __forceinline__ void epi_inputs(int L) {
    const int t = tid_now() - 288, mt = cta_now() >> 4, nt = cta_now() & 15;
    float p[2][8], r0[3], r1[3];
    #pragma unroll
    for (int k = 0; k < 2; k++)
        #pragma unroll
        for (int q = 0; q < 8; q++) p[k][q] = __ldcg(g_csum + q * (3 * D_) + ((t + 96 * k) >> 6) * D_ + nt * 64 + ((t + 96 * k) & 63));
    #pragma unroll
    for (int k = 0; k < 2; k++) stsf(SB + OFF_CS + (t + 96 * k) * 4, ((p[k][0] + p[k][1]) + (p[k][2] + p[k][3])) + ((p[k][4] + p[k][5]) + (p[k][6] + p[k][7])));
    bool wait;
    uint32_t n = 0;
    do {
        wait = false;
        #pragma unroll
        for (int k = 0; k < 3; k++) {
            const int row = mt * 256 + min(t + 96 * k, 255);
            if (L == 0) { const float2 s = __ldcg(&g_rs0[row]); r0[k] = s.x; r1[k] = s.y; }
            else { const uint4 s = ld_relaxed4(&g_sums[row]); r0[k] = __uint_as_float(s.x); r1[k] = __uint_as_float(s.y); wait = wait || has_sent(s); }
        }
    } while (wait && ++n < SPIN_MAX);
    #pragma unroll
    for (int k = 0; k < 3; k++) {
        if (L != 0) {
            const float mean = r0[k] * (1.f / D_);
            const float var = fmaxf(r1[k] * (1.f / D_) - mean * mean, 0.f);
            const float a = 1.f + rsqrtf(var + LN_EPS);
            r0[k] = a * rsqrtf(a * a * var + LN_EPS); r1[k] = mean;
        }
        if (t + 96 * k < 256) sts64f(SB + OFF_RC + (t + 96 * k) * 8, r0[k], r1[k]);
    }
    if (L == 0 && t < 32) {
        float z = 0.f;
        if (t < 6) {
            #pragma unroll
            for (int q = 0; q < 8; q++) z += __ldcg(g_wsq + q * 96 + (t >> 1) * 32 + nt * 2 + (t & 1));
        }
        const float b = sqrtf(z) * (t < 2 ? 34.f * QSCALE : 34.f);
        const float sc = t < 4 ? fminf(pow2_inv(b) * 32768.f, 1.f) : pow2_inv(b);
        const float bk = __shfl_down_sync(0xffffffffu, b, 2), sk = __shfl_down_sync(0xffffffffu, sc, 2);
        if (t < 6) stsf(SB + OFF_M + M_SC + t * 4, t < 2 ? sc * QSCALE : sc);
        if (t < 2) { stsf(SB + OFF_M + M_ISC + t * 4, 1.f / (sc * sk)); sts32(SB + OFF_M + M_OK + t * 4, sc == 1.f && sk == 1.f && b * bk < 60000.f ? CH_OK : 0u); }
        if (t == 4 || t == 5) stsf(SB + OFF_M + M_IVS + (t - 4) * 4, 1.f / sc);
    }
}

__device__ __forceinline__ int ypos_col(int p) { return (p >> 7) * 128 + ((p >> 1) & 7) * 16 + (p & 1) * 8 + ((p >> 4) & 7); }

template <int NT>
__device__ __forceinline__ float ffn_finish(int L, const RouteOut& rt, int t, uint32_t red, int bid) {
    constexpr int NL = (2 * NFC + NT - 1) / NT;
    const int c = cta_now(), col = ypos_col(c * 8 + (t & 7));
    const uint32_t* src = &g_ypart[L][t >> 1][c * 8 + (t & 1) * 4];
    uint32_t n = 0, xp;
    do { xp = ld_relaxed(&g_xrow[L][rt.idx >> 7][((col >> 5) & 7) * 64 + (col >> 8) * 16 + (col & 6) * 2 + ((col >> 3) & 3)]); } while (xp == SENT && ++n < SPIN_MAX);
    uint4 v[NL];
    #pragma unroll
    for (int i = 0; i < NL; i++) v[i] = t + NT * i < 2 * NFC ? ld_relaxed4(src + i * (NT / 2) * D_) : make_uint4(0u, 0u, 0u, 0u);
    const float xv = (col & 1) ? bf_hi(xp) : bf_lo(xp);
    float rsel = bf_round(rcp(1.f + ex2(bf_round(rt.r) * -1.4426950408889634f))), xn = bf_round((xv - rt.mean) * rt.rstd);
    asm volatile("" : "+f"(rsel), "+f"(xn));
    while (true) {
        bool wait = false;
        #pragma unroll
        for (int i = 0; i < NL; i++) wait = wait || has_sent(v[i]);
        if (!wait || ++n >= SPIN_MAX) break;
        #pragma unroll
        for (int i = 0; i < NL; i++) if (t + NT * i < 2 * NFC) v[i] = ld_relaxed4(src + i * (NT / 2) * D_);
    }
    spin_check(n);
    __syncwarp();
    float a[4] = {0.f, 0.f, 0.f, 0.f};
    #pragma unroll
    for (int i = 0; i < NL; i++) { a[0] += __uint_as_float(v[i].x); a[1] += __uint_as_float(v[i].y); a[2] += __uint_as_float(v[i].z); a[3] += __uint_as_float(v[i].w); }
    const bool b1 = t & 2, b2 = t & 4;
    a[0] = (b1 ? a[1] : a[0]) + __shfl_xor_sync(0xffffffffu, b1 ? a[0] : a[1], 2);
    a[2] = (b1 ? a[3] : a[2]) + __shfl_xor_sync(0xffffffffu, b1 ? a[2] : a[3], 2);
    a[0] = (b2 ? a[2] : a[0]) + __shfl_xor_sync(0xffffffffu, b2 ? a[0] : a[2], 4);
    a[0] += __shfl_xor_sync(0xffffffffu, a[0], 8); a[0] += __shfl_xor_sync(0xffffffffu, a[0], 16);
    if ((t & 31) < 8) stsf(red + (t >> 5) * 32 + (t & 1) * 16 + (t & 6) * 2, a[0]);
    named_sync(bid, NT);
    float y = 0.f, y2 = 0.f;
    #pragma unroll
    for (int i = 0; i < NT / 32; i++) { const float p = ldsf(red + (t & 7) * 4 + i * 32); if (i & 1) y2 += p; else y += p; }
    y += y2;
    return bf_round(xv + bf_round(xn + bf_round(bf_round(y) * rsel)));
}

__device__ __forceinline__ void routed_qkv(int ridx) {
    const int t = tid_now() - 288, c = cta_now(), lane = t & 31, warp = t >> 5;
    constexpr uint32_t red = SB + OFF_RED;
    {
        uint4 v[3];
        uint32_t n = 0;
        do {
            v[0] = ld_relaxed4(g_x2row + t * 4); v[1] = ld_relaxed4(g_x2row + (t + 96) * 4);
            v[2] = t < 64 ? ld_relaxed4(g_x2row + (t + 192) * 4) : make_uint4(0u, 0u, 0u, 0u);
        } while ((has_sent(v[0]) || has_sent(v[1]) || has_sent(v[2])) && ++n < SPIN_MAX);
        spin_check(n);
        __syncwarp();
        TL(288, 0, 21);
        float f[12];
        float s = 0.f;
        #pragma unroll
        for (int i = 0; i < 3; i++) { f[4*i] = __uint_as_float(v[i].x); f[4*i+1] = __uint_as_float(v[i].y); f[4*i+2] = __uint_as_float(v[i].z); f[4*i+3] = __uint_as_float(v[i].w); }
        #pragma unroll
        for (int i = 0; i < 12; i++) s += f[i];
        s = warp_sum(s);
        if (lane == 0) stsf(red + warp * 4, s);
        named_sync(2, 96);
        const float mean = (ldsf(red) + ldsf(red + 4) + ldsf(red + 8)) * (1.f / D_);
        float q = 0.f;
        #pragma unroll
        for (int i = 0; i < 12; i++) { f[i] -= mean; if (i < 8 || t < 64) q = fmaf(f[i], f[i], q); }
        q = warp_sum(q);
        if (lane == 0) stsf(red + 16 + warp * 4, q);
        named_sync(2, 96);
        const float rstd = rsqrtf((ldsf(red + 16) + ldsf(red + 20) + ldsf(red + 24)) * (1.f / D_) + LN_EPS);
        #pragma unroll
        for (int i = 0; i < 3; i++)
            if (i < 2 || t < 64) sts128(SB + OFF_XS + (t + 96 * i) * 16, make_uint4(pack_bf16(0.f, f[4*i] * rstd), pack_bf16(0.f, f[4*i+1] * rstd), pack_bf16(0.f, f[4*i+2] * rstd), pack_bf16(0.f, f[4*i+3] * rstd)));
    }
    named_sync(2, 96);
    TL(288, 0, 22);
    mbar_wait(B_SW, 0);
    TL(288, 0, 23);
    float a[8];
    #pragma unroll
    for (int i = 0; i < 8; i++) a[i] = 0.f;
    const uint32_t wa = SB + OFF_SIDE + t * 16, xa = SB + OFF_XS + (t / 3) * 4;
    #pragma unroll 4
    for (int i = 0; i < 32; i++) {
        const uint4 u = lds128(wa + i * 1536);
        const float xv = ldsf(xa + i * 128);
        a[0] = fmaf(xv, bf_lo(u.x), a[0]); a[1] = fmaf(xv, bf_hi(u.x), a[1]); a[2] = fmaf(xv, bf_lo(u.y), a[2]); a[3] = fmaf(xv, bf_hi(u.y), a[3]);
        a[4] = fmaf(xv, bf_lo(u.z), a[4]); a[5] = fmaf(xv, bf_hi(u.z), a[5]); a[6] = fmaf(xv, bf_lo(u.w), a[6]); a[7] = fmaf(xv, bf_hi(u.w), a[7]);
    }
    named_sync(2, 96);
    TL(288, 0, 41);
    sts128(SB + OFF_SIDE + t * 32, make_uint4(__float_as_uint(a[0]), __float_as_uint(a[1]), __float_as_uint(a[2]), __float_as_uint(a[3])));
    sts128(SB + OFF_SIDE + t * 32 + 16, make_uint4(__float_as_uint(a[4]), __float_as_uint(a[5]), __float_as_uint(a[6]), __float_as_uint(a[7])));
    named_sync(2, 96);
    {
        float y = 0.f;
        #pragma unroll
        for (int i = 0; i < 8; i++) y += ldsf(SB + OFF_SIDE + ((t & 3) * 8 + i) * 96 + (t >> 2) * 4);
        y += __shfl_xor_sync(0xffffffffu, y, 1); y += __shfl_xor_sync(0xffffffffu, y, 2);
        if ((t & 3) == 0) st_relaxed(g_fix + c * 24 + (t >> 2), not_sent(y));
    }
    if ((ridx >> 8) == (c >> 4) && t < 24) {
        const uint32_t* src = g_fix + (t >> 3) * D_ + (c & 15) * 64 + (t & 7) * 8;
        uint4 a, b;
        uint32_t n = 0;
        do { a = ld_relaxed4(src); b = ld_relaxed4(src + 4); } while ((has_sent(a) || has_sent(b)) && ++n < SPIN_MAX);
        spin_check(n);
        const int hh = t >> 2, ch = t & 3, lr = ridx & 255;
        const float hs = ldsf(SB + OFF_M + M_SC + hh * 4);
        sts128(SB + OFF_FIX + t * 16, make_uint4(pack_f16(__uint_as_float(a.x) * hs, __uint_as_float(a.y) * hs), pack_f16(__uint_as_float(a.z) * hs, __uint_as_float(a.w) * hs),
                                                 pack_f16(__uint_as_float(b.x) * hs, __uint_as_float(b.y) * hs), pack_f16(__uint_as_float(b.z) * hs, __uint_as_float(b.w) * hs)));
        sts32(SB + OFF_FIX + 512 + t * 4, SB + (hh < 2 ? OFF_QA + hh * 16384 + (lr >> 6) * 4096 + ch * 1024 + (lr & 63) * 16
                                                        : (hh & 1) * OFF_FE + (hh >> 2) * 16384 + ch * 4096 + lr * 16));
    }
    __syncwarp();
}

#define XP0 2
#define XP1 7
#define FW_NS 1000
__device__ __forceinline__ void ffn_load(const Maps& mp, int c, int i, uint32_t dst, uint32_t bar, bool last_use) {
    if (i < 8) tma_load_h(dst, (i & 1) ? &mp.u : &mp.g, c * 32, (i >> 1) * 256, bar, last_use);
    else tma_load3_h(dst, &mp.d, 0, c * 32, (i - 8) * 4, bar, last_use);
}
__device__ __forceinline__ void side_role(const Maps& mp, const bf16* __restrict__ x0, const bf16* __restrict__ wo, const bf16* __restrict__ w_r) {
    prep_work(x0, &mp.w64, threadIdx.x - 288);
    epi_inputs(0);
    #pragma unroll 1
    for (int L = 0; L < 2; L++) {
        const int t = tid_now() - 288, lane = t & 31, sw = warp_uniform(t >> 5);
        const int c = cta_now(), mt = c >> 4, nt = c & 15;
        named_sync(2, 96);
        if (t == 0) mbar_arrive(B_EPI);
        TL(288, L, 5);
        __syncwarp();
        char* kv = g_kv + (size_t)(nt * 16 + mt) * KV_WIN;
        if (sw < 2) {
            mbar_wait(sw ? B_K0 : B_KV0, L);
            bulk_store(kv + (1 - sw) * 16384, SB + (1 - sw) * 16384, 16384);
            bulk_commit();
            publish(&g_kvc[L][nt * 2][mt], 1 + sw);
            TL(288, L, 6);
        }
        if (sw == 0) {
            named_sync(N_KV1, 64);
            bulk_store(kv + 8 * KV_WIN, SB + OFF_FE, KV_WIN);
            bulk_commit();
            publish(&g_kvc[L][nt * 2 + 1][mt], 3);
        }
        if (sw < 2) {
            #pragma unroll 1
            for (int p = 0; p < 2; p++) {
                named_sync(N_OST + 2 * p + sw, p > sw ? 192 : 160);
                TL(p ? -1 : 288, L, 30); TL(p ? 288 : -1, L, 31);
                if (p == 1) mbar_arrive_elect(B_QAF);
                ctr_arrive(&g_oc[L][mt * 2 + sw][p][nt]);
            }
        } else {
            if (L == 0) {
                float ws = 0.f;
                #pragma unroll
                for (int i = 0; i < 4; i++) {
                    const uint4 v = reinterpret_cast<const uint4*>(w_r)[i * 32 + lane];
                    ws += ((bf_lo(v.x) + bf_hi(v.x)) + (bf_lo(v.y) + bf_hi(v.y))) + ((bf_lo(v.z) + bf_hi(v.z)) + (bf_lo(v.w) + bf_hi(v.w)));
                }
                const uint32_t* wp = reinterpret_cast<const uint32_t*>(w_r) + (nt >> 1) * 64 + (lane >> 2) * 8 + (lane & 3);
                sts64f(SB + OFF_WR + lane * 8, __uint_as_float(wp[0]), __uint_as_float(wp[4]));
                ws = warp_sum(ws);
                if (lane == 0) { stsf(SB + OFF_M + M_WS, ws); sts64f(SB + OFF_M + M_ORDY, 0.f, 0.f); sts64f(SB + OFF_WR + 256, __uint_as_float(0x3F803F80u), __uint_as_float(0x3F803F80u)); }
                __syncwarp();
            }
            named_sync(N_FW, 64);
            mbar_expect_tx(B_RES, 32768);
            #pragma unroll
            for (int i = 0; i < 4; i++) tma_load_h(SB + OFF_XT + i * 8192, L == 0 ? &mp.x0 : &mp.x, (nt >> 1) * 128 + (i >> 1) * 64, mt * 256 + (nt & 1) * 128 + (i & 1) * 64, B_RES, true);
            if (c < NFC) {
                #pragma unroll 1
                for (int r = 0; r < 4; r++) {
                    __nanosleep(FW_NS);
                    if (r > 0) mbar_wait(B_FW, (r + L) & 1);
                    const uint32_t bar = r < 3 ? B_FW : B_FE;
                    mbar_expect_tx(bar, 3 * 16384);
                    #pragma unroll 1
                    for (int b = 0; b < 3; b++) ffn_load(mp, c, 9 - 3 * r + b, SB + OFF_FE + b * 16384, bar, r == 3);
                }
            }
        }
        if (sw == 2) {
            l2_prefetch(reinterpret_cast<const char*>(wo) + (size_t)c * 16384, 16384);
            mbar_wait(B_RES, L);
            const uint32_t lr = lds32(SB + OFF_M + M_RIDX) - (mt * 256 + (nt & 1) * 128);
            if (L == 1 && lr < 128u && lane < 16) {
                const uint4 a = ld_relaxed4(g_x2row + (nt >> 1) * 128 + lane * 8), b = ld_relaxed4(g_x2row + (nt >> 1) * 128 + lane * 8 + 4);
                sts128(SB + OFF_XT + (lane >> 3) * 16384 + lr * 128 + (((lane & 7) ^ (lr & 7)) << 4),
                       make_uint4(__byte_perm(a.x, a.y, 0x7632), __byte_perm(a.z, a.w, 0x7632), __byte_perm(b.x, b.y, 0x7632), __byte_perm(b.z, b.w, 0x7632)));
            }
            if (L == 1) {
                #pragma unroll
                for (int i = 0; i < 4; i++) {
                    const float2 r = ln_coef(ld_relaxed4(&g_sums[mt * 256 + (nt & 1) * 128 + i * 32 + lane]));
                    const float a = i * 32 + lane == lr ? 0.f : r.x;
                    sts64f(SB + OFF_LC + (i * 32 + lane) * 8, a, -a * r.y);
                }
            }
            __syncwarp();
            mbar_arrive_elect(B_RES2);
            named_sync(N_OST + 2, 192);
            l2_prefetch(&g_ypart[L][0][0] + c * (NFC * 8), NFC * 32);
            l2_prefetch(&g_acc[L][c * 16][0], 512);
            l2_prefetch(&g_sums[c * 16], 256);
            l2_prefetch(&g_xrow[L][0][0] + c * 64, 256);
            l2_prefetch(&g_tab[L][0][0][0] + c * 2, 32);
            l2_prefetch(c < 32 ? &g_x2row[c * 32] : c < 40 ? &g_kvc[1][(c - 32) * 4][0] : &g_xc[0][0], c < 40 ? 128 : 64);
            l2_prefetch(&g_fix[c * 24], 96);
            uint32_t ready, n = 0;
            do {
                ready = __ballot_sync(0xffffffffu, ld_acquire(&g_oc[L][mt * 2 + (nt & 1)][1][lane & 15]) != 0);
                fence_async_global();
                if (lane == 0) sts_release(SB + OFF_M + M_ORDY + 4 * L, ready & ready >> 1);
            } while (ready != 0xFFFFFFFFu && ++n < SPIN_MAX);
            spin_check(n);
        }
        if (sw < 2) {
            named_sync(N_XST + sw, 160);
            const int row0 = mt * 256 + (nt & 1) * 128 + sw * 64, col0 = (nt >> 1) * 128;
            #pragma unroll 1
            for (int h = 0; h < 8; h++) {
                if (L == 0) bulk_wait_n<XP0>(); else bulk_wait_n<XP1>();
                tma_store(L == 0 ? &mp.xs : &mp.out, SB + OFF_XT + (h & 1) * 16384 + sw * 8192 + (h >> 1) * 2048, col0 + (h & 1) * 64, row0 + (h >> 1) * 16);
                bulk_commit();
            }
            publish(&g_xc[L][mt]);
            TL(288, L, 14);
        }
        if (L == 0) {
            __syncwarp();
            named_sync(N_RT, 128);
            const RouteOut rt = route_out(lds128(SB + OFF_RT + 128));
            if (t == 0) { sts32(SB + OFF_M + M_RIDX, rt.idx); if (c == 0) g_c0 = 0u; }
            epi_inputs(1);
            const float v = ffn_finish<96>(0, rt, t, SB + OFF_RED, 2);
            TL(288, L, 20);
            if (t < 8) st_relaxed(g_x2row + ypos_col(c * 8 + t), not_sent(v));
            routed_qkv(rt.idx);
        }
    }
}

struct EpiIn { float2 c2[4]; float hs; };
template <int HH>
__device__ __forceinline__ EpiIn qkv_epi_in(int t) {
    EpiIn e;
    #pragma unroll
    for (int jj = 0; jj < 4; jj++) e.c2[jj] = lds64f(SB + OFF_CS + (HH * 32 + jj * 8) * 4 + t * 8);
    e.hs = ldsf(SB + OFF_M + M_SC + HH * 4);
    return e;
}
template <int HH, int NEXT>
__device__ __forceinline__ void qkv_epi_head(const float (&acc0)[96], const float (&acc1)[96], const float (&cf)[4], const float (&nm)[4], EpiIn& in, uint32_t dst, int t) {
    const EpiIn e = in;
    #pragma unroll
    for (int i = 0; i < 4; i++) {
        const float* a = (i >> 1) ? acc1 : acc0;
        const float sc = cf[i] * e.hs;
        uint32_t pk[4];
        #pragma unroll
        for (int jj = 0; jj < 4; jj++)
            pk[jj] = pack_f16(fmaf(nm[i], e.c2[jj].x, a[4 * (4 * HH + jj) + 2 * (i & 1)]) * sc, fmaf(nm[i], e.c2[jj].y, a[4 * (4 * HH + jj) + 2 * (i & 1) + 1]) * sc);
        #pragma unroll
        for (int jj = 0; jj < 4; jj++) pk[jj] = round8(pk[jj]);
        stsm4(dst + (i >> 1) * (HH < 2 ? 4096 : 1024) + (i & 1) * 128, pk[0], pk[1], pk[2], pk[3]);
        if (i == 1 && NEXT >= 0) in = qkv_epi_in<NEXT < 0 ? 0 : NEXT>(t);
    }
}
__device__ __forceinline__ void qkv_patch(int lane, uint32_t mask) {
    const uint4 v = lds128(SB + OFF_FIX + lane * 16);
    const uint32_t dst = lds32(SB + OFF_FIX + 512 + lane * 4);
    __syncwarp();
    asm volatile("{\n.reg .pred q;\nsetp.ne.u32 q, %5, 0;\n@q st.shared.v4.b32 [%0], {%1, %2, %3, %4};\n}"
                 :: "r"(dst), "r"(v.x), "r"(v.y), "r"(v.z), "r"(v.w), "r"((mask >> lane) & 1) : "memory");
}

template <bool INIT>
__device__ __forceinline__ void qkv_step(float (&acc0)[96], float (&acc1)[96], uint32_t st, int wg) {
    const uint64_t da = desc_sw128(SB, 16, 1024) + ((st * Q_STB + wg * 16384) >> 4);
    const uint64_t db = desc_sw128(SB + Q_ABYTES, 8192, 1024) + ((st * Q_STB) >> 4);
    wg_fence();
    if (INIT) { wg_gemm_n192_init(acc0, da, db); wg_gemm_n192_init(acc1, da + (8192 >> 4), db); }
    #pragma unroll
    for (int kk = INIT ? 1 : 0; kk < 4; kk++) {
        wg_gemm_n192(acc0, da + kk * 2, db + kk * 128);
        wg_gemm_n192(acc1, da + (8192 >> 4) + kk * 2, db + kk * 128);
    }
    wg_commit();
}
__device__ __forceinline__ void qkv_phase(int L, int wg) {
    const uint32_t rb = L * 32;
    float acc0[96], acc1[96];
    const bool leader = (tid_now() & 127) == 0;
    mbar_wait(rb + B_QF, 0);
    TL(0, L, 1);
    qkv_step<true>(acc0, acc1, 0, wg);
    uint32_t st = 1, ph = 0;
    #pragma unroll 1
    for (int k = 1; k < 16; k++) {
        mbar_wait(rb + B_QF + 8 * st, ph);
        qkv_step<false>(acc0, acc1, st, wg);
        wg_wait<1>();
        if (leader) mbar_arrive(rb + B_QE + 8 * (st == 0 ? 2 : st - 1));
        if (++st == 3) { st = 0; ph ^= 1; }
    }
    const int tid = tid_now(), lane = tid & 31, w = (tid >> 5) & 3, g = lane >> 2, t = lane & 3;
    mbar_wait(B_EPI, L);
    float cf[4], nm[4];
    #pragma unroll
    for (int i = 0; i < 4; i++) { const float2 r = lds64f(SB + OFF_RC + (wg * 128 + w * 16 + g + (i >> 1) * 64 + (i & 1) * 8) * 8); cf[i] = r.x; nm[i] = -r.y; }
    const int d = (int)lds32(SB + OFF_M + M_RIDX) - (cta_now() >> 4) * 256;
    const bool own = L == 1 && (d >> 7) == wg && ((d >> 4) & 3) == w;
    EpiIn in = qkv_epi_in<2>(t);
    wg_wait<0>();
    TL(0, L, 2);
    TL(128, L, 40);
    named_sync(1, 256);
    const uint32_t dk = SB + wg * 2048 + (lane >> 3) * 4096 + (w * 16 + (lane & 7)) * 16;
    const uint32_t dq = SB + OFF_QA + wg * 8192 + (lane >> 3) * 1024 + (w * 16 + (lane & 7)) * 16;
    qkv_epi_head<2, 4>(acc0, acc1, cf, nm, in, dk, t);
    if (own) qkv_patch(lane, 0x000F00u);
    fence_async_smem();
    __syncwarp();
    mbar_arrive_elect(B_K0);
    qkv_epi_head<4, 0>(acc0, acc1, cf, nm, in, dk + 16384, t);
    if (own) qkv_patch(lane, 0x0F0000u);
    #pragma unroll
    for (int s = 0; s < 3; s++) sts128(SB + s * A_WIN + KV_WIN + tid * 16, make_uint4(0x3C003C00u, 0x3C003C00u, 0x3C003C00u, 0x3C003C00u));
    fence_async_smem();
    __syncwarp();
    mbar_arrive_elect(B_KV0);
    TL(0, L, 4);
    qkv_epi_head<0, 1>(acc0, acc1, cf, nm, in, dq, t);
    qkv_epi_head<1, 3>(acc0, acc1, cf, nm, in, dq + 16384, t);
    qkv_epi_head<3, 5>(acc0, acc1, cf, nm, in, dk + OFF_FE, t);
    qkv_epi_head<5, -1>(acc0, acc1, cf, nm, in, dk + OFF_FE + 16384, t);
    if (own) qkv_patch(lane, 0xF0F0FFu);
    fence_async_smem();
    named_sync(3 + wg, 128);
    TL(0, L, 3);
}

struct Unit {
    uint32_t o[8];
    uint32_t l, bz, sc;
    uint32_t ch[2];
};
template <int H> __device__ __forceinline__ uint32_t hdup(uint32_t v) {
    uint32_t r;
    if (H) asm("{.reg .b16 l, h; mov.b32 {l, h}, %1; mov.b32 %0, {h, h};}" : "=r"(r) : "r"(v));
    else asm("{.reg .b16 l, h; mov.b32 {l, h}, %1; mov.b32 %0, {l, l};}" : "=r"(r) : "r"(v));
    return r;
}
__device__ __forceinline__ uint32_t hmax2(uint32_t a, uint32_t b) { uint32_t r; asm("max.f16x2 %0, %1, %2;" : "=r"(r) : "r"(a), "r"(b)); return r; }
__device__ __forceinline__ uint32_t hadd2(uint32_t a, uint32_t b) { uint32_t r; asm("add.rn.f16x2 %0, %1, %2;" : "=r"(r) : "r"(a), "r"(b)); return r; }
__device__ __forceinline__ uint32_t hsub2(uint32_t a, uint32_t b) { uint32_t r; asm("sub.rn.f16x2 %0, %1, %2;" : "=r"(r) : "r"(a), "r"(b)); return r; }
__device__ __forceinline__ uint32_t hfma2(uint32_t a, uint32_t b, uint32_t c) { uint32_t r; asm("fma.rn.f16x2 %0, %1, %2, %3;" : "=r"(r) : "r"(a), "r"(b), "r"(c)); return r; }
__device__ __forceinline__ uint32_t exp2_h2(uint32_t s, uint32_t bz, uint32_t& ch) {
    uint32_t z, w, d;
    asm("fma.rn.relu.f16x2 %0, %1, %2, %3;" : "=r"(z) : "r"(s), "r"(0x00400040u), "r"(bz));
    asm("lop3.b32 %0, %1, 0x003F003F, %0, 0xC2;" : "+r"(ch) : "r"(z));
    asm("fma.rn.f16x2 %0, %1, %2, %3;" : "=r"(w) : "r"(ch), "r"(0x30A630A6u), "r"(0xACCCACCCu));
    asm("{.reg .b32 n; neg.f16x2 n, %1; fma.rn.relu.f16x2 %0, n, %1, %2;}" : "=r"(d) : "r"(w), "r"(0x00580058u));
    return (z << 4) - d;
}
__device__ __forceinline__ void exp_tile(uint32_t (&p)[32], const uint32_t (&s)[32], Unit& u) {
    #pragma unroll
    for (int i = 0; i < 32; i++) p[i] = exp2_h2(s[i], (i & 1) ? hdup<1>(u.bz) : hdup<0>(u.bz), u.ch[i & 1]);
}
struct QOp { uint32_t r[4]; uint64_t d; };
__device__ __forceinline__ void issue_qk(uint32_t (&s)[32], const QOp& q, uint64_t dk) {
    wg_qk_init(s, q.r[0], q.r[1], q.r[2], q.r[3], dk); wg_qk_acc(s, q.d, dk + (8192 >> 4));
    wg_commit();
}
template <bool INIT>
__device__ __forceinline__ void issue_pv(uint32_t (&h)[10], const uint32_t (&p)[32], uint64_t dv) {
    #pragma unroll
    for (int k = 0; k < 8; k++) {
        if (INIT && k == 0) wg_pv_init(h, p[0], p[1], p[2], p[3], dv);
        else wg_pv_acc(h, p[4*k], p[4*k+1], p[4*k+2], p[4*k+3], dv + k * 16);
    }
    wg_commit();
}
__device__ __forceinline__ void unit_init(Unit& u, const uint32_t (&s)[32], uint32_t ok) {
    uint32_t m0 = s[0], m1 = s[1];
    #pragma unroll
    for (int i = 1; i < 16; i++) { m0 = hmax2(m0, s[2 * i]); m1 = hmax2(m1, s[2 * i + 1]); }
    uint32_t m = hmax2(__byte_perm(m0, m1, 0x5410), __byte_perm(m0, m1, 0x7632));
    m = hmax2(m, __shfl_xor_sync(0xffffffffu, m, 1)); m = hmax2(m, __shfl_xor_sync(0xffffffffu, m, 2));
    const uint32_t q = hfma2(m, 0x80048004u, 0x003E003Eu);
    u.bz = hfma2(q, 0x4C004C00u, 0x80008000u);
    u.ch[0] = u.ch[1] = ok & ~hadd2(q, q);
    u.sc = 0u; u.l = 0u;
    #pragma unroll
    for (int i = 0; i < 8; i++) u.o[i] = 0u;
}
template <bool MORE>
__device__ __forceinline__ void unit_flush(Unit& u, const uint32_t (&h)[10]) {
    u.l = hfma2(u.l, u.sc, __byte_perm(h[8], h[9], 0x5410));
    #pragma unroll
    for (int i = 0; i < 8; i++) u.o[i] = hfma2(u.o[i], (i & 1) ? hdup<1>(u.sc) : hdup<0>(u.sc), h[i]);
    if (MORE) {
        const uint32_t ex = u.l & 0x7C007C00u;
        u.sc = 0x84008400u - ex;
        u.bz = hsub2(hadd2(u.bz, 0x04800480u), ex >> 4);
    }
}
__device__ __forceinline__ char* o_block(int wg, int pass) { const int c = cta_now(); return g_o + (size_t)((((c >> 4) * 2 + wg) * 2 + pass) * 16 + (c & 15)) * 8192; }
__device__ __forceinline__ uint32_t unit_finish(Unit& u, float ivs) {
    float lf[2]; h2_unpack(u.l, lf[0], lf[1]);
    #pragma unroll
    for (int i = 0; i < 8; i++) { float x, y; h2_unpack(u.o[i], x, y); const float inv = ivs * rcp(lf[i & 1]); u.o[i] = pack_bf16(x * inv, y * inv); }
    return ((~u.ch[0] & CH_OK) != 0 || (u.l << 16) - 0x40000000u >= 0x3C000000u ? 1u : 0u) | ((~u.ch[1] & CH_OK) != 0 || u.l - 0x40000000u >= 0x3C000000u ? 2u : 0u);
}
__device__ __forceinline__ void unit_store(const Unit& u, char* dst) {
    #pragma unroll
    for (int i = 0; i < 8; i++) *reinterpret_cast<uint32_t*>(dst + (i >> 1) * 1024 + (i & 1) * 128) = u.o[i];
}
__device__ __noinline__ void exact_rows(int L, int pass, int wg, uint32_t bad) {
    const int tid = tid_now() & 127, lane = tid & 31, w = tid >> 5, t = lane & 3;
    const int head = (cta_now() & 15) * 2 + pass;
    const uint32_t scr = SB + OFF_PART + wg * 1024;
    bad = redux_or(bad << (lane & 28));
    if (lane == 0) sts32(scr + w * 4, bad);
    ctr_wait_all(&g_kvc[L][head][lane & 7], 3);
    named_sync(3 + wg, 128);
    const float isc = ldsf(SB + OFF_M + M_ISC + pass * 4), ivs = ldsf(SB + OFF_M + M_IVS + pass * 4);
    const char* kv = g_kv + (size_t)(head * 8 + w * 2) * KV_WIN + t * 4096 + (lane >> 2) * 16;
    #pragma unroll 1
    for (int ww = 0; ww < 4; ww++)
    #pragma unroll 1
    for (uint32_t m = lds32(scr + ww * 4); m; m &= m - 1) {
        const int bit = __ffs(m) - 1;
        const uint32_t ro = (bit & 2) * 2048 + (ww * 16 + (bit & 1) * 8 + (bit >> 2)) * 16;
        const uint4 q = lds128(SB + OFF_QA + pass * 16384 + wg * 8192 + ro + t * 1024);
        float a[9], mx = -INFINITY;
        #pragma unroll
        for (int i = 0; i < 9; i++) a[i] = 0.f;
        #pragma unroll 1
        for (int it = 0; it < 8; it++) {
            uint4 k[8], v[8];
            #pragma unroll
            for (int i = 0; i < 8; i++) {
                const char* p = kv + (it >> 2) * KV_WIN + (it & 3) * 1024 + i * 128;
                k[i] = __ldcg(reinterpret_cast<const uint4*>(p)); v[i] = __ldcg(reinterpret_cast<const uint4*>(p + 16384));
            }
            float s[8], mn = mx;
            #pragma unroll
            for (int i = 0; i < 8; i += 2) {
                float c[4] = {0.f, 0.f, 0.f, 0.f};
                mma_f16(c, k[i].x, k[i + 1].x, k[i].y, k[i + 1].y, q.x, q.y);
                mma_f16(c, k[i].z, k[i + 1].z, k[i].w, k[i + 1].w, q.z, q.w);
                s[i] = c[0]; s[i + 1] = c[2];
                mn = fmaxf(mn, fmaxf(c[0], c[2]));
            }
            const float al = ex2((mx - mn) * isc);
            mx = mn;
            #pragma unroll
            for (int i = 0; i < 9; i++) a[i] *= al;
            #pragma unroll
            for (int i = 0; i < 8; i++) {
                const float p = ex2((s[i] - mx) * isc);
                const uint32_t u[4] = {v[i].x, v[i].y, v[i].z, v[i].w};
                a[8] += p;
                #pragma unroll
                for (int e = 0; e < 4; e++) { float x, y; h2_unpack(u[e], x, y); a[2 * e] = fmaf(p, x, a[2 * e]); a[2 * e + 1] = fmaf(p, y, a[2 * e + 1]); }
            }
        }
        #pragma unroll 1
        for (int o = 4; o < 32; o <<= 1) {
            const float mn = fmaxf(mx, __shfl_xor_sync(0xffffffffu, mx, o)), al = ex2((mx - mn) * isc);
            mx = mn;
            #pragma unroll
            for (int i = 0; i < 9; i++) { a[i] *= al; a[i] += __shfl_xor_sync(0xffffffffu, a[i], o); }
        }
        named_sync(3 + wg, 128);
        const uint32_t mine = scr + 16 + w * 144;
        sts128(mine + t * 32, make_uint4(__float_as_uint(a[0]), __float_as_uint(a[1]), __float_as_uint(a[2]), __float_as_uint(a[3])));
        sts128(mine + t * 32 + 16, make_uint4(__float_as_uint(a[4]), __float_as_uint(a[5]), __float_as_uint(a[6]), __float_as_uint(a[7])));
        sts64f(mine + 128, a[8], mx);
        named_sync(3 + wg, 128);
        float o = 0.f, l = 0.f;
        mx = -INFINITY;
        #pragma unroll 1
        for (int i = 0; i < 4; i++) {
            const float2 e = lds64f(scr + 16 + i * 144 + 128);
            const float mn = fmaxf(mx, e.y), al = ex2((mx - mn) * isc), be = ex2((e.y - mn) * isc);
            mx = mn;
            o = fmaf(o, al, be * ldsf(scr + 16 + i * 144 + lane * 4)); l = fmaf(l, al, be * e.x);
        }
        if (w == 0) *reinterpret_cast<unsigned short*>(o_block(wg, pass) + ro + (lane >> 3) * 1024 + (lane & 7) * 2) = (unsigned short)pack_bf16(o * ivs * rcp(l), 0.f);
    }
}

__device__ __forceinline__ void attention_phase(int L, int wg) {
    const uint32_t rb = L * 32;
    constexpr uint64_t dk0 = desc_plain(SB, 4096, 128), dv0 = desc_plain(SB + 16384, 128, 4096);
    constexpr int T1 = 2048 >> 4;
    uint32_t st = 0, ph = 0;
    #pragma unroll 1
    for (int pass = 0; pass < 2; pass++) {
        QOp dqa, dqc;
        dqa.d = desc_plain(SB + OFF_QA + 2048, 1024, 128) + (pass * 4 + wg * 2) * (4096 >> 4); dqc.d = dqa.d + (4096 >> 4);
        {
            const int tid = tid_now();
            const uint32_t a0 = SB + OFF_QA + (pass * 4 + wg * 2) * 4096 + ((tid >> 4) & 1) * 1024 + (((tid >> 5) & 3) * 16 + (tid & 15)) * 16;
            ldsm4(dqa.r[0], dqa.r[1], dqa.r[2], dqa.r[3], a0); ldsm4(dqc.r[0], dqc.r[1], dqc.r[2], dqc.r[3], a0 + 4096);
        }
        Unit a, c;
        st = warp_uniform(st); ph = warp_uniform(ph);
        uint32_t SA[32], SC[32], PA[32], PC[32], ha[10], hc[10], bad;
        #pragma unroll
        for (int i = 0; i < 10; i++) hc[i] = 0u;
        #pragma unroll
        for (int i = 0; i < 32; i++) PC[i] = 0u;
        const uint32_t ok = lds32(SB + OFF_M + M_OK + pass * 4);
        mbar_wait(rb + B_AF + 8 * st, ph);
        wg_fence();
        issue_qk(SA, dqa, dk0 + st * (A_WIN >> 4));
        issue_qk(SC, dqc, dk0 + st * (A_WIN >> 4));
        wg_wait<1>();
        unit_init(a, SA, ok);
        exp_tile(PA, SA, a);
        wg_wait<0>();
        unit_init(c, SC, ok);
        uint32_t eb = 0;
        #pragma unroll 1
        for (int s = 0;; s++) {
            const uint64_t dkb = dk0 + st * (A_WIN >> 4), dvb = dv0 + st * (A_WIN >> 4);
            if (__builtin_expect(s == 8 * gridDim.y, 0)) {
                wg_wait<0>();
                bad = 0;
                #pragma unroll
                for (int i = 0; i < 32; i++) bad |= PC[i];
                break;
            }
            wg_fence();
            issue_pv<true>(ha, PA, dvb); issue_qk(SA, dqa, dkb + T1);
            wg_wait<2>();
            if (s > 0) { mbar_arrive_elect(eb); unit_flush<true>(c, hc); }
            exp_tile(PC, SC, c);
            wg_fence();
            issue_pv<true>(hc, PC, dvb); issue_qk(SC, dqc, dkb + T1);
            wg_wait<2>();
            exp_tile(PA, SA, a);
            eb = rb + B_AE + 8 * st;
            if (++st == 3) { st = 0; ph ^= 1; }
            if (s == 7) {
                wg_fence(); issue_pv<false>(ha, PA, dvb + T1);
                wg_wait<1>();
                exp_tile(PC, SC, c);
                wg_fence(); issue_pv<false>(hc, PC, dvb + T1);
                wg_wait<1>();
                const int tid = tid_now();
                const float ivs = ldsf(SB + OFF_M + M_IVS + pass * 4);
                char* dst = o_block(wg, pass) + (tid & 96) * 8 + (tid & 31) * 4;
                unit_flush<false>(a, ha);
                bad = unit_finish(a, ivs);
                wg_wait<0>();
                mbar_arrive_elect(eb);
                unit_store(a, dst);
                unit_flush<false>(c, hc);
                bad |= unit_finish(c, ivs) << 2;
                unit_store(c, dst + 4096);
                break;
            }
            const uint64_t dkn = dk0 + st * (A_WIN >> 4);
            mbar_wait(rb + B_AF + 8 * st, ph);
            wg_fence();
            issue_pv<false>(ha, PA, dvb + T1); issue_qk(SA, dqa, dkn);
            wg_wait<2>();
            exp_tile(PC, SC, c);
            wg_fence();
            issue_pv<false>(hc, PC, dvb + T1); issue_qk(SC, dqc, dkn);
            wg_wait<2>();
            unit_flush<true>(a, ha);
            exp_tile(PA, SA, a);
        }
        if (__builtin_expect(named_any(bad != 0, 3 + wg), 0)) {
            exact_rows(L, pass, wg, bad);
        }
        named_arrive(N_OST + 2 * pass + wg, pass > wg ? 192 : 160);
        TL(pass ? -1 : 0, L, 8); TL(pass ? 0 : -1, L, 9);
    }
}

#define XS0 0
#define OW0 1
#define OUNR 1
#define GDP 0
#define DDP 1

template <bool INIT>
__device__ __forceinline__ void oproj_step(float (&acc)[64], uint32_t s, int wg) {
    const uint64_t da = desc_plain(SB, 1024, 128) + ((o_stage(s) + wg * 4096) >> 4);
    const uint64_t db = desc_sw128(SB + 16384, 8192, 1024) + (o_stage(s) >> 4);
    wg_fence();
    if (INIT) wg_gemm_n128_init(acc, da, db);
    #pragma unroll
    for (int kk = INIT ? 1 : 0; kk < 4; kk++) wg_gemm_n128(acc, da + (kk >> 1) * 512 + (kk & 1) * 128, db + kk * 128);
    wg_commit();
}
__device__ __forceinline__ void oproj_phase(int L, int wg, bf16* __restrict__ out) {
    const int c = cta_now(), tid = tid_now(), lane = tid & 31, W = tid >> 5, g = lane >> 2, t = lane & 3;
    const int row0 = (c >> 4) * 256 + (c & 1) * 128, col0 = ((c & 15) >> 1) * 128;
    float acc[64];
    mbar_wait(B_OF, 0);
    TL(0, L, 10);
    oproj_step<true>(acc, 0, wg);
    const uint32_t xa = SB + OFF_XT + (W * 16 + ((lane >> 3) & 1) * 8 + (lane & 7)) * 128, xs = (lane >> 4) ^ (lane & 7);
    mbar_wait(B_RES2, L);
    const float2 c0 = lds64f(SB + OFF_LC + (W * 16 + g) * 8), c1 = lds64f(SB + OFF_LC + (W * 16 + g + 8) * 8);
    constexpr int ounr = OUNR;
    #pragma unroll ounr
    for (int k = 1; k < 16; k++) {
        if (OW0) { wg_wait<0>(); if ((tid & 127) == 0) mbar_arrive(B_OE + 8 * ((k - 1) & 3)); }
        mbar_wait(B_OF + 8 * (k & 3), (k >> 2) & 1);
        TL(k == 8 ? 0 : -1, L, 11);
        oproj_step<false>(acc, k & 3, wg);
        if (!OW0) { wg_wait<1>(); if ((tid & 127) == 0) mbar_arrive(B_OE + 8 * ((k - 1) & 3)); }
        if (L == 1 && (k & 1)) {
            const uint32_t a = xa + (k & 8) * 2048 + ((xs ^ (k & 6)) << 4);
            uint32_t v0, v1, v2, v3;
            ldsm4(v0, v1, v2, v3, a);
            stsm4(a, add_ln2(v0, c0.x, c0.y), add_ln2(v1, c1.x, c1.y), add_ln2(v2, c0.x, c0.y), add_ln2(v3, c1.x, c1.y));
        }
    }
    uint32_t x[32];
    const uint32_t wra = SB + OFF_WR + (g == 4 ? t * 8 : 256), wrs = g == 4 ? 32 : 0;
    float2 wb[8];
    #pragma unroll
    for (int ks = 0; ks < 8; ks++) {
        ldsm4(x[4*ks], x[4*ks+1], x[4*ks+2], x[4*ks+3], xa + (ks >> 2) * 16384 + ((xs ^ ((ks & 3) * 2)) << 4));
        wb[ks] = lds64f(wra + ks * wrs);
    }
    wg_wait<0>();
    if ((tid & 127) == 0) mbar_arrive(B_OE + 24);
    TL(0, L, 12);
    {
        float sd[4] = {0.f, 0.f, 0.f, 0.f}, z0[4] = {0.f, 0.f, 0.f, 0.f}, z1[4] = {0.f, 0.f, 0.f, 0.f};
        #pragma unroll
        for (int ks = 0; ks < 8; ks++) {
            #pragma unroll
            for (int i = 0; i < 4; i++) x[4*ks + i] = badd2(x[4*ks + i], pack_bf16(acc[8*ks + 2*i], acc[8*ks + 2*i + 1]));
            mma_bf16(sd, x[4*ks], x[4*ks+1], x[4*ks+2], x[4*ks+3], __float_as_uint(wb[ks].x), __float_as_uint(wb[ks].y));
            mma_bf16(z0, x[4*ks], x[4*ks+1], x[4*ks+2], x[4*ks+3], x[4*ks], x[4*ks+2]);
            mma_bf16(z1, x[4*ks], x[4*ks+1], x[4*ks+2], x[4*ks+3], x[4*ks+1], x[4*ks+3]);
        }
        const float s0 = __shfl_sync(0xffffffffu, (g & 1) ? z0[1] : z0[0], 4 * g + (g >> 1));
        const float s1 = __shfl_sync(0xffffffffu, (g & 1) ? z1[3] : z1[2], 4 * g + (g >> 1));
        double* p = &g_acc[L][row0 + W * 16 + g][t];
        asm volatile("red.relaxed.gpu.global.add.f64 [%0], %1;" :: "l"(p), "d"((double)sel4(t, sd[0], s0, sd[0], 1.f)) : "memory");
        asm volatile("red.relaxed.gpu.global.add.f64 [%0], %1;" :: "l"(p + 32), "d"((double)sel4(t, sd[2], s1, sd[2], 1.f)) : "memory");
    }
    TL(0, L, 13);
    if (L == 0) {
        #pragma unroll
        for (int ks = 0; ks < 8; ks++) stsm4(xa + (ks >> 2) * 16384 + ((xs ^ ((ks & 3) * 2)) << 4), x[4*ks], x[4*ks+1], x[4*ks+2], x[4*ks+3]);
        fence_async_smem();
        if (XS0 == 0) named_arrive(N_XST + wg, 160);
    }
    const bool ffn = c < NFC;
    uint4 fa[32], fd[16];
    const uint32_t ga = SB + W * 2048 + ((lane >> 4) * 8 + (lane & 7)) * 64 + ((((lane >> 3) & 1) ^ ((lane >> 1) & 3)) << 4);
    if (ffn) mbar_wait(B_FE, L);
    #pragma unroll
    for (int i = 0; i < 12; i++) ldsm4t(fa[i].x, fa[i].y, fa[i].z, fa[i].w, (ga ^ ((i & 1) * 32)) + gu_piece(i >> 2) + (i & 2) * 512);
    float2 r0, r1;
    {
        const float ws = ldsf(SB + OFF_M + M_WS);
        const uint32_t row = row0 + W * 16 + g;
        const bool odd = t & 1, up = t & 2;
        const uint32_t me = row + (odd ? 8 : 0);
        uint4 v;
        uint32_t n = 0;
        do { v = ld_relaxed4(&g_acc[L][me][t & 2]); } while (__any_sync(0xffffffffu, up && v.w != 0x40200000u) && ++n < SPIN_MAX);
        spin_check(n);
        TL(0, L, 46);
        if (XS0 == 1 && L == 0) named_arrive(N_XST + wg, 160);
        const float f0 = (float)__hiloint2double(v.y, v.x), f1 = (float)__hiloint2double(v.w, v.z);
        const float e0 = __shfl_xor_sync(0xffffffffu, f0, 2), e1 = __shfl_xor_sync(0xffffffffu, f1, 2);
        const float a[3] = {up ? e0 : f0, up ? e1 : f1, up ? f0 : e0};
        const uint4 tot = make_uint4(not_sent(a[0]), not_sent(a[1]), 0u, 0u);
        st_relaxed4_if(&g_sums[me], tot, L == 0 && col0 == 0 && t < 2);
        const float2 r = ln_coef(tot), ro = make_float2(__shfl_xor_sync(0xffffffffu, r.x, 1), __shfl_xor_sync(0xffffffffu, r.y, 1));
        r0 = odd ? ro : r; r1 = odd ? r : ro;
        const uint32_t k = min(order_bits(r.x * fmaf(-r.y, ws, a[2])), SENT - 1);
        const uint32_t m = redux_max(k), mrow = redux_min(k == m ? me : 0x7FFFFFFFu);
        if (me == mrow) sts128(SB + OFF_RT + W * 16, make_uint4(k, me, not_sent(r.y), not_sent(r.x)));
    }
    named_sync(1, 256);
    {
        const uint4 e = lds128(SB + OFF_RT + (lane & 7) * 16);
        const uint32_t m = redux_max(e.x), row = redux_min(e.x == m ? e.y : 0x7FFFFFFFu);
        const int lr = row - row0;
        st_relaxed4_if(&g_tab[L][(c & 15) >> 1][row0 >> 7][(lane >> 3) & 1], e, W == ((lr >> 4) ^ 1) && e.y == row && lane < 16);
        if ((lr >> 4) == W) {
            const bool hi = lr & 8;
            uint32_t* dst = &g_xrow[L][row0 >> 7][(col0 & 128) * 2 + (col0 >> 8) * 16 + t * 4];
            #pragma unroll
            for (int i = 0; i < 4; i++)
                st_relaxed4_if(dst + i * 64, make_uint4(min(hi ? x[8*i+1] : x[8*i], SENT - 1), min(hi ? x[8*i+3] : x[8*i+2], SENT - 1),
                               min(hi ? x[8*i+5] : x[8*i+4], SENT - 1), min(hi ? x[8*i+7] : x[8*i+6], SENT - 1)), g == (lr & 7));
        }
        __syncwarp();
    }
    TL(0, L, 15);
    if (XS0 == 2 && L == 0) named_arrive(N_XST + wg, 160);
    if (L == 1) {
        const float b0 = -r0.x * r0.y, b1 = -r1.x * r1.y;
        #pragma unroll
        for (int ks = 0; ks < 8; ks++)
            stsm4(xa + (ks >> 2) * 16384 + ((xs ^ ((ks & 3) * 2)) << 4), add_ln2(x[4*ks], r0.x, b0), add_ln2(x[4*ks+1], r1.x, b1),
                  add_ln2(x[4*ks+2], r0.x, b0), add_ln2(x[4*ks+3], r1.x, b1));
        TL(0, L, 47);
        fence_async_smem();
        named_arrive(N_XST + wg, 160);
    }
    TL(0, L, 45);
    RouteOut rt;
    {
        const uint4* tp = &g_tab[L][(c & 15) >> 1][lane & 15][0];
        uint4 e = ld_relaxed4(tp);
        if (ffn) mbar_wait(B_FL, L);
        #pragma unroll
        for (int i = 12; i < 32; i++) ldsm4t(fa[i].x, fa[i].y, fa[i].z, fa[i].w, (ga ^ ((i & 1) * 32)) + gu_piece(i >> 2) + (i & 2) * 512);
        TL(0, L, 44);
        if (L == 0 && GDP == 0) named_arrive(N_GD, 288);
        uint32_t n = 0;
        while (has_sent(e) && ++n < SPIN_MAX) e = ld_relaxed4(tp);
        spin_check(n);
        __syncwarp();
        e = warp_best(e);
        rt = route_out(e);
        if (W == 7 && L == 0) { sts128(SB + OFF_RT + 128, e); named_arrive(N_RT, 128); }
    }
    TL(0, L, 16);
    uint2 xrow;
    {
        const uint32_t* xp = &g_xrow[L][rt.idx >> 7][W * 64 + (g >> 1) * 16 + t * 4 + (g & 1) * 2];
        xrow = ld_relaxed2(xp);
        if (ffn) mbar_wait(B_FD, L);
        const uint32_t wa = SB + OFF_FD + W * 8192 + ((lane >> 4) * 8 + (lane & 7)) * 128 + ((((lane >> 3) & 1) ^ (lane & 7)) << 4);
        #pragma unroll
        for (int i = 0; i < 16; i++) ldsm4t(fd[i].x, fd[i].y, fd[i].z, fd[i].w, (wa ^ (((i >> 1) & 3) * 32)) + (i >> 3) * 4096 + (i & 1) * 2048);
        if (L == 0 && GDP == 1) named_arrive(N_GD, 288);
        if (L == 0 && DDP == 1) named_arrive(N_DD, 288);
        uint32_t n = 0;
        while ((xrow.x == SENT || xrow.y == SENT) && ++n < SPIN_MAX) xrow = ld_relaxed2(xp);
        spin_check(n);
        __syncwarp();
    }
    if (L == 0 && GDP == 2) named_arrive(N_GD, 288);
    if (L == 0 && DDP == 2) named_arrive(N_DD, 288);
    TL(0, L, 17);
    {
        const float nb = -rt.mean * rt.rstd;
        const uint32_t n0 = pack_bf16(fmaf(bf_lo(xrow.x), rt.rstd, nb), fmaf(bf_hi(xrow.x), rt.rstd, nb));
        const uint32_t n1 = pack_bf16(fmaf(bf_lo(xrow.y), rt.rstd, nb), fmaf(bf_hi(xrow.y), rt.rstd, nb));
        float gu[4][4];
        #pragma unroll
        for (int i = 0; i < 4; i++) { gu[i][0] = 0.f; gu[i][1] = 0.f; gu[i][2] = 0.f; gu[i][3] = 0.f; }
        #pragma unroll
        for (int ks = 0; ks < 8; ks++) {
            const uint32_t b0 = __shfl_sync(0xffffffffu, n0, 4 * ks + t), b1 = __shfl_sync(0xffffffffu, n1, 4 * ks + t);
            #pragma unroll
            for (int i = 0; i < 4; i++) {
                const uint4& a = fa[(ks >> 1) * 8 + (i >> 1) * 4 + (ks & 1) * 2 + (i & 1)];
                mma_bf16(gu[i], a.x, a.y, a.z, a.w, b0, b1);
            }
        }
        stsf(SB + OFF_PART + (W * 64 + t * 16 + g) * 4, sel4(t, gu[0][0], gu[1][0], gu[2][0], gu[3][0]));
        stsf(SB + OFF_PART + (W * 64 + t * 16 + g + 8) * 4, sel4(t, gu[0][2], gu[1][2], gu[2][2], gu[3][2]));
    }
    named_sync(1, 256);
    TL(0, L, 18);
    {
        float gp[8], up[8];
        #pragma unroll
        for (int i = 0; i < 8; i++) gp[i] = ldsf(SB + OFF_PART + (i * 64 + lane) * 4);
        #pragma unroll
        for (int i = 0; i < 8; i++) up[i] = ldsf(SB + OFF_PART + (i * 64 + 32 + lane) * 4);
        const float gv = bf_round(((gp[0] + gp[1]) + (gp[2] + gp[3])) + ((gp[4] + gp[5]) + (gp[6] + gp[7])));
        const float uv = bf_round(((up[0] + up[1]) + (up[2] + up[3])) + ((up[4] + up[5]) + (up[6] + up[7])));
        const float hv = bf_round(gv * rcp(1.f + ex2(gv * -1.4426950408889634f))) * uv;
        const uint32_t hp = pack_bf16(hv, __shfl_down_sync(0xffffffffu, hv, 1));
        uint32_t hb[4];
        #pragma unroll
        for (int i = 0; i < 4; i++) hb[i] = __shfl_sync(0xffffffffu, hp, 8 * i + 2 * t);
        float y[8][4];
        #pragma unroll
        for (int mb = 0; mb < 8; mb++) {
            y[mb][0] = 0.f; y[mb][1] = 0.f; y[mb][2] = 0.f; y[mb][3] = 0.f;
            #pragma unroll
            for (int ks = 0; ks < 2; ks++) mma_bf16(y[mb], fd[2*mb + ks].x, fd[2*mb + ks].y, fd[2*mb + ks].z, fd[2*mb + ks].w, hb[2 * ks], hb[2 * ks + 1]);
        }
        st_relaxed4_if(&g_ypart[L][min(c, NFC - 1)][tid * 4], make_uint4(not_sent(sel4(t, y[0][0], y[2][0], y[4][0], y[6][0])), not_sent(sel4(t, y[0][2], y[2][2], y[4][2], y[6][2])),
                       not_sent(sel4(t, y[1][0], y[3][0], y[5][0], y[7][0])), not_sent(sel4(t, y[1][2], y[3][2], y[5][2], y[7][2]))), ffn);
    }
    if (L == 0 && DDP == 3) named_arrive(N_DD, 288);
    TL(0, L, 19);
    if (L == 1) {
        if (W == 7) ctr_wait(&g_xc[1][rt.idx >> 8], 32);
        unsigned short* dst = reinterpret_cast<unsigned short*>(out) + (size_t)rt.idx * D_ + ypos_col(c * 8 + (tid & 7));
        asm volatile("" : "+l"(dst));
        const float v = ffn_finish<256>(1, rt, tid, SB + OFF_FE, 1);
        if (tid < 8) asm volatile("st.global.u16 [%0], %1;" :: "l"(dst), "h"((unsigned short)(__float_as_uint(v) >> 16)) : "memory");
        TL(0, L, 20);
    }
}

#define FW0 9
#define RK0 7
#define BAL 1500
#define KW1 4
static_assert(FW0 >= 8 && KW1 >= 3 && KW1 < 7, "buffer reuse");
__device__ __forceinline__ void qkv_fill(const CUtensorMap* tx, const CUtensorMap* tw, uint32_t bar, int st, int k) {
    const uint32_t sa = SB + st * Q_STB;
    mbar_expect_tx(bar, Q_STB);
    tma_load(sa, tx, k * 64, (blockIdx.x >> 4) * 256, bar);
    tma_load3(sa + Q_ABYTES, tw, (blockIdx.x & 15) * 64, k * 64, 0, bar);
}
__device__ __forceinline__ void oproj_fill(const Maps& mp, const char* osrc, int s, int par, int pair, int L, int k) {
    const uint32_t fb = B_OF + 8 * s, sa = SB + o_stage(s);
    mbar_expect_tx(fb, 32768);
    bulk_load(sa, osrc + (par * 16 + pair) * 8192, 16384, fb);
    tma_load5(sa + 16384, &mp.wo, 0, 0, par, pair, blockIdx.x & 14, fb);
}
__device__ __forceinline__ void producer_role(const Maps& mp) {
    const int c = blockIdx.x, mt = c >> 4, nt = c & 15, lane = threadIdx.x & 31;
    #pragma unroll 1
    for (int i = 2; i < 13; i++) tm_prefetch(&mp.xa0 + i);
    #pragma unroll 1
    for (int L = 0; L < 2; L++) {
        const uint32_t rb = L * 32;
        uint32_t st = 0, ph = L;
        #pragma unroll 1
        for (int k = L == 0 ? 3 : 0; k < 16; k++) {
            if (k == 0) { ctr_wait_all(&g_xc[0][mt], 32); fence_async_global(); named_sync(N_GD, 288); }
            if (k == 1) named_sync(N_DD, 288);
            mbar_wait(rb + B_QE + 8 * st, ph);
            TL(k == 3 ? 256 : -1, L, 28);
            qkv_fill(L == 0 ? &mp.xa0 : &mp.xa, &mp.wqkv, rb + B_QF + 8 * st, st, k);
            if (L == 1 && k >= RK0 && k < RK0 + 4) {
                if (k == RK0) mbar_expect_tx(B_SW, 4 * 12288);
                tma_load(SB + OFF_SIDE + (k - RK0) * 12288, &mp.r, c * 24, (k - RK0) * 256, B_SW);
            }
            if (++st == 3) { st = 0; ph ^= 1; }
        }
        mbar_wait(B_KV0, L);
        mbar_arrive_elect(rb + B_AF);
        TL(256, L, 29);
        {
            const int win = nt * 16 + ((mt + 1) & 7);
            mbar_expect_tx(rb + B_AF + 8, KV_WIN);
            #pragma unroll 1
            for (int h = 0; h < 2; h++) {
                ctr_wait_all(&g_kvc[L][0][0] + win, 2 + h);
                fence_async_global();
                bulk_load(SB + A_WIN + h * 16384, g_kv + (size_t)win * KV_WIN + h * 16384, 16384, rb + B_AF + 8);
            }
            TL(256, L, 7);
        }
        st = 2; ph = 1;
        #pragma unroll 1
        for (int w = 2; w < 16; w++) {
            const int win = nt * 16 + (w & 8) + ((mt + w) & 7);
            if (w <= 3 || w == 8) {
                ctr_wait_all(&g_kvc[L][0][0] + (w < 3 ? win : (win & ~7) + (lane & 7)), 3);
                fence_async_global();
            }
            mbar_wait(rb + B_AE + 8 * st, ph);
            mbar_expect_tx(rb + B_AF + 8 * st, KV_WIN);
            bulk_load(SB + st * A_WIN, g_kv + (size_t)win * KV_WIN, KV_WIN, rb + B_AF + 8 * st);
            if (w == KW1 || w == FW0) named_arrive(w == FW0 ? N_FW : N_KV1, 64);
            if (++st == 3) { st = 0; ph ^= 1; }
        }
        ctr_wait_all(&g_oc[L][mt * 2 + (nt & 1)][0][lane & 15], 1);
        fence_async_global();
        const char* osrc = g_o + (size_t)(mt * 2 + (nt & 1)) * 32 * 8192;
        #pragma unroll
        for (int k = 0; k < 4; k++) {
            mbar_wait(k < 2 ? rb + B_AE + 8 + 8 * k : k == 2 ? rb + B_AE : B_QAF, k < 2 ? 0 : k == 2 ? 1 : L);
            oproj_fill(mp, osrc, k, 0, 2 * k, L, k);
        }
        uint32_t ready = 0xFFFFu;
        #pragma unroll 1
        for (int k4 = 1; k4 < 4; k4++) {
            #pragma unroll
            for (int s = 0; s < 4; s++) {
                const int p = k4 * 8 + 2 * s;
                if (!((ready >> p) & 1)) {
                    ready = smem_wait_any(SB + OFF_M + M_ORDY + 4 * L, 1u << p);
                    fence_async_global();
                }
                mbar_wait(B_OE + 8 * s, (k4 - 1) & 1);
                oproj_fill(mp, osrc, s, p >> 4, p & 15, L, k4 * 4 + s);
            }
        }
        if (c < NFC) {
            mbar_expect_tx(B_FL, 5 * 16384);
            mbar_expect_tx(B_FD, 4 * 16384);
            #pragma unroll 1
            for (int i = 3; i < 12; i++) {
                mbar_wait(B_OE + (i < 5 ? 0 : i == 5 ? 8 : i < 9 ? 16 : 24), 1);
                if (i == 8) mbar_wait(B_FL, L);
                TL(i == 9 ? 256 : -1, L, 32);
                ffn_load(mp, c, i, SB + (i < 8 ? gu_piece(i) : OFF_FD + (i - 8) * 16384), i < 8 ? B_FL : B_FD, true);
            }
        }
    }
}

__global__ void __launch_bounds__(384, 1) k_all(const bf16* __restrict__ x0, const bf16* __restrict__ wo, const bf16* __restrict__ w_r, bf16* __restrict__ out,
                                                const __grid_constant__ Maps mp) {
    extern __shared__ __align__(1024) char smem[];
    if (smem_u32(smem) != SB) __trap();
    const int warp = warp_uniform(threadIdx.x >> 5), wg = warp >> 2;
    TL(0, 0, 0);
    {
        const int grp = warp >= 8 ? warp - 8 : warp + 4;
        #pragma unroll
        for (int i = 0; i < 4; i++) mbar_init(BB + grp * 32 + i * 8, grp < 7 ? 1 : grp < 10 ? 2 : 8);
        fence_mbar_init();
    }
    if (warp == 8) {
        #pragma unroll 1
        for (int s = 0; s < 3; s++) qkv_fill(&mp.xa0, &mp.wqkv, B_QF + 8 * s, s, s);
    }
    __syncthreads();
    if (wg == 2) {
        reg_dec<40>();
        if (warp == 8) producer_role(mp);
        else side_role(mp, x0, wo, w_r);
        if (gridDim.y == 2) {
            uint32_t v = threadIdx.x;
            #pragma unroll
            for (int i = 0; i < BAL; i++) asm volatile("fma.rn.f16x2 %0, %0, %0, %0;" : "+r"(v));
            sts32(SB, v);
        }
    } else {
        reg_inc<232>();
        #pragma unroll 1
        for (int L = 0; L < 2; L++) {
            qkv_phase(L, wg);
            attention_phase(L, wg);
            oproj_phase(L, wg, out);
        }
    }
}

typedef CUresult (*EncodeFn)(CUtensorMap*, CUtensorMapDataType, cuuint32_t, void*, const cuuint64_t*, const cuuint64_t*, const cuuint32_t*,
                             const cuuint32_t*, CUtensorMapInterleave, CUtensorMapSwizzle, CUtensorMapL2promotion, CUtensorMapFloatOOBfill);

void make_map(EncodeFn enc, CUtensorMap* tm, const void* ptr, int rank, const cuuint64_t* dims, const cuuint64_t* strides, const cuuint32_t* box, CUtensorMapSwizzle sw) {
    const cuuint32_t es[5] = {1, 1, 1, 1, 1};
    enc(tm, CU_TENSOR_MAP_DATA_TYPE_BFLOAT16, rank, const_cast<void*>(ptr), dims, strides, box, es, CU_TENSOR_MAP_INTERLEAVE_NONE, sw,
        box[0] == 64 ? CU_TENSOR_MAP_L2_PROMOTION_L2_128B : CU_TENSOR_MAP_L2_PROMOTION_NONE, CU_TENSOR_MAP_FLOAT_OOB_FILL_NONE);
}
void make_map2(EncodeFn enc, CUtensorMap* tm, const void* ptr, uint64_t cols, uint64_t rows, uint32_t bc, uint32_t br, CUtensorMapSwizzle sw) {
    const cuuint64_t dims[2] = {cols, rows}, strides[1] = {cols * 2};
    const cuuint32_t box[2] = {bc, br};
    make_map(enc, tm, ptr, 2, dims, strides, box, sw);
}

}

extern "C" void kernel_launch(void* const* d_in, const int* in_sizes, int n_in, void* d_out, int out_size) {
    const bf16* x0 = (const bf16*)d_in[0];
    const bf16* wqkv = (const bf16*)d_in[1];
    const bf16* wo = (const bf16*)d_in[2];
    const bf16* w_r = (const bf16*)d_in[4];
    const bf16* w_gate = (const bf16*)d_in[5];
    const bf16* w_up = (const bf16*)d_in[6];
    const bf16* w_down = (const bf16*)d_in[7];

    EncodeFn enc = nullptr;
    cudaDriverEntryPointQueryResult qr;
    cudaGetDriverEntryPoint("cuTensorMapEncodeTiled", (void**)&enc, cudaEnableDefault, &qr);
    void* p_x;
    cudaGetSymbolAddress(&p_x, g_x);
    Maps mp;
    const CUtensorMapSwizzle S128 = CU_TENSOR_MAP_SWIZZLE_128B;
    make_map2(enc, &mp.x0, x0, D_, S_, 64, 64, S128);
    make_map2(enc, &mp.x, p_x, D_, S_, 64, 64, S128);
    make_map2(enc, &mp.out, d_out, D_, S_, 64, 16, S128);
    make_map2(enc, &mp.xs, p_x, D_, S_, 64, 16, S128);
    make_map2(enc, &mp.xa0, x0, D_, S_, 64, 256, S128);
    make_map2(enc, &mp.xa, p_x, D_, S_, 64, 256, S128);
    make_map2(enc, &mp.w64, wqkv, 3 * D_, D_, 64, 64, S128);
    {
        const cuuint64_t dims[3] = {D_, D_, 3}, strides[2] = {3 * D_ * 2, D_ * 2};
        const cuuint32_t box[3] = {64, 64, 3};
        make_map(enc, &mp.wqkv, wqkv, 3, dims, strides, box, S128);
    }
    make_map2(enc, &mp.r, wqkv, 3 * D_, D_, 24, 256, CU_TENSOR_MAP_SWIZZLE_NONE);
    make_map2(enc, &mp.g, w_gate, FF, D_, 32, 256, CU_TENSOR_MAP_SWIZZLE_64B);
    make_map2(enc, &mp.u, w_up, FF, D_, 32, 256, CU_TENSOR_MAP_SWIZZLE_64B);
    {
        const cuuint64_t dims[5] = {64, 32, 2, 16, 16}, strides[4] = {D_ * 2, 32 * D_ * 2, 64 * D_ * 2, 128};
        const cuuint32_t box[5] = {64, 32, 1, 2, 2};
        make_map(enc, &mp.wo, wo, 5, dims, strides, box, S128);
    }
    {
        const cuuint64_t dims[3] = {64, FF, 16}, strides[2] = {D_ * 2, 128};
        const cuuint32_t box[3] = {64, 32, 4};
        make_map(enc, &mp.d, w_down, 3, dims, strides, box, S128);
    }
    cudaFuncSetAttribute(k_all, cudaFuncAttributeMaxDynamicSharedMemorySize, K_SMEM);
    k_all<<<128, 384, K_SMEM, cudaStreamPerThread>>>(x0, wo, w_r, (bf16*)d_out, mp);
}
```

```cpp
#include <cuda_runtime.h>
#include <cuda_bf16.h>
#include <cuda_fp16.h>
#include <cuda.h>
#include <cudaTypedefs.h>
#include <stdint.h>

namespace {

typedef __nv_bfloat16 bf16;

constexpr int S_ = 2048, D_ = 1024, NH = 32, FF = 3584, NFC = FF / 32;
constexpr float LN_EPS = 1e-5f;
constexpr float QSCALE = 0.17677669529663687f * 1.4426950408889634f;
constexpr uint32_t SENT = 0xFFFFFFFFu;

constexpr int KV_WIN = 32768;
__device__ __align__(1024) char g_kv[NH * 8 * KV_WIN];
__device__ __align__(1024) char g_o[32 * 2 * 16 * 4096];
__device__ __align__(1024) bf16 g_x[S_ * D_];
__device__ float g_csum[8 * 3 * D_];
__device__ float g_wsq[8 * 96];
__device__ float2 g_rs0[S_];
__device__ __align__(128) double g_acc[2][S_][4];
__device__ __align__(128) uint4 g_sums[S_];
__device__ __align__(128) uint32_t g_ypart[2][NFC][D_];
__device__ __align__(128) uint4 g_tab[2][8][16][2];
__device__ __align__(128) uint32_t g_xrow[2][16][D_ / 2];
__device__ __align__(128) uint32_t g_x2row[D_];
__device__ __align__(128) uint32_t g_fix[3 * D_];
__device__ uint32_t g_c0;
__device__ __align__(128) uint32_t g_kvc[2][NH][8];
__device__ __align__(128) uint32_t g_oc[2][16][2][16];
__device__ __align__(128) uint32_t g_xc[2][8];
struct RouteOut { int idx; float r; float mean; float rstd; };

constexpr uint32_t SB = 1024;

__device__ __forceinline__ uint32_t smem_u32(const void* p) { return (uint32_t)__cvta_generic_to_shared(p); }
__device__ __forceinline__ void mbar_arrive(uint32_t bar) { asm volatile("mbarrier.arrive.shared::cta.b64 _, [%0];" :: "r"(bar) : "memory"); }
__device__ __forceinline__ void mbar_wait(uint32_t bar, uint32_t parity) {
    asm volatile("{\n.reg .pred p, q;\n.reg .u32 n;\nmov.u32 n, 0;\n"
                 "LAB_WAIT:\nadd.u32 n, n, 1;\nmbarrier.try_wait.parity.shared::cta.b64 p, [%0], %1;\n"
                 "setp.lt.and.u32 q, n, 0x800000, !p;\n@q bra LAB_WAIT;\n@!p st.shared.u32 [n], n;\n}" :: "r"(bar), "r"(parity) : "memory");
}
__device__ __forceinline__ void mbar_arrive_elect(uint32_t bar) {
    asm volatile("{\n.reg .pred p;\nelect.sync _|p, 0xffffffff;\n@p mbarrier.arrive.shared::cta.b64 _, [%0];\n}" :: "r"(bar) : "memory");
}
__device__ __forceinline__ int tid_now() { int v; asm volatile("mov.u32 %0, %%tid.x;" : "=r"(v)); return v; }
__device__ __forceinline__ int cta_now() { int v; asm volatile("mov.u32 %0, %%ctaid.x;" : "=r"(v)); return v; }
__device__ __forceinline__ int warp_uniform(int v) { return __shfl_sync(0xffffffffu, v, 0); }
__device__ __forceinline__ void fence_mbar_init() { asm volatile("fence.mbarrier_init.release.cluster;" ::: "memory"); }
__device__ __forceinline__ void fence_async_smem() { asm volatile("fence.proxy.async.shared::cta;" ::: "memory"); }
__device__ __forceinline__ void fence_async_global() { asm volatile("fence.proxy.async.global;" ::: "memory"); }
__device__ __forceinline__ void named_sync(int id, int n) { asm volatile("bar.sync %0, %1;" :: "r"(id), "r"(n) : "memory"); }
__device__ __forceinline__ void named_arrive(int id, int n) { asm volatile("bar.arrive %0, %1;" :: "r"(id), "r"(n) : "memory"); }
__device__ __forceinline__ bool named_any(bool p, int id) {
    uint32_t r;
    asm volatile("{\n.reg .pred a, b;\nsetp.ne.u32 a, %1, 0;\nbarrier.cta.red.or.pred b, %2, 128, a;\nselp.u32 %0, 1, 0, b;\n}" : "=r"(r) : "r"((uint32_t)p), "r"(id) : "memory");
    return r != 0;
}
#define ELECT(op) "{\n.reg .pred e;\nelect.sync _|e, 0xffffffff;\n@e " op "\n}"
__device__ __forceinline__ void mbar_init(uint32_t bar, int cnt) { asm volatile(ELECT("mbarrier.init.shared::cta.b64 [%0], %1;") :: "r"(bar), "r"(cnt) : "memory"); }
__device__ __forceinline__ void mbar_expect_tx(uint32_t bar, uint32_t bytes) { asm volatile(ELECT("mbarrier.arrive.expect_tx.shared::cta.b64 _, [%0], %1;") :: "r"(bar), "r"(bytes) : "memory"); }
__device__ __forceinline__ void bulk_load(uint32_t dst, const void* src, uint32_t bytes, uint32_t bar) {
    asm volatile(ELECT("cp.async.bulk.shared::cluster.global.mbarrier::complete_tx::bytes [%0], [%1], %2, [%3];") :: "r"(dst), "l"(src), "r"(bytes), "r"(bar) : "memory");
}
__device__ __forceinline__ void bulk_store(void* dst, uint32_t src, uint32_t bytes) {
    asm volatile(ELECT("cp.async.bulk.global.shared::cta.bulk_group [%0], [%1], %2;") :: "l"(dst), "r"(src), "r"(bytes) : "memory");
}
__device__ __forceinline__ void bulk_commit() { asm volatile("cp.async.bulk.commit_group;" ::: "memory"); }
__device__ __forceinline__ void bulk_wait() { asm volatile("cp.async.bulk.wait_group 0;" ::: "memory"); }
template <int N> __device__ __forceinline__ void bulk_wait_n() { asm volatile("cp.async.bulk.wait_group %0;" :: "n"(N) : "memory"); }
__device__ __forceinline__ void l2_prefetch(const void* src, uint32_t bytes) {
    asm volatile(ELECT("cp.async.bulk.prefetch.L2.global [%0], %1;") :: "l"(src), "r"(bytes) : "memory");
}
__device__ __forceinline__ void tma_load(uint32_t dst, const CUtensorMap* tm, int c0, int c1, uint32_t bar) {
    asm volatile(ELECT("cp.async.bulk.tensor.2d.shared::cluster.global.mbarrier::complete_tx::bytes [%0], [%1, {%3, %4}], [%2];")
                 :: "r"(dst), "l"(tm), "r"(bar), "r"(c0), "r"(c1) : "memory");
}
__device__ __forceinline__ void tma_load3(uint32_t dst, const CUtensorMap* tm, int c0, int c1, int c2, uint32_t bar) {
    asm volatile(ELECT("cp.async.bulk.tensor.3d.shared::cluster.global.mbarrier::complete_tx::bytes [%0], [%1, {%3, %4, %5}], [%2];")
                 :: "r"(dst), "l"(tm), "r"(bar), "r"(c0), "r"(c1), "r"(c2) : "memory");
}
__device__ __forceinline__ uint64_t evict_first() { uint64_t a; asm("createpolicy.fractional.L2::evict_first.b64 %0, 1.0;" : "=l"(a)); return a; }
__device__ __forceinline__ void tma_load_h(uint32_t dst, const CUtensorMap* tm, int c0, int c1, uint32_t bar, bool ef) {
    if (!ef) tma_load(dst, tm, c0, c1, bar);
    else asm volatile(ELECT("cp.async.bulk.tensor.2d.shared::cluster.global.mbarrier::complete_tx::bytes.L2::cache_hint [%0], [%1, {%3, %4}], [%2], %5;")
                      :: "r"(dst), "l"(tm), "r"(bar), "r"(c0), "r"(c1), "l"(evict_first()) : "memory");
}
__device__ __forceinline__ void tma_load3_h(uint32_t dst, const CUtensorMap* tm, int c0, int c1, int c2, uint32_t bar, bool ef) {
    if (!ef) tma_load3(dst, tm, c0, c1, c2, bar);
    else asm volatile(ELECT("cp.async.bulk.tensor.3d.shared::cluster.global.mbarrier::complete_tx::bytes.L2::cache_hint [%0], [%1, {%3, %4, %5}], [%2], %6;")
                      :: "r"(dst), "l"(tm), "r"(bar), "r"(c0), "r"(c1), "r"(c2), "l"(evict_first()) : "memory");
}
__device__ __forceinline__ void tma_load5(uint32_t dst, const CUtensorMap* tm, int c0, int c1, int c2, int c3, int c4, uint32_t bar) {
    asm volatile(ELECT("cp.async.bulk.tensor.5d.shared::cluster.global.mbarrier::complete_tx::bytes [%0], [%1, {%3, %4, %5, %6, %7}], [%2];")
                 :: "r"(dst), "l"(tm), "r"(bar), "r"(c0), "r"(c1), "r"(c2), "r"(c3), "r"(c4) : "memory");
}
__device__ __forceinline__ void tma_store(const CUtensorMap* tm, uint32_t src, int c0, int c1) {
    asm volatile(ELECT("cp.async.bulk.tensor.2d.global.shared::cta.bulk_group [%0, {%2, %3}], [%1];") :: "l"(tm), "r"(src), "r"(c0), "r"(c1) : "memory");
}
__device__ __forceinline__ void tm_prefetch(const CUtensorMap* tm) { asm volatile(ELECT("prefetch.tensormap [%0];") :: "l"(tm) : "memory"); }
__device__ __forceinline__ uint32_t lds32(uint32_t a) { uint32_t v; asm volatile("ld.shared.b32 %0, [%1];" : "=r"(v) : "r"(a) : "memory"); return v; }
__device__ __forceinline__ float ldsf(uint32_t a) { return __uint_as_float(lds32(a)); }
__device__ __forceinline__ float2 lds64f(uint32_t a) { float2 v; asm volatile("ld.shared.v2.f32 {%0, %1}, [%2];" : "=f"(v.x), "=f"(v.y) : "r"(a) : "memory"); return v; }
__device__ __forceinline__ uint4 lds128(uint32_t a) { uint4 v; asm volatile("ld.shared.v4.b32 {%0, %1, %2, %3}, [%4];" : "=r"(v.x), "=r"(v.y), "=r"(v.z), "=r"(v.w) : "r"(a) : "memory"); return v; }
__device__ __forceinline__ void sts32(uint32_t a, uint32_t v) { asm volatile("st.shared.b32 [%0], %1;" :: "r"(a), "r"(v) : "memory"); }
__device__ __forceinline__ void stsf(uint32_t a, float v) { sts32(a, __float_as_uint(v)); }
__device__ __forceinline__ void sts64f(uint32_t a, float x, float y) { asm volatile("st.shared.v2.f32 [%0], {%1, %2};" :: "r"(a), "f"(x), "f"(y) : "memory"); }
__device__ __forceinline__ void sts128(uint32_t a, const uint4& v) { asm volatile("st.shared.v4.b32 [%0], {%1, %2, %3, %4};" :: "r"(a), "r"(v.x), "r"(v.y), "r"(v.z), "r"(v.w) : "memory"); }
__device__ __forceinline__ void stsm4(uint32_t a, uint32_t x, uint32_t y, uint32_t z, uint32_t w) {
    asm volatile("stmatrix.sync.aligned.m8n8.x4.shared.b16 [%0], {%1, %2, %3, %4};" :: "r"(a), "r"(x), "r"(y), "r"(z), "r"(w) : "memory");
}
__device__ __forceinline__ void ldsm4(uint32_t& a0, uint32_t& a1, uint32_t& a2, uint32_t& a3, uint32_t addr) {
    asm volatile("ldmatrix.sync.aligned.m8n8.x4.shared.b16 {%0,%1,%2,%3}, [%4];" : "=r"(a0), "=r"(a1), "=r"(a2), "=r"(a3) : "r"(addr) : "memory");
}
__device__ __forceinline__ void ldsm4t(uint32_t& a0, uint32_t& a1, uint32_t& a2, uint32_t& a3, uint32_t addr) {
    asm volatile("ldmatrix.sync.aligned.m8n8.x4.trans.shared.b16 {%0,%1,%2,%3}, [%4];" : "=r"(a0), "=r"(a1), "=r"(a2), "=r"(a3) : "r"(addr) : "memory");
}
__device__ __forceinline__ void mma_bf16(float (&c)[4], uint32_t a0, uint32_t a1, uint32_t a2, uint32_t a3, uint32_t b0, uint32_t b1) {
    asm("mma.sync.aligned.m16n8k16.row.col.f32.bf16.bf16.f32 {%0,%1,%2,%3}, {%4,%5,%6,%7}, {%8,%9}, {%0,%1,%2,%3};"
        : "+f"(c[0]), "+f"(c[1]), "+f"(c[2]), "+f"(c[3]) : "r"(a0), "r"(a1), "r"(a2), "r"(a3), "r"(b0), "r"(b1));
}
__device__ __forceinline__ void mma_f16(float (&c)[4], uint32_t a0, uint32_t a1, uint32_t a2, uint32_t a3, uint32_t b0, uint32_t b1) {
    asm("mma.sync.aligned.m16n8k16.row.col.f32.f16.f16.f32 {%0,%1,%2,%3}, {%4,%5,%6,%7}, {%8,%9}, {%0,%1,%2,%3};"
        : "+f"(c[0]), "+f"(c[1]), "+f"(c[2]), "+f"(c[3]) : "r"(a0), "r"(a1), "r"(a2), "r"(a3), "r"(b0), "r"(b1));
}
__device__ __forceinline__ uint32_t ld_acquire(const void* p) { uint32_t v; asm volatile("ld.acquire.gpu.global.u32 %0, [%1];" : "=r"(v) : "l"(p) : "memory"); return v; }
__device__ __forceinline__ void sts_release(uint32_t a, uint32_t v) { asm volatile("st.release.cta.shared.u32 [%0], %1;" :: "r"(a), "r"(v) : "memory"); }
__device__ __forceinline__ uint32_t ld_relaxed(const void* p) { uint32_t v; asm volatile("ld.relaxed.gpu.global.u32 %0, [%1];" : "=r"(v) : "l"(p) : "memory"); return v; }
__device__ __forceinline__ uint4 ld_relaxed4(const void* p) {
    uint4 v; asm volatile("ld.relaxed.gpu.global.v4.b32 {%0, %1, %2, %3}, [%4];" : "=r"(v.x), "=r"(v.y), "=r"(v.z), "=r"(v.w) : "l"(p) : "memory"); return v;
}
__device__ __forceinline__ uint2 ld_relaxed2(const void* p) { uint2 v; asm volatile("ld.relaxed.gpu.global.v2.b32 {%0, %1}, [%2];" : "=r"(v.x), "=r"(v.y) : "l"(p) : "memory"); return v; }
__device__ __forceinline__ void st_relaxed(void* p, uint32_t v) { asm volatile("st.relaxed.gpu.global.u32 [%0], %1;" :: "l"(p), "r"(v) : "memory"); }
__device__ __forceinline__ void st_relaxed4_if(void* p, const uint4& v, bool on) {
    asm volatile("{\n.reg .pred q;\nsetp.ne.u32 q, %5, 0;\n@q st.relaxed.gpu.global.v4.b32 [%0], {%1, %2, %3, %4};\n}"
                 :: "l"(p), "r"(v.x), "r"(v.y), "r"(v.z), "r"(v.w), "r"((uint32_t)on) : "memory");
}
__device__ __forceinline__ uint32_t not_sent(float v) { const uint32_t u = __float_as_uint(v); return u == SENT ? 0x7FFFFFFFu : u; }
__device__ __forceinline__ bool has_sent(const uint4& v) { return max(max(v.x, v.y), max(v.z, v.w)) == SENT; }
constexpr uint32_t SPIN_MAX = 1u << 22;
__device__ __forceinline__ void spin_check(uint32_t n) { asm volatile("{\n.reg .pred p;\nsetp.ge.u32 p, %0, %1;\n@p st.global.u32 [%2], %0;\n}" :: "r"(n), "n"(SPIN_MAX), "l"(0ull) : "memory"); }
__device__ __forceinline__ void ctr_arrive(uint32_t* c, uint32_t n = 1) { asm volatile(ELECT("red.release.gpu.global.add.u32 [%0], %1;") :: "l"(c), "r"(n) : "memory"); }
__device__ __forceinline__ void ctr_wait(const uint32_t* c, uint32_t target) {
    asm volatile("{\n.reg .pred p;\n.reg .u32 n, v;\nmov.u32 n, 0;\n"
                 "LAB_WAIT:\nld.acquire.gpu.global.u32 v, [%0];\nsetp.ge.u32 p, v, %1;\n@p bra LAB_DONE;\n"
                 "add.u32 n, n, 1;\nsetp.lt.u32 p, n, 0x400000;\n@p bra LAB_WAIT;\ntrap;\nLAB_DONE:\n}" :: "l"(c), "r"(target) : "memory");
}
__device__ __forceinline__ void ctr_wait_all(const uint32_t* c, uint32_t target) {
    asm volatile("{\n.reg .pred p;\n.reg .u32 n, v;\nmov.u32 n, 0;\n"
                 "LAB_WAIT:\nld.acquire.gpu.global.u32 v, [%0];\nsetp.ge.u32 p, v, %1;\nvote.sync.all.pred p, p, 0xffffffff;\n@p bra.uni LAB_DONE;\n"
                 "add.u32 n, n, 1;\nsetp.lt.u32 p, n, 0x400000;\n@p bra.uni LAB_WAIT;\ntrap;\nLAB_DONE:\n}" :: "l"(c), "r"(target) : "memory");
}
__device__ __forceinline__ uint32_t smem_wait_any(uint32_t a, uint32_t mask) {
    uint32_t v;
    asm volatile("{\n.reg .pred p;\n.reg .u32 n, t;\nmov.u32 n, 0;\n"
                 "LAB_WAIT:\nld.acquire.cta.shared.u32 %0, [%1];\nand.b32 t, %0, %2;\nsetp.ne.u32 p, t, 0;\nvote.sync.all.pred p, p, 0xffffffff;\n@p bra.uni LAB_DONE;\n"
                 "add.u32 n, n, 1;\nsetp.lt.u32 p, n, 0x4000000;\n@p bra.uni LAB_WAIT;\ntrap;\nLAB_DONE:\n}" : "=r"(v) : "r"(a), "r"(mask) : "memory");
    return warp_uniform(v);
}
__device__ __forceinline__ void publish(uint32_t* c, uint32_t n = 1) { bulk_wait(); fence_async_global(); ctr_arrive(c, n); }

__device__ __forceinline__ void wg_fence() { asm volatile("wgmma.fence.sync.aligned;" ::: "memory"); }
__device__ __forceinline__ void wg_commit() { asm volatile("wgmma.commit_group.sync.aligned;" ::: "memory"); }
template <int N> __device__ __forceinline__ void wg_wait() { asm volatile("wgmma.wait_group.sync.aligned %0;" :: "n"(N) : "memory"); }
template <int N> __device__ __forceinline__ void reg_inc() { asm volatile("setmaxnreg.inc.sync.aligned.u32 %0;" :: "n"(N)); }
template <int N> __device__ __forceinline__ void reg_dec() { asm volatile("setmaxnreg.dec.sync.aligned.u32 %0;" :: "n"(N)); }
__host__ __device__ constexpr uint64_t desc_plain(uint32_t addr, uint32_t lbo, uint32_t sbo) {
    return (uint64_t)((addr & 0x3FFFF) >> 4) | ((uint64_t)(lbo >> 4) << 16) | ((uint64_t)(sbo >> 4) << 32);
}
__host__ __device__ constexpr uint64_t desc_sw128(uint32_t addr, uint32_t lbo, uint32_t sbo) { return desc_plain(addr, lbo, sbo) | (1ull << 62); }

__device__ __forceinline__ float ex2(float x) { float y; asm("ex2.approx.ftz.f32 %0, %1;" : "=f"(y) : "f"(x)); return y; }
__device__ __forceinline__ float rcp(float x) { float y; asm("rcp.approx.ftz.f32 %0, %1;" : "=f"(y) : "f"(x)); return y; }
__device__ __forceinline__ float rsq(float x) { float y; asm("rsqrt.approx.ftz.f32 %0, %1;" : "=f"(y) : "f"(x)); return y; }
__device__ __forceinline__ uint32_t pack_bf16(float lo, float hi) { uint32_t r; asm("cvt.rn.bf16x2.f32 %0, %1, %2;" : "=r"(r) : "f"(hi), "f"(lo)); return r; }
__device__ __forceinline__ uint32_t pack_f16(float lo, float hi) { uint32_t r; asm("cvt.rn.f16x2.f32 %0, %1, %2;" : "=r"(r) : "f"(hi), "f"(lo)); return r; }
__device__ __forceinline__ uint32_t round8(uint32_t v) { return (v + 0x00040004u) & 0xFFF8FFF8u; }
__device__ __forceinline__ float bf_lo(uint32_t v) { return __uint_as_float(v << 16); }
__device__ __forceinline__ float bf_hi(uint32_t v) { return __uint_as_float(v & 0xFFFF0000u); }
__device__ __forceinline__ float bf_round(float x) { return __uint_as_float(pack_bf16(0.f, x)); }
__device__ __forceinline__ uint32_t badd2(uint32_t a, uint32_t b) { uint32_t r; asm("add.rn.bf16x2 %0, %1, %2;" : "=r"(r) : "r"(a), "r"(b)); return r; }
__device__ __forceinline__ void h2_unpack(uint32_t v, float& lo, float& hi) {
    asm("{.reg .f16 l, h; mov.b32 {l, h}, %2; cvt.f32.f16 %0, l; cvt.f32.f16 %1, h;}" : "=f"(lo), "=f"(hi) : "r"(v));
}
__device__ __forceinline__ uint32_t add_ln2(uint32_t x, float rstd, float nb) { return badd2(x, pack_bf16(fmaf(bf_lo(x), rstd, nb), fmaf(bf_hi(x), rstd, nb))); }
__device__ __forceinline__ float sel4(int t, float a0, float a1, float a2, float a3) {
    float r;
    asm("{\n.reg .pred p, q;\n.reg .f32 x, y;\nsetp.ne.u32 p, %1, 0;\nsetp.ne.u32 q, %2, 0;\nselp.f32 x, %4, %3, p;\nselp.f32 y, %6, %5, p;\nselp.f32 %0, y, x, q;\n}"
        : "=f"(r) : "r"(t & 1), "r"(t & 2), "f"(a0), "f"(a1), "f"(a2), "f"(a3));
    return r;
}
__device__ __forceinline__ float warp_sum(float v) {
    #pragma unroll
    for (int o = 16; o > 0; o >>= 1) v += __shfl_xor_sync(0xffffffffu, v, o);
    return v;
}
__device__ __forceinline__ uint32_t redux_or(uint32_t v) { uint32_t r; asm volatile("redux.sync.or.b32 %0, %1, 0xffffffff;" : "=r"(r) : "r"(v)); return r; }
__device__ __forceinline__ uint32_t redux_max(uint32_t v) { uint32_t r; asm volatile("redux.sync.max.u32 %0, %1, 0xffffffff;" : "=r"(r) : "r"(v)); return r; }
__device__ __forceinline__ uint32_t redux_min(uint32_t v) { uint32_t r; asm volatile("redux.sync.min.u32 %0, %1, 0xffffffff;" : "=r"(r) : "r"(v)); return r; }


__device__ __forceinline__ void wg_gemm_n128(float (&d)[64], uint64_t desca, uint64_t desc) {
    asm volatile("{\n.reg .pred p;\nsetp.ne.b32 p, 1, 0;\n"
        "wgmma.mma_async.sync.aligned.m64n128k16.f32.bf16.bf16 "
        "{%0,%1,%2,%3,%4,%5,%6,%7,%8,%9,%10,%11,%12,%13,%14,%15,%16,%17,%18,%19,%20,%21,%22,%23,%24,%25,%26,%27,%28,%29,%30,%31,%32,%33,%34,%35,%36,%37,%38,%39,%40,%41,%42,%43,%44,%45,%46,%47,%48,%49,%50,%51,%52,%53,%54,%55,%56,%57,%58,%59,%60,%61,%62,%63}, "
        "%64, %65, p, 1, 1, 0, 1;\n}\n"
        : "+f"(d[0]), "+f"(d[1]), "+f"(d[2]), "+f"(d[3]), "+f"(d[4]), "+f"(d[5]), "+f"(d[6]), "+f"(d[7]),
          "+f"(d[8]), "+f"(d[9]), "+f"(d[10]), "+f"(d[11]), "+f"(d[12]), "+f"(d[13]), "+f"(d[14]), "+f"(d[15]),
          "+f"(d[16]), "+f"(d[17]), "+f"(d[18]), "+f"(d[19]), "+f"(d[20]), "+f"(d[21]), "+f"(d[22]), "+f"(d[23]),
          "+f"(d[24]), "+f"(d[25]), "+f"(d[26]), "+f"(d[27]), "+f"(d[28]), "+f"(d[29]), "+f"(d[30]), "+f"(d[31]),
          "+f"(d[32]), "+f"(d[33]), "+f"(d[34]), "+f"(d[35]), "+f"(d[36]), "+f"(d[37]), "+f"(d[38]), "+f"(d[39]),
          "+f"(d[40]), "+f"(d[41]), "+f"(d[42]), "+f"(d[43]), "+f"(d[44]), "+f"(d[45]), "+f"(d[46]), "+f"(d[47]),
          "+f"(d[48]), "+f"(d[49]), "+f"(d[50]), "+f"(d[51]), "+f"(d[52]), "+f"(d[53]), "+f"(d[54]), "+f"(d[55]),
          "+f"(d[56]), "+f"(d[57]), "+f"(d[58]), "+f"(d[59]), "+f"(d[60]), "+f"(d[61]), "+f"(d[62]), "+f"(d[63])
        : "l"(desca), "l"(desc));
}
__device__ __forceinline__ void wg_gemm_n128_init(float (&d)[64], uint64_t desca, uint64_t desc) {
    asm volatile("{\n.reg .pred p;\nsetp.ne.b32 p, 0, 0;\n"
        "wgmma.mma_async.sync.aligned.m64n128k16.f32.bf16.bf16 "
        "{%0,%1,%2,%3,%4,%5,%6,%7,%8,%9,%10,%11,%12,%13,%14,%15,%16,%17,%18,%19,%20,%21,%22,%23,%24,%25,%26,%27,%28,%29,%30,%31,%32,%33,%34,%35,%36,%37,%38,%39,%40,%41,%42,%43,%44,%45,%46,%47,%48,%49,%50,%51,%52,%53,%54,%55,%56,%57,%58,%59,%60,%61,%62,%63}, "
        "%64, %65, p, 1, 1, 0, 1;\n}\n"
        : "=f"(d[0]), "=f"(d[1]), "=f"(d[2]), "=f"(d[3]), "=f"(d[4]), "=f"(d[5]), "=f"(d[6]), "=f"(d[7]),
          "=f"(d[8]), "=f"(d[9]), "=f"(d[10]), "=f"(d[11]), "=f"(d[12]), "=f"(d[13]), "=f"(d[14]), "=f"(d[15]),
          "=f"(d[16]), "=f"(d[17]), "=f"(d[18]), "=f"(d[19]), "=f"(d[20]), "=f"(d[21]), "=f"(d[22]), "=f"(d[23]),
          "=f"(d[24]), "=f"(d[25]), "=f"(d[26]), "=f"(d[27]), "=f"(d[28]), "=f"(d[29]), "=f"(d[30]), "=f"(d[31]),
          "=f"(d[32]), "=f"(d[33]), "=f"(d[34]), "=f"(d[35]), "=f"(d[36]), "=f"(d[37]), "=f"(d[38]), "=f"(d[39]),
          "=f"(d[40]), "=f"(d[41]), "=f"(d[42]), "=f"(d[43]), "=f"(d[44]), "=f"(d[45]), "=f"(d[46]), "=f"(d[47]),
          "=f"(d[48]), "=f"(d[49]), "=f"(d[50]), "=f"(d[51]), "=f"(d[52]), "=f"(d[53]), "=f"(d[54]), "=f"(d[55]),
          "=f"(d[56]), "=f"(d[57]), "=f"(d[58]), "=f"(d[59]), "=f"(d[60]), "=f"(d[61]), "=f"(d[62]), "=f"(d[63])
        : "l"(desca), "l"(desc));
}
__device__ __forceinline__ void wg_gemm_n192(float (&d)[96], uint64_t desca, uint64_t desc) {
    asm volatile("{\n.reg .pred p;\nsetp.ne.b32 p, 1, 0;\n"
        "wgmma.mma_async.sync.aligned.m64n192k16.f32.bf16.bf16 "
        "{%0,%1,%2,%3,%4,%5,%6,%7,%8,%9,%10,%11,%12,%13,%14,%15,%16,%17,%18,%19,%20,%21,%22,%23,%24,%25,%26,%27,%28,%29,%30,%31,%32,%33,%34,%35,%36,%37,%38,%39,%40,%41,%42,%43,%44,%45,%46,%47,%48,%49,%50,%51,%52,%53,%54,%55,%56,%57,%58,%59,%60,%61,%62,%63,%64,%65,%66,%67,%68,%69,%70,%71,%72,%73,%74,%75,%76,%77,%78,%79,%80,%81,%82,%83,%84,%85,%86,%87,%88,%89,%90,%91,%92,%93,%94,%95}, "
        "%96, %97, p, 1, 1, 0, 1;\n}\n"
        : "+f"(d[0]), "+f"(d[1]), "+f"(d[2]), "+f"(d[3]), "+f"(d[4]), "+f"(d[5]), "+f"(d[6]), "+f"(d[7]),
          "+f"(d[8]), "+f"(d[9]), "+f"(d[10]), "+f"(d[11]), "+f"(d[12]), "+f"(d[13]), "+f"(d[14]), "+f"(d[15]),
          "+f"(d[16]), "+f"(d[17]), "+f"(d[18]), "+f"(d[19]), "+f"(d[20]), "+f"(d[21]), "+f"(d[22]), "+f"(d[23]),
          "+f"(d[24]), "+f"(d[25]), "+f"(d[26]), "+f"(d[27]), "+f"(d[28]), "+f"(d[29]), "+f"(d[30]), "+f"(d[31]),
          "+f"(d[32]), "+f"(d[33]), "+f"(d[34]), "+f"(d[35]), "+f"(d[36]), "+f"(d[37]), "+f"(d[38]), "+f"(d[39]),
          "+f"(d[40]), "+f"(d[41]), "+f"(d[42]), "+f"(d[43]), "+f"(d[44]), "+f"(d[45]), "+f"(d[46]), "+f"(d[47]),
          "+f"(d[48]), "+f"(d[49]), "+f"(d[50]), "+f"(d[51]), "+f"(d[52]), "+f"(d[53]), "+f"(d[54]), "+f"(d[55]),
          "+f"(d[56]), "+f"(d[57]), "+f"(d[58]), "+f"(d[59]), "+f"(d[60]), "+f"(d[61]), "+f"(d[62]), "+f"(d[63]),
          "+f"(d[64]), "+f"(d[65]), "+f"(d[66]), "+f"(d[67]), "+f"(d[68]), "+f"(d[69]), "+f"(d[70]), "+f"(d[71]),
          "+f"(d[72]), "+f"(d[73]), "+f"(d[74]), "+f"(d[75]), "+f"(d[76]), "+f"(d[77]), "+f"(d[78]), "+f"(d[79]),
          "+f"(d[80]), "+f"(d[81]), "+f"(d[82]), "+f"(d[83]), "+f"(d[84]), "+f"(d[85]), "+f"(d[86]), "+f"(d[87]),
          "+f"(d[88]), "+f"(d[89]), "+f"(d[90]), "+f"(d[91]), "+f"(d[92]), "+f"(d[93]), "+f"(d[94]), "+f"(d[95])
        : "l"(desca), "l"(desc));
}
__device__ __forceinline__ void wg_gemm_n192_init(float (&d)[96], uint64_t desca, uint64_t desc) {
    asm volatile("{\n.reg .pred p;\nsetp.ne.b32 p, 0, 0;\n"
        "wgmma.mma_async.sync.aligned.m64n192k16.f32.bf16.bf16 "
        "{%0,%1,%2,%3,%4,%5,%6,%7,%8,%9,%10,%11,%12,%13,%14,%15,%16,%17,%18,%19,%20,%21,%22,%23,%24,%25,%26,%27,%28,%29,%30,%31,%32,%33,%34,%35,%36,%37,%38,%39,%40,%41,%42,%43,%44,%45,%46,%47,%48,%49,%50,%51,%52,%53,%54,%55,%56,%57,%58,%59,%60,%61,%62,%63,%64,%65,%66,%67,%68,%69,%70,%71,%72,%73,%74,%75,%76,%77,%78,%79,%80,%81,%82,%83,%84,%85,%86,%87,%88,%89,%90,%91,%92,%93,%94,%95}, "
        "%96, %97, p, 1, 1, 0, 1;\n}\n"
        : "=f"(d[0]), "=f"(d[1]), "=f"(d[2]), "=f"(d[3]), "=f"(d[4]), "=f"(d[5]), "=f"(d[6]), "=f"(d[7]),
          "=f"(d[8]), "=f"(d[9]), "=f"(d[10]), "=f"(d[11]), "=f"(d[12]), "=f"(d[13]), "=f"(d[14]), "=f"(d[15]),
          "=f"(d[16]), "=f"(d[17]), "=f"(d[18]), "=f"(d[19]), "=f"(d[20]), "=f"(d[21]), "=f"(d[22]), "=f"(d[23]),
          "=f"(d[24]), "=f"(d[25]), "=f"(d[26]), "=f"(d[27]), "=f"(d[28]), "=f"(d[29]), "=f"(d[30]), "=f"(d[31]),
          "=f"(d[32]), "=f"(d[33]), "=f"(d[34]), "=f"(d[35]), "=f"(d[36]), "=f"(d[37]), "=f"(d[38]), "=f"(d[39]),
          "=f"(d[40]), "=f"(d[41]), "=f"(d[42]), "=f"(d[43]), "=f"(d[44]), "=f"(d[45]), "=f"(d[46]), "=f"(d[47]),
          "=f"(d[48]), "=f"(d[49]), "=f"(d[50]), "=f"(d[51]), "=f"(d[52]), "=f"(d[53]), "=f"(d[54]), "=f"(d[55]),
          "=f"(d[56]), "=f"(d[57]), "=f"(d[58]), "=f"(d[59]), "=f"(d[60]), "=f"(d[61]), "=f"(d[62]), "=f"(d[63]),
          "=f"(d[64]), "=f"(d[65]), "=f"(d[66]), "=f"(d[67]), "=f"(d[68]), "=f"(d[69]), "=f"(d[70]), "=f"(d[71]),
          "=f"(d[72]), "=f"(d[73]), "=f"(d[74]), "=f"(d[75]), "=f"(d[76]), "=f"(d[77]), "=f"(d[78]), "=f"(d[79]),
          "=f"(d[80]), "=f"(d[81]), "=f"(d[82]), "=f"(d[83]), "=f"(d[84]), "=f"(d[85]), "=f"(d[86]), "=f"(d[87]),
          "=f"(d[88]), "=f"(d[89]), "=f"(d[90]), "=f"(d[91]), "=f"(d[92]), "=f"(d[93]), "=f"(d[94]), "=f"(d[95])
        : "l"(desca), "l"(desc));
}
__device__ __forceinline__ void wg_qk_init(uint32_t (&d)[32], uint32_t a0, uint32_t a1, uint32_t a2, uint32_t a3, uint64_t desc) {
    asm volatile("{\n.reg .pred p;\nsetp.ne.b32 p, 0, 0;\n"
        "wgmma.mma_async.sync.aligned.m64n128k16.f16.f16.f16 "
        "{%0,%1,%2,%3,%4,%5,%6,%7,%8,%9,%10,%11,%12,%13,%14,%15,%16,%17,%18,%19,%20,%21,%22,%23,%24,%25,%26,%27,%28,%29,%30,%31}, "
        "{%32,%33,%34,%35}, %36, p, 1, 1, 0;\n}\n"
        : "=r"(d[0]), "=r"(d[1]), "=r"(d[2]), "=r"(d[3]), "=r"(d[4]), "=r"(d[5]), "=r"(d[6]), "=r"(d[7]),
          "=r"(d[8]), "=r"(d[9]), "=r"(d[10]), "=r"(d[11]), "=r"(d[12]), "=r"(d[13]), "=r"(d[14]), "=r"(d[15]),
          "=r"(d[16]), "=r"(d[17]), "=r"(d[18]), "=r"(d[19]), "=r"(d[20]), "=r"(d[21]), "=r"(d[22]), "=r"(d[23]),
          "=r"(d[24]), "=r"(d[25]), "=r"(d[26]), "=r"(d[27]), "=r"(d[28]), "=r"(d[29]), "=r"(d[30]), "=r"(d[31])
        : "r"(a0), "r"(a1), "r"(a2), "r"(a3), "l"(desc));
}
__device__ __forceinline__ void wg_qk_acc(uint32_t (&d)[32], uint64_t desca, uint64_t desc) {
    asm volatile("{\n.reg .pred p;\nsetp.ne.b32 p, 1, 0;\n"
        "wgmma.mma_async.sync.aligned.m64n128k16.f16.f16.f16 "
        "{%0,%1,%2,%3,%4,%5,%6,%7,%8,%9,%10,%11,%12,%13,%14,%15,%16,%17,%18,%19,%20,%21,%22,%23,%24,%25,%26,%27,%28,%29,%30,%31}, "
        "%32, %33, p, 1, 1, 0, 0;\n}\n"
        : "+r"(d[0]), "+r"(d[1]), "+r"(d[2]), "+r"(d[3]), "+r"(d[4]), "+r"(d[5]), "+r"(d[6]), "+r"(d[7]),
          "+r"(d[8]), "+r"(d[9]), "+r"(d[10]), "+r"(d[11]), "+r"(d[12]), "+r"(d[13]), "+r"(d[14]), "+r"(d[15]),
          "+r"(d[16]), "+r"(d[17]), "+r"(d[18]), "+r"(d[19]), "+r"(d[20]), "+r"(d[21]), "+r"(d[22]), "+r"(d[23]),
          "+r"(d[24]), "+r"(d[25]), "+r"(d[26]), "+r"(d[27]), "+r"(d[28]), "+r"(d[29]), "+r"(d[30]), "+r"(d[31])
        : "l"(desca), "l"(desc));
}
__device__ __forceinline__ void wg_pv_init(uint32_t (&d)[10], uint32_t a0, uint32_t a1, uint32_t a2, uint32_t a3, uint64_t desc) {
    asm volatile("{\n.reg .pred p;\nsetp.ne.b32 p, 0, 0;\n"
        "wgmma.mma_async.sync.aligned.m64n40k16.f16.f16.f16 "
        "{%0,%1,%2,%3,%4,%5,%6,%7,%8,%9}, "
        "{%10,%11,%12,%13}, %14, p, 1, 1, 1;\n}\n"
        : "=r"(d[0]), "=r"(d[1]), "=r"(d[2]), "=r"(d[3]), "=r"(d[4]), "=r"(d[5]), "=r"(d[6]), "=r"(d[7]),
          "=r"(d[8]), "=r"(d[9])
        : "r"(a0), "r"(a1), "r"(a2), "r"(a3), "l"(desc));
}
__device__ __forceinline__ void wg_pv_acc(uint32_t (&d)[10], uint32_t a0, uint32_t a1, uint32_t a2, uint32_t a3, uint64_t desc) {
    asm volatile("{\n.reg .pred p;\nsetp.ne.b32 p, 1, 0;\n"
        "wgmma.mma_async.sync.aligned.m64n40k16.f16.f16.f16 "
        "{%0,%1,%2,%3,%4,%5,%6,%7,%8,%9}, "
        "{%10,%11,%12,%13}, %14, p, 1, 1, 1;\n}\n"
        : "+r"(d[0]), "+r"(d[1]), "+r"(d[2]), "+r"(d[3]), "+r"(d[4]), "+r"(d[5]), "+r"(d[6]), "+r"(d[7]),
          "+r"(d[8]), "+r"(d[9])
        : "r"(a0), "r"(a1), "r"(a2), "r"(a3), "l"(desc));
}

constexpr int Q_ABYTES = 256 * 64 * 2, Q_STB = Q_ABYTES + 192 * 64 * 2;
constexpr int OFF_SIDE = 3 * Q_STB;
constexpr int OFF_XS = OFF_SIDE + 49152;
constexpr int OFF_CS = OFF_XS + 4096;
constexpr int OFF_RC = OFF_CS + 768;
constexpr int OFF_FIX = OFF_RC + 2048;
constexpr int A_WIN = KV_WIN + 4096;
constexpr int OFF_QA = 3 * A_WIN;
constexpr int OFF_LC = OFF_QA + 32768;
constexpr int OFF_FE = 147456;
constexpr int OFF_XT = 196608;
__host__ __device__ constexpr uint32_t o_stage(uint32_t s) { return s == 3 ? OFF_QA : s == 2 ? 0 : (s + 1) * A_WIN; }
__host__ __device__ constexpr uint32_t gu_piece(uint32_t i) { return i < 3 ? OFF_FE + i * 16384 : i < 6 ? (i - 1) * 16384 : (i - 6) * 16384; }
constexpr int OFF_FD = 5 * 16384;
constexpr int OFF_BAR = OFF_XT + 32768;
constexpr int OFF_PART = OFF_BAR + 384;
constexpr int OFF_RED = OFF_PART + 2048;
constexpr int OFF_RT = OFF_RED + 96;
constexpr int OFF_M = OFF_RT + 144;
constexpr int OFF_WR = OFF_M + 72;
constexpr int K_SMEM = OFF_WR + 264;
static_assert(K_SMEM <= 232448 && OFF_FIX + 768 <= OFF_BAR && OFF_QA + 32768 <= OFF_FE, "smem");
constexpr uint32_t CH_OK = 0x38003800u;
constexpr int M_SC = 0,
              M_IVS = 24,
              M_ISC = 32,
              M_OK = 40,
              M_WS = 48,
              M_RIDX = 60,
              M_ORDY = 64;
constexpr uint32_t BB = SB + OFF_BAR;
constexpr uint32_t B_QF = BB, B_EPI = BB + 24, B_RES2 = BB + 56, B_AF = BB + 64, B_RES = BB + 120, B_OF = BB + 128,
                   B_FE = BB + 160, B_FL = BB + 168, B_FD = BB + 184, B_PR = BB + 192, B_FW = B_PR, B_SW = BB + 216,
                   B_QE = BB + 224, B_QAF = BB + 248, B_OE = BB + 288, B_AE = BB + 320, B_K0 = BB + 344, B_KV0 = BB + 376;

constexpr int N_OST = 5, N_XST = 9, N_RT = 11, N_KV1 = 12, N_FW = 13, N_GD = 14, N_DD = 15;

struct Maps { CUtensorMap xa0, wqkv, xa, x0, x, out, w64, wo, r, g, u, d, xs; };

__device__ __forceinline__ float2 ln_coef(const uint4& s) {
    const float mean = __uint_as_float(s.x) * (1.f / D_);
    return make_float2(rsq(fmaxf(fmaf(-mean, mean, fmaf(__uint_as_float(s.y), 1.f / D_, LN_EPS)), LN_EPS)), mean);
}
__device__ __forceinline__ uint32_t order_bits(float r) { const uint32_t u = __float_as_uint(r); return (u & 0x80000000u) ? ~u : (u | 0x80000000u); }
__device__ __forceinline__ uint4 warp_best(const uint4& e) {
    const uint32_t m = redux_max(e.x), row = redux_min(e.x == m ? e.y : 0x7FFFFFFFu);
    const int src = __ffs(__ballot_sync(0xffffffffu, e.y == row)) - 1;
    return make_uint4(m, row, __shfl_sync(0xffffffffu, e.z, src), __shfl_sync(0xffffffffu, e.w, src));
}
__device__ __forceinline__ RouteOut route_out(const uint4& e) {
    RouteOut rt;
    rt.idx = e.y; rt.r = __uint_as_float((e.x & 0x80000000u) ? e.x & 0x7FFFFFFFu : ~e.x); rt.mean = __uint_as_float(e.z); rt.rstd = __uint_as_float(e.w);
    return rt;
}

__device__ __forceinline__ void prep_work(const bf16* __restrict__ x0, const CUtensorMap* tmW, int t) {
    const int c = blockIdx.x, lane = t & 31, warp = warp_uniform(t >> 5);
    const int ki = c >> 4, n = c & 15;
    constexpr uint32_t red = SB + OFF_SIDE, xs = red + 4096;
    if (warp == 0) {
        mbar_expect_tx(B_PR, 32768);
        bulk_load(xs, x0 + (size_t)c * 16 * D_, 32768, B_PR);
        mbar_expect_tx(B_PR + 8, 16384);
        tma_load(xs + 32768, tmW, 2 * D_ + n * 64, ki * 128, B_PR + 8);
        tma_load(xs + 32768 + 8192, tmW, 2 * D_ + n * 64, ki * 128 + 64, B_PR + 8);
    }
    const uint4 sent = make_uint4(SENT, SENT, SENT, SENT);
    for (int i = t; i < 2 * NFC * 2; i += 96) reinterpret_cast<uint4*>(&g_ypart[0][0][0])[c * (2 * NFC * 2) + i] = sent;
    if (t < 64) reinterpret_cast<uint4*>(&g_acc[0][0][0])[c * 64 + t] = make_uint4(0u, 0u, 0u, 0u);
    if (t >= 64 && t < 80) g_sums[c * 16 + t - 64] = sent;
    if (t < 2) reinterpret_cast<uint4*>(g_x2row)[c * 2 + t] = sent;
    else if (t < 8) reinterpret_cast<uint4*>(g_fix)[c * 6 + t - 2] = sent;
    else if (t < 12) (&g_kvc[0][0][0])[c * 4 + t - 8] = 0u;
    else if (t >= 24 && t < 32) (&g_oc[0][0][0][0])[c * 8 + t - 24] = 0u;
    else if (t == 13 && c < 16) (&g_xc[0][0])[c] = 0u;
    else if (t >= 16 && t < 20) (&g_tab[0][0][0][0])[c * 4 + t - 16] = sent;
    else if (t >= 32 && t < 64) reinterpret_cast<uint4*>(&g_xrow[0][0][0])[c * 32 + t - 32] = sent;
    mbar_wait(B_PR, 0);
    #pragma unroll 1
    for (int r = warp; r < 16; r += 3) {
        float s = 0.f, q = 0.f;
        #pragma unroll
        for (int i = 0; i < 4; i++) {
            const uint4 u = lds128(xs + r * 2048 + (lane + 32 * i) * 16);
            const float f[8] = {bf_lo(u.x), bf_hi(u.x), bf_lo(u.y), bf_hi(u.y), bf_lo(u.z), bf_hi(u.z), bf_lo(u.w), bf_hi(u.w)};
            #pragma unroll
            for (int e = 0; e < 8; e++) { s += f[e]; q = fmaf(f[e], f[e], q); }
        }
        #pragma unroll
        for (int o = 16; o > 0; o >>= 1) { s += __shfl_xor_sync(0xffffffffu, s, o); q += __shfl_xor_sync(0xffffffffu, q, o); }
        const float mean = s * (1.f / D_);
        const float var = fmaxf(q * (1.f / D_) - mean * mean, 0.f);
        if (lane == 0) g_rs0[c * 16 + r] = make_float2(rsqrtf(var + LN_EPS), mean);
    }
    named_sync(2, 96);
    if (warp == 0) {
        mbar_expect_tx(B_PR + 16, 32768);
        #pragma unroll
        for (int b = 0; b < 4; b++) tma_load(xs + b * 8192, tmW, (b >> 1) * D_ + n * 64, ki * 128 + (b & 1) * 64, B_PR + 16);
    }
    const int j = t & 7, rg = t >> 3;
    #pragma unroll 1
    for (int blk = 0; blk < 3; blk++) {
        const int type = blk == 0 ? 2 : blk - 1;
        const uint32_t wb = xs + type * 16384;
        if (blk < 2) mbar_wait(B_PR + 8 + 8 * blk, 0);
        float cs[8];
        uint32_t z2[4] = {0u, 0u, 0u, 0u};
        #pragma unroll
        for (int i = 0; i < 8; i++) cs[i] = 0.f;
        #pragma unroll 4
        for (int r = rg; r < 128; r += 12) {
            const uint4 u = lds128(wb + r * 128 + ((j ^ (r & 7)) << 4));
            cs[0] += bf_lo(u.x); cs[1] += bf_hi(u.x); cs[2] += bf_lo(u.y); cs[3] += bf_hi(u.y);
            cs[4] += bf_lo(u.z); cs[5] += bf_hi(u.z); cs[6] += bf_lo(u.w); cs[7] += bf_hi(u.w);
            asm("fma.rn.bf16x2 %0, %1, %1, %0;" : "+r"(z2[0]) : "r"(u.x));
            asm("fma.rn.bf16x2 %0, %1, %1, %0;" : "+r"(z2[1]) : "r"(u.y));
            asm("fma.rn.bf16x2 %0, %1, %1, %0;" : "+r"(z2[2]) : "r"(u.z));
            asm("fma.rn.bf16x2 %0, %1, %1, %0;" : "+r"(z2[3]) : "r"(u.w));
        }
        #pragma unroll
        for (int i = 0; i < 8; i++) { cs[i] += __shfl_xor_sync(0xffffffffu, cs[i], 8); cs[i] += __shfl_xor_sync(0xffffffffu, cs[i], 16); }
        float z = ((bf_lo(z2[0]) + bf_hi(z2[0])) + (bf_lo(z2[1]) + bf_hi(z2[1]))) + ((bf_lo(z2[2]) + bf_hi(z2[2])) + (bf_lo(z2[3]) + bf_hi(z2[3])));
        z += __shfl_xor_sync(0xffffffffu, z, 1); z += __shfl_xor_sync(0xffffffffu, z, 2);
        z += __shfl_xor_sync(0xffffffffu, z, 8); z += __shfl_xor_sync(0xffffffffu, z, 16);
        if (lane < 8) {
            #pragma unroll
            for (int i = 0; i < 8; i++) stsf(red + (warp * 200 + type * 64 + j * 8 + i) * 4, cs[i]);
            if ((lane & 3) == 0) stsf(red + (warp * 200 + 192 + type * 2 + (lane >> 2)) * 4, z);
        }
    }
    named_sync(2, 96);
    for (int i = t; i < 198; i += 96) {
        const float v = ldsf(red + i * 4) + ldsf(red + (200 + i) * 4) + ldsf(red + (400 + i) * 4);
        if (i < 192) g_csum[ki * (3 * D_) + (i >> 6) * D_ + n * 64 + (i & 63)] = v;
        else g_wsq[ki * 96 + ((i - 192) >> 1) * 32 + n * 2 + (i & 1)] = v;
    }
    named_sync(2, 96);
    if (warp == 0) { ctr_arrive(&g_c0); ctr_wait(&g_c0, 128); }
    named_sync(2, 96);
}

__device__ __forceinline__ float pow2_inv(float b) {
    const int e = min(max((int)(__float_as_uint(b) >> 23) + 1, 20), 234);
    return __uint_as_float((uint32_t)(254 - e) << 23);
}
__device__ __forceinline__ void epi_inputs(int L) {
    const int t = tid_now() - 288, mt = cta_now() >> 4, nt = cta_now() & 15;
    float p[2][8], r0[3], r1[3];
    #pragma unroll
    for (int k = 0; k < 2; k++)
        #pragma unroll
        for (int q = 0; q < 8; q++) p[k][q] = __ldcg(g_csum + q * (3 * D_) + ((t + 96 * k) >> 6) * D_ + nt * 64 + ((t + 96 * k) & 63));
    #pragma unroll
    for (int k = 0; k < 2; k++) stsf(SB + OFF_CS + (t + 96 * k) * 4, ((p[k][0] + p[k][1]) + (p[k][2] + p[k][3])) + ((p[k][4] + p[k][5]) + (p[k][6] + p[k][7])));
    bool wait;
    uint32_t n = 0;
    do {
        wait = false;
        #pragma unroll
        for (int k = 0; k < 3; k++) {
            const int row = mt * 256 + min(t + 96 * k, 255);
            if (L == 0) { const float2 s = __ldcg(&g_rs0[row]); r0[k] = s.x; r1[k] = s.y; }
            else { const uint4 s = ld_relaxed4(&g_sums[row]); r0[k] = __uint_as_float(s.x); r1[k] = __uint_as_float(s.y); wait = wait || has_sent(s); }
        }
    } while (wait && ++n < SPIN_MAX);
    #pragma unroll
    for (int k = 0; k < 3; k++) {
        if (L != 0) {
            const float mean = r0[k] * (1.f / D_);
            const float var = fmaxf(r1[k] * (1.f / D_) - mean * mean, 0.f);
            const float a = 1.f + rsqrtf(var + LN_EPS);
            r0[k] = a * rsqrtf(a * a * var + LN_EPS); r1[k] = mean;
        }
        if (t + 96 * k < 256) sts64f(SB + OFF_RC + (t + 96 * k) * 8, r0[k], r1[k]);
    }
    if (L == 0 && t < 32) {
        float z = 0.f;
        if (t < 6) {
            #pragma unroll
            for (int q = 0; q < 8; q++) z += __ldcg(g_wsq + q * 96 + (t >> 1) * 32 + nt * 2 + (t & 1));
        }
        const float b = sqrtf(z) * (t < 2 ? 34.f * QSCALE : 34.f);
        const float sc = t < 4 ? fminf(pow2_inv(b) * 32768.f, 1.f) : pow2_inv(b);
        const float bk = __shfl_down_sync(0xffffffffu, b, 2), sk = __shfl_down_sync(0xffffffffu, sc, 2);
        if (t < 6) stsf(SB + OFF_M + M_SC + t * 4, t < 2 ? sc * QSCALE : sc);
        if (t < 2) { stsf(SB + OFF_M + M_ISC + t * 4, 1.f / (sc * sk)); sts32(SB + OFF_M + M_OK + t * 4, sc == 1.f && sk == 1.f && b * bk < 60000.f ? CH_OK : 0u); }
        if (t == 4 || t == 5) stsf(SB + OFF_M + M_IVS + (t - 4) * 4, 1.f / sc);
    }
}

__device__ __forceinline__ int ypos_col(int p) { return (p >> 7) * 128 + ((p >> 1) & 7) * 16 + (p & 1) * 8 + ((p >> 4) & 7); }

template <int NT>
__device__ __forceinline__ float ffn_finish(int L, const RouteOut& rt, int t, uint32_t red, int bid) {
    constexpr int NL = (2 * NFC + NT - 1) / NT;
    const int c = cta_now(), col = ypos_col(c * 8 + (t & 7));
    const uint32_t* src = &g_ypart[L][t >> 1][c * 8 + (t & 1) * 4];
    uint32_t n = 0, xp;
    do { xp = ld_relaxed(&g_xrow[L][rt.idx >> 7][((col >> 5) & 7) * 64 + (col >> 8) * 16 + (col & 6) * 2 + ((col >> 3) & 3)]); } while (xp == SENT && ++n < SPIN_MAX);
    uint4 v[NL];
    #pragma unroll
    for (int i = 0; i < NL; i++) v[i] = t + NT * i < 2 * NFC ? ld_relaxed4(src + i * (NT / 2) * D_) : make_uint4(0u, 0u, 0u, 0u);
    const float xv = (col & 1) ? bf_hi(xp) : bf_lo(xp);
    float rsel = bf_round(rcp(1.f + ex2(bf_round(rt.r) * -1.4426950408889634f))), xn = bf_round((xv - rt.mean) * rt.rstd);
    asm volatile("" : "+f"(rsel), "+f"(xn));
    while (true) {
        bool wait = false;
        #pragma unroll
        for (int i = 0; i < NL; i++) wait = wait || has_sent(v[i]);
        if (!wait || ++n >= SPIN_MAX) break;
        #pragma unroll
        for (int i = 0; i < NL; i++) if (t + NT * i < 2 * NFC) v[i] = ld_relaxed4(src + i * (NT / 2) * D_);
    }
    spin_check(n);
    __syncwarp();
    float a[4] = {0.f, 0.f, 0.f, 0.f};
    #pragma unroll
    for (int i = 0; i < NL; i++) { a[0] += __uint_as_float(v[i].x); a[1] += __uint_as_float(v[i].y); a[2] += __uint_as_float(v[i].z); a[3] += __uint_as_float(v[i].w); }
    const bool b1 = t & 2, b2 = t & 4;
    a[0] = (b1 ? a[1] : a[0]) + __shfl_xor_sync(0xffffffffu, b1 ? a[0] : a[1], 2);
    a[2] = (b1 ? a[3] : a[2]) + __shfl_xor_sync(0xffffffffu, b1 ? a[2] : a[3], 2);
    a[0] = (b2 ? a[2] : a[0]) + __shfl_xor_sync(0xffffffffu, b2 ? a[0] : a[2], 4);
    a[0] += __shfl_xor_sync(0xffffffffu, a[0], 8); a[0] += __shfl_xor_sync(0xffffffffu, a[0], 16);
    if ((t & 31) < 8) stsf(red + (t >> 5) * 32 + (t & 1) * 16 + (t & 6) * 2, a[0]);
    named_sync(bid, NT);
    float y = 0.f, y2 = 0.f;
    #pragma unroll
    for (int i = 0; i < NT / 32; i++) { const float p = ldsf(red + (t & 7) * 4 + i * 32); if (i & 1) y2 += p; else y += p; }
    y += y2;
    return bf_round(xv + bf_round(xn + bf_round(bf_round(y) * rsel)));
}

__device__ __forceinline__ void routed_qkv(int ridx) {
    const int t = tid_now() - 288, c = cta_now(), lane = t & 31, warp = t >> 5;
    constexpr uint32_t red = SB + OFF_RED;
    {
        uint4 v[3];
        uint32_t n = 0;
        do {
            v[0] = ld_relaxed4(g_x2row + t * 4); v[1] = ld_relaxed4(g_x2row + (t + 96) * 4);
            v[2] = t < 64 ? ld_relaxed4(g_x2row + (t + 192) * 4) : make_uint4(0u, 0u, 0u, 0u);
        } while ((has_sent(v[0]) || has_sent(v[1]) || has_sent(v[2])) && ++n < SPIN_MAX);
        spin_check(n);
        __syncwarp();
        float f[12];
        float s = 0.f;
        #pragma unroll
        for (int i = 0; i < 3; i++) { f[4*i] = __uint_as_float(v[i].x); f[4*i+1] = __uint_as_float(v[i].y); f[4*i+2] = __uint_as_float(v[i].z); f[4*i+3] = __uint_as_float(v[i].w); }
        #pragma unroll
        for (int i = 0; i < 12; i++) s += f[i];
        s = warp_sum(s);
        if (lane == 0) stsf(red + warp * 4, s);
        named_sync(2, 96);
        const float mean = (ldsf(red) + ldsf(red + 4) + ldsf(red + 8)) * (1.f / D_);
        float q = 0.f;
        #pragma unroll
        for (int i = 0; i < 12; i++) { f[i] -= mean; if (i < 8 || t < 64) q = fmaf(f[i], f[i], q); }
        q = warp_sum(q);
        if (lane == 0) stsf(red + 16 + warp * 4, q);
        named_sync(2, 96);
        const float rstd = rsqrtf((ldsf(red + 16) + ldsf(red + 20) + ldsf(red + 24)) * (1.f / D_) + LN_EPS);
        #pragma unroll
        for (int i = 0; i < 3; i++)
            if (i < 2 || t < 64) sts128(SB + OFF_XS + (t + 96 * i) * 16, make_uint4(pack_bf16(0.f, f[4*i] * rstd), pack_bf16(0.f, f[4*i+1] * rstd), pack_bf16(0.f, f[4*i+2] * rstd), pack_bf16(0.f, f[4*i+3] * rstd)));
    }
    named_sync(2, 96);
    mbar_wait(B_SW, 0);
    float a[8];
    #pragma unroll
    for (int i = 0; i < 8; i++) a[i] = 0.f;
    const uint32_t wa = SB + OFF_SIDE + t * 16, xa = SB + OFF_XS + (t / 3) * 4;
    #pragma unroll 4
    for (int i = 0; i < 32; i++) {
        const uint4 u = lds128(wa + i * 1536);
        const float xv = ldsf(xa + i * 128);
        a[0] = fmaf(xv, bf_lo(u.x), a[0]); a[1] = fmaf(xv, bf_hi(u.x), a[1]); a[2] = fmaf(xv, bf_lo(u.y), a[2]); a[3] = fmaf(xv, bf_hi(u.y), a[3]);
        a[4] = fmaf(xv, bf_lo(u.z), a[4]); a[5] = fmaf(xv, bf_hi(u.z), a[5]); a[6] = fmaf(xv, bf_lo(u.w), a[6]); a[7] = fmaf(xv, bf_hi(u.w), a[7]);
    }
    named_sync(2, 96);
    sts128(SB + OFF_SIDE + t * 32, make_uint4(__float_as_uint(a[0]), __float_as_uint(a[1]), __float_as_uint(a[2]), __float_as_uint(a[3])));
    sts128(SB + OFF_SIDE + t * 32 + 16, make_uint4(__float_as_uint(a[4]), __float_as_uint(a[5]), __float_as_uint(a[6]), __float_as_uint(a[7])));
    named_sync(2, 96);
    {
        float y = 0.f;
        #pragma unroll
        for (int i = 0; i < 8; i++) y += ldsf(SB + OFF_SIDE + ((t & 3) * 8 + i) * 96 + (t >> 2) * 4);
        y += __shfl_xor_sync(0xffffffffu, y, 1); y += __shfl_xor_sync(0xffffffffu, y, 2);
        if ((t & 3) == 0) st_relaxed(g_fix + c * 24 + (t >> 2), not_sent(y));
    }
    if ((ridx >> 8) == (c >> 4) && t < 24) {
        const uint32_t* src = g_fix + (t >> 3) * D_ + (c & 15) * 64 + (t & 7) * 8;
        uint4 a, b;
        uint32_t n = 0;
        do { a = ld_relaxed4(src); b = ld_relaxed4(src + 4); } while ((has_sent(a) || has_sent(b)) && ++n < SPIN_MAX);
        spin_check(n);
        const int hh = t >> 2, ch = t & 3, lr = ridx & 255;
        const float hs = ldsf(SB + OFF_M + M_SC + hh * 4);
        sts128(SB + OFF_FIX + t * 16, make_uint4(pack_f16(__uint_as_float(a.x) * hs, __uint_as_float(a.y) * hs), pack_f16(__uint_as_float(a.z) * hs, __uint_as_float(a.w) * hs),
                                                 pack_f16(__uint_as_float(b.x) * hs, __uint_as_float(b.y) * hs), pack_f16(__uint_as_float(b.z) * hs, __uint_as_float(b.w) * hs)));
        sts32(SB + OFF_FIX + 512 + t * 4, SB + (hh < 2 ? OFF_QA + hh * 16384 + (lr >> 6) * 4096 + ch * 1024 + (lr & 63) * 16
                                                        : (hh & 1) * OFF_FE + (hh >> 2) * 16384 + ch * 4096 + lr * 16));
    }
    __syncwarp();
}

__device__ __forceinline__ void ffn_load(const Maps& mp, int c, int i, uint32_t dst, uint32_t bar, bool last_use) {
    if (i < 8) tma_load_h(dst, (i & 1) ? &mp.u : &mp.g, c * 32, (i >> 1) * 256, bar, last_use);
    else tma_load3_h(dst, &mp.d, 0, c * 32, (i - 8) * 4, bar, last_use);
}
__device__ __forceinline__ void side_role(const Maps& mp, const bf16* __restrict__ x0, const bf16* __restrict__ wo, const bf16* __restrict__ w_r) {
    prep_work(x0, &mp.w64, threadIdx.x - 288);
    epi_inputs(0);
    #pragma unroll 1
    for (int L = 0; L < 2; L++) {
        const int t = tid_now() - 288, lane = t & 31, sw = warp_uniform(t >> 5);
        const int c = cta_now(), mt = c >> 4, nt = c & 15;
        named_sync(2, 96);
        if (t == 0) mbar_arrive(B_EPI);
        __syncwarp();
        char* kv = g_kv + (size_t)(nt * 16 + mt) * KV_WIN;
        if (sw < 2) {
            mbar_wait(sw ? B_K0 : B_KV0, L);
            bulk_store(kv + (1 - sw) * 16384, SB + (1 - sw) * 16384, 16384);
            bulk_commit();
            publish(&g_kvc[L][nt * 2][mt], 1 + sw);
        }
        if (sw == 0) {
            named_sync(N_KV1, 64);
            bulk_store(kv + 8 * KV_WIN, SB + OFF_FE, KV_WIN);
            bulk_commit();
            publish(&g_kvc[L][nt * 2 + 1][mt], 3);
        }
        if (sw < 2) {
            #pragma unroll 1
            for (int p = 0; p < 2; p++) {
                named_sync(N_OST + 2 * p + sw, p > sw ? 192 : 160);
                if (p == 1) mbar_arrive_elect(B_QAF);
                ctr_arrive(&g_oc[L][mt * 2 + sw][p][nt]);
            }
        } else {
            if (L == 0) {
                float ws = 0.f;
                #pragma unroll
                for (int i = 0; i < 4; i++) {
                    const uint4 v = reinterpret_cast<const uint4*>(w_r)[i * 32 + lane];
                    ws += ((bf_lo(v.x) + bf_hi(v.x)) + (bf_lo(v.y) + bf_hi(v.y))) + ((bf_lo(v.z) + bf_hi(v.z)) + (bf_lo(v.w) + bf_hi(v.w)));
                }
                const uint32_t* wp = reinterpret_cast<const uint32_t*>(w_r) + (nt >> 1) * 64 + (lane >> 2) * 8 + (lane & 3);
                sts64f(SB + OFF_WR + lane * 8, __uint_as_float(wp[0]), __uint_as_float(wp[4]));
                ws = warp_sum(ws);
                if (lane == 0) { stsf(SB + OFF_M + M_WS, ws); sts64f(SB + OFF_M + M_ORDY, 0.f, 0.f); sts64f(SB + OFF_WR + 256, __uint_as_float(0x3F803F80u), __uint_as_float(0x3F803F80u)); }
                __syncwarp();
            }
            named_sync(N_FW, 64);
            mbar_expect_tx(B_RES, 32768);
            #pragma unroll
            for (int i = 0; i < 4; i++) tma_load_h(SB + OFF_XT + i * 8192, L == 0 ? &mp.x0 : &mp.x, (nt >> 1) * 128 + (i >> 1) * 64, mt * 256 + (nt & 1) * 128 + (i & 1) * 64, B_RES, true);
            if (c < NFC) {
                #pragma unroll 1
                for (int r = 0; r < 4; r++) {
                    __nanosleep(1000);
                    if (r > 0) mbar_wait(B_FW, (r + L) & 1);
                    const uint32_t bar = r < 3 ? B_FW : B_FE;
                    mbar_expect_tx(bar, 3 * 16384);
                    #pragma unroll 1
                    for (int b = 0; b < 3; b++) ffn_load(mp, c, 9 - 3 * r + b, SB + OFF_FE + b * 16384, bar, r == 3);
                }
            }
        }
        if (sw == 2) {
            l2_prefetch(reinterpret_cast<const char*>(wo) + (size_t)c * 16384, 16384);
            mbar_wait(B_RES, L);
            const uint32_t lr = lds32(SB + OFF_M + M_RIDX) - (mt * 256 + (nt & 1) * 128);
            if (L == 1 && lr < 128u && lane < 16) {
                const uint4 a = ld_relaxed4(g_x2row + (nt >> 1) * 128 + lane * 8), b = ld_relaxed4(g_x2row + (nt >> 1) * 128 + lane * 8 + 4);
                sts128(SB + OFF_XT + (lane >> 3) * 16384 + lr * 128 + (((lane & 7) ^ (lr & 7)) << 4),
                       make_uint4(__byte_perm(a.x, a.y, 0x7632), __byte_perm(a.z, a.w, 0x7632), __byte_perm(b.x, b.y, 0x7632), __byte_perm(b.z, b.w, 0x7632)));
            }
            if (L == 1) {
                #pragma unroll
                for (int i = 0; i < 4; i++) {
                    const float2 r = ln_coef(ld_relaxed4(&g_sums[mt * 256 + (nt & 1) * 128 + i * 32 + lane]));
                    const float a = i * 32 + lane == lr ? 0.f : r.x;
                    sts64f(SB + OFF_LC + (i * 32 + lane) * 8, a, -a * r.y);
                }
            }
            __syncwarp();
            mbar_arrive_elect(B_RES2);
            named_sync(N_OST + 2, 192);
            l2_prefetch(&g_ypart[L][0][0] + c * (NFC * 8), NFC * 32);
            l2_prefetch(&g_acc[L][c * 16][0], 512);
            l2_prefetch(&g_sums[c * 16], 256);
            l2_prefetch(&g_xrow[L][0][0] + c * 64, 256);
            l2_prefetch(&g_tab[L][0][0][0] + c * 2, 32);
            l2_prefetch(c < 32 ? &g_x2row[c * 32] : c < 40 ? &g_kvc[1][(c - 32) * 4][0] : &g_xc[0][0], c < 40 ? 128 : 64);
            l2_prefetch(&g_fix[c * 24], 96);
            uint32_t ready, n = 0;
            do {
                ready = __ballot_sync(0xffffffffu, ld_acquire(&g_oc[L][mt * 2 + (nt & 1)][1][lane & 15]) != 0);
                fence_async_global();
                if (lane == 0) sts_release(SB + OFF_M + M_ORDY + 4 * L, ready & ready >> 1);
            } while (ready != 0xFFFFFFFFu && ++n < SPIN_MAX);
            spin_check(n);
        }
        if (sw < 2) {
            named_sync(N_XST + sw, 160);
            const int row0 = mt * 256 + (nt & 1) * 128 + sw * 64, col0 = (nt >> 1) * 128;
            #pragma unroll 1
            for (int h = 0; h < 8; h++) {
                if (L == 0) bulk_wait_n<2>();
                tma_store(L == 0 ? &mp.xs : &mp.out, SB + OFF_XT + (h & 1) * 16384 + sw * 8192 + (h >> 1) * 2048, col0 + (h & 1) * 64, row0 + (h >> 1) * 16);
                bulk_commit();
            }
            publish(&g_xc[L][mt]);
        }
        if (L == 0) {
            __syncwarp();
            named_sync(N_RT, 128);
            const RouteOut rt = route_out(lds128(SB + OFF_RT + 128));
            if (t == 0) { sts32(SB + OFF_M + M_RIDX, rt.idx); if (c == 0) g_c0 = 0u; }
            epi_inputs(1);
            const float v = ffn_finish<96>(0, rt, t, SB + OFF_RED, 2);
            if (t < 8) st_relaxed(g_x2row + ypos_col(c * 8 + t), not_sent(v));
            routed_qkv(rt.idx);
        }
    }
}

struct EpiIn { float2 c2[4]; float hs; };
template <int HH>
__device__ __forceinline__ EpiIn qkv_epi_in(int t) {
    EpiIn e;
    #pragma unroll
    for (int jj = 0; jj < 4; jj++) e.c2[jj] = lds64f(SB + OFF_CS + (HH * 32 + jj * 8) * 4 + t * 8);
    e.hs = ldsf(SB + OFF_M + M_SC + HH * 4);
    return e;
}
template <int HH, int NEXT>
__device__ __forceinline__ void qkv_epi_head(const float (&acc0)[96], const float (&acc1)[96], const float (&cf)[4], const float (&nm)[4], EpiIn& in, uint32_t dst, int t) {
    const EpiIn e = in;
    #pragma unroll
    for (int i = 0; i < 4; i++) {
        const float* a = (i >> 1) ? acc1 : acc0;
        const float sc = cf[i] * e.hs;
        uint32_t pk[4];
        #pragma unroll
        for (int jj = 0; jj < 4; jj++)
            pk[jj] = pack_f16(fmaf(nm[i], e.c2[jj].x, a[4 * (4 * HH + jj) + 2 * (i & 1)]) * sc, fmaf(nm[i], e.c2[jj].y, a[4 * (4 * HH + jj) + 2 * (i & 1) + 1]) * sc);
        #pragma unroll
        for (int jj = 0; jj < 4; jj++) if (HH >= 2) pk[jj] = round8(pk[jj]);
        stsm4(dst + (i >> 1) * (HH < 2 ? 4096 : 1024) + (i & 1) * 128, pk[0], pk[1], pk[2], pk[3]);
        if (i == 1 && NEXT >= 0) in = qkv_epi_in<NEXT < 0 ? 0 : NEXT>(t);
    }
}
__device__ __forceinline__ void qkv_patch(int lane, uint32_t mask) {
    const uint4 v = lds128(SB + OFF_FIX + lane * 16);
    const uint32_t dst = lds32(SB + OFF_FIX + 512 + lane * 4);
    __syncwarp();
    asm volatile("{\n.reg .pred q;\nsetp.ne.u32 q, %5, 0;\n@q st.shared.v4.b32 [%0], {%1, %2, %3, %4};\n}"
                 :: "r"(dst), "r"(v.x), "r"(v.y), "r"(v.z), "r"(v.w), "r"((mask >> lane) & 1) : "memory");
}

template <bool INIT>
__device__ __forceinline__ void qkv_step(float (&acc0)[96], float (&acc1)[96], uint32_t st, int wg) {
    const uint64_t da = desc_sw128(SB, 16, 1024) + ((st * Q_STB + wg * 16384) >> 4);
    const uint64_t db = desc_sw128(SB + Q_ABYTES, 8192, 1024) + ((st * Q_STB) >> 4);
    wg_fence();
    if (INIT) { wg_gemm_n192_init(acc0, da, db); wg_gemm_n192_init(acc1, da + (8192 >> 4), db); }
    #pragma unroll
    for (int kk = INIT ? 1 : 0; kk < 4; kk++) {
        wg_gemm_n192(acc0, da + kk * 2, db + kk * 128);
        wg_gemm_n192(acc1, da + (8192 >> 4) + kk * 2, db + kk * 128);
    }
    wg_commit();
}
__device__ __forceinline__ void qkv_phase(int L, int wg) {
    const uint32_t rb = L * 32;
    float acc0[96], acc1[96];
    const bool leader = (tid_now() & 127) == 0;
    mbar_wait(rb + B_QF, 0);
    qkv_step<true>(acc0, acc1, 0, wg);
    uint32_t st = 1, ph = 0;
    #pragma unroll 1
    for (int k = 1; k < 16; k++) {
        mbar_wait(rb + B_QF + 8 * st, ph);
        qkv_step<false>(acc0, acc1, st, wg);
        wg_wait<1>();
        if (leader) mbar_arrive(rb + B_QE + 8 * (st == 0 ? 2 : st - 1));
        if (++st == 3) { st = 0; ph ^= 1; }
    }
    const int tid = tid_now(), lane = tid & 31, w = (tid >> 5) & 3, g = lane >> 2, t = lane & 3;
    mbar_wait(B_EPI, L);
    float cf[4], nm[4];
    #pragma unroll
    for (int i = 0; i < 4; i++) { const float2 r = lds64f(SB + OFF_RC + (wg * 128 + w * 16 + g + (i >> 1) * 64 + (i & 1) * 8) * 8); cf[i] = r.x; nm[i] = -r.y; }
    const int d = (int)lds32(SB + OFF_M + M_RIDX) - (cta_now() >> 4) * 256;
    const bool own = L == 1 && (d >> 7) == wg && ((d >> 4) & 3) == w;
    EpiIn in = qkv_epi_in<2>(t);
    wg_wait<0>();
    named_sync(1, 256);
    const uint32_t dk = SB + wg * 2048 + (lane >> 3) * 4096 + (w * 16 + (lane & 7)) * 16;
    const uint32_t dq = SB + OFF_QA + wg * 8192 + (lane >> 3) * 1024 + (w * 16 + (lane & 7)) * 16;
    qkv_epi_head<2, 4>(acc0, acc1, cf, nm, in, dk, t);
    if (own) qkv_patch(lane, 0x000F00u);
    fence_async_smem();
    __syncwarp();
    mbar_arrive_elect(B_K0);
    qkv_epi_head<4, 0>(acc0, acc1, cf, nm, in, dk + 16384, t);
    if (own) qkv_patch(lane, 0x0F0000u);
    #pragma unroll
    for (int s = 0; s < 3; s++) sts128(SB + s * A_WIN + KV_WIN + tid * 16, make_uint4(0x3C003C00u, 0x3C003C00u, 0x3C003C00u, 0x3C003C00u));
    fence_async_smem();
    __syncwarp();
    mbar_arrive_elect(B_KV0);
    qkv_epi_head<0, 1>(acc0, acc1, cf, nm, in, dq, t);
    qkv_epi_head<1, 3>(acc0, acc1, cf, nm, in, dq + 16384, t);
    qkv_epi_head<3, 5>(acc0, acc1, cf, nm, in, dk + OFF_FE, t);
    qkv_epi_head<5, -1>(acc0, acc1, cf, nm, in, dk + OFF_FE + 16384, t);
    if (own) qkv_patch(lane, 0xF0F0FFu);
    fence_async_smem();
    named_sync(3 + wg, 128);
}

struct Unit {
    uint32_t o[8];
    uint32_t l, bz, sc;
    uint32_t ch[2];
};
template <int H> __device__ __forceinline__ uint32_t hdup(uint32_t v) {
    uint32_t r;
    if (H) asm("{.reg .b16 l, h; mov.b32 {l, h}, %1; mov.b32 %0, {h, h};}" : "=r"(r) : "r"(v));
    else asm("{.reg .b16 l, h; mov.b32 {l, h}, %1; mov.b32 %0, {l, l};}" : "=r"(r) : "r"(v));
    return r;
}
__device__ __forceinline__ uint32_t hmax2(uint32_t a, uint32_t b) { uint32_t r; asm("max.f16x2 %0, %1, %2;" : "=r"(r) : "r"(a), "r"(b)); return r; }
__device__ __forceinline__ uint32_t hadd2(uint32_t a, uint32_t b) { uint32_t r; asm("add.rn.f16x2 %0, %1, %2;" : "=r"(r) : "r"(a), "r"(b)); return r; }
__device__ __forceinline__ uint32_t hsub2(uint32_t a, uint32_t b) { uint32_t r; asm("sub.rn.f16x2 %0, %1, %2;" : "=r"(r) : "r"(a), "r"(b)); return r; }
__device__ __forceinline__ uint32_t hfma2(uint32_t a, uint32_t b, uint32_t c) { uint32_t r; asm("fma.rn.f16x2 %0, %1, %2, %3;" : "=r"(r) : "r"(a), "r"(b), "r"(c)); return r; }
__device__ __forceinline__ uint32_t exp2_h2(uint32_t s, uint32_t bz, uint32_t& ch) {
    uint32_t z, w, d;
    asm("fma.rn.relu.f16x2 %0, %1, %2, %3;" : "=r"(z) : "r"(s), "r"(0x00400040u), "r"(bz));
    asm("lop3.b32 %0, %1, 0x003F003F, %0, 0xC2;" : "+r"(ch) : "r"(z));
    asm("fma.rn.f16x2 %0, %1, %2, %3;" : "=r"(w) : "r"(ch), "r"(0x30A630A6u), "r"(0xACCCACCCu));
    asm("{.reg .b32 n; neg.f16x2 n, %1; fma.rn.relu.f16x2 %0, n, %1, %2;}" : "=r"(d) : "r"(w), "r"(0x00580058u));
    return (z << 4) - d;
}
__device__ __forceinline__ void exp_tile(uint32_t (&p)[32], const uint32_t (&s)[32], Unit& u) {
    #pragma unroll
    for (int i = 0; i < 32; i++) p[i] = exp2_h2(s[i], (i & 1) ? hdup<1>(u.bz) : hdup<0>(u.bz), u.ch[i & 1]);
}
struct QOp { uint32_t r[4]; uint64_t d; };
__device__ __forceinline__ void issue_qk(uint32_t (&s)[32], const QOp& q, uint64_t dk) {
    wg_qk_init(s, q.r[0], q.r[1], q.r[2], q.r[3], dk); wg_qk_acc(s, q.d, dk + (8192 >> 4));
    wg_commit();
}
template <bool INIT>
__device__ __forceinline__ void issue_pv(uint32_t (&h)[10], const uint32_t (&p)[32], uint64_t dv) {
    #pragma unroll
    for (int k = 0; k < 8; k++) {
        if (INIT && k == 0) wg_pv_init(h, p[0], p[1], p[2], p[3], dv);
        else wg_pv_acc(h, p[4*k], p[4*k+1], p[4*k+2], p[4*k+3], dv + k * 16);
    }
    wg_commit();
}
__device__ __forceinline__ void unit_init(Unit& u, const uint32_t (&s)[32], uint32_t ok) {
    uint32_t m0 = s[0], m1 = s[1];
    #pragma unroll
    for (int i = 1; i < 16; i++) { m0 = hmax2(m0, s[2 * i]); m1 = hmax2(m1, s[2 * i + 1]); }
    uint32_t m = hmax2(__byte_perm(m0, m1, 0x5410), __byte_perm(m0, m1, 0x7632));
    m = hmax2(m, __shfl_xor_sync(0xffffffffu, m, 1)); m = hmax2(m, __shfl_xor_sync(0xffffffffu, m, 2));
    const uint32_t q = hfma2(m, 0x80048004u, 0x003E003Eu);
    u.bz = hfma2(q, 0x4C004C00u, 0x80008000u);
    u.ch[0] = u.ch[1] = ok & ~hadd2(q, q);
    u.sc = 0u; u.l = 0u;
    #pragma unroll
    for (int i = 0; i < 8; i++) u.o[i] = 0u;
}
template <bool MORE>
__device__ __forceinline__ void unit_flush(Unit& u, const uint32_t (&h)[10]) {
    u.l = hfma2(u.l, u.sc, __byte_perm(h[8], h[9], 0x5410));
    #pragma unroll
    for (int i = 0; i < 8; i++) u.o[i] = hfma2(u.o[i], (i & 1) ? hdup<1>(u.sc) : hdup<0>(u.sc), h[i]);
    if (MORE) {
        const uint32_t ex = u.l & 0x7C007C00u;
        u.sc = 0x84008400u - ex;
        u.bz = hsub2(hadd2(u.bz, 0x04800480u), ex >> 4);
    }
}
__device__ __forceinline__ char* o_block(int wg, int pass) { const int c = cta_now(); return g_o + (size_t)((((c >> 4) * 2 + wg) * 2 + pass) * 16 + (c & 15)) * 8192; }
__device__ __forceinline__ uint32_t unit_finish(Unit& u, float ivs) {
    float lf[2]; h2_unpack(u.l, lf[0], lf[1]);
    #pragma unroll
    for (int i = 0; i < 8; i++) { float x, y; h2_unpack(u.o[i], x, y); const float inv = ivs * rcp(lf[i & 1]); u.o[i] = pack_bf16(x * inv, y * inv); }
    return ((~u.ch[0] & CH_OK) != 0 || (u.l << 16) - 0x40000000u >= 0x3C000000u ? 1u : 0u) | ((~u.ch[1] & CH_OK) != 0 || u.l - 0x40000000u >= 0x3C000000u ? 2u : 0u);
}
__device__ __forceinline__ void unit_store(const Unit& u, char* dst) {
    #pragma unroll
    for (int i = 0; i < 8; i++) *reinterpret_cast<uint32_t*>(dst + (i >> 1) * 1024 + (i & 1) * 128) = u.o[i];
}
__device__ __noinline__ void exact_rows(int L, int pass, int wg, uint32_t bad) {
    const int tid = tid_now() & 127, lane = tid & 31, w = tid >> 5, t = lane & 3;
    const int head = (cta_now() & 15) * 2 + pass;
    const uint32_t scr = SB + OFF_PART + wg * 1024;
    bad = redux_or(bad << (lane & 28));
    if (lane == 0) sts32(scr + w * 4, bad);
    ctr_wait_all(&g_kvc[L][head][lane & 7], 3);
    named_sync(3 + wg, 128);
    const float isc = ldsf(SB + OFF_M + M_ISC + pass * 4), ivs = ldsf(SB + OFF_M + M_IVS + pass * 4);
    const char* kv = g_kv + (size_t)(head * 8 + w * 2) * KV_WIN + t * 4096 + (lane >> 2) * 16;
    #pragma unroll 1
    for (int ww = 0; ww < 4; ww++)
    #pragma unroll 1
    for (uint32_t m = lds32(scr + ww * 4); m; m &= m - 1) {
        const int bit = __ffs(m) - 1;
        const uint32_t ro = (bit & 2) * 2048 + (ww * 16 + (bit & 1) * 8 + (bit >> 2)) * 16;
        const uint4 q = lds128(SB + OFF_QA + pass * 16384 + wg * 8192 + ro + t * 1024);
        float a[9], mx = -INFINITY;
        #pragma unroll
        for (int i = 0; i < 9; i++) a[i] = 0.f;
        #pragma unroll 1
        for (int it = 0; it < 8; it++) {
            uint4 k[8], v[8];
            #pragma unroll
            for (int i = 0; i < 8; i++) {
                const char* p = kv + (it >> 2) * KV_WIN + (it & 3) * 1024 + i * 128;
                k[i] = __ldcg(reinterpret_cast<const uint4*>(p)); v[i] = __ldcg(reinterpret_cast<const uint4*>(p + 16384));
            }
            float s[8], mn = mx;
            #pragma unroll
            for (int i = 0; i < 8; i += 2) {
                float c[4] = {0.f, 0.f, 0.f, 0.f};
                mma_f16(c, k[i].x, k[i + 1].x, k[i].y, k[i + 1].y, q.x, q.y);
                mma_f16(c, k[i].z, k[i + 1].z, k[i].w, k[i + 1].w, q.z, q.w);
                s[i] = c[0]; s[i + 1] = c[2];
                mn = fmaxf(mn, fmaxf(c[0], c[2]));
            }
            const float al = ex2((mx - mn) * isc);
            mx = mn;
            #pragma unroll
            for (int i = 0; i < 9; i++) a[i] *= al;
            #pragma unroll
            for (int i = 0; i < 8; i++) {
                const float p = ex2((s[i] - mx) * isc);
                const uint32_t u[4] = {v[i].x, v[i].y, v[i].z, v[i].w};
                a[8] += p;
                #pragma unroll
                for (int e = 0; e < 4; e++) { float x, y; h2_unpack(u[e], x, y); a[2 * e] = fmaf(p, x, a[2 * e]); a[2 * e + 1] = fmaf(p, y, a[2 * e + 1]); }
            }
        }
        #pragma unroll 1
        for (int o = 4; o < 32; o <<= 1) {
            const float mn = fmaxf(mx, __shfl_xor_sync(0xffffffffu, mx, o)), al = ex2((mx - mn) * isc);
            mx = mn;
            #pragma unroll
            for (int i = 0; i < 9; i++) { a[i] *= al; a[i] += __shfl_xor_sync(0xffffffffu, a[i], o); }
        }
        named_sync(3 + wg, 128);
        const uint32_t mine = scr + 16 + w * 144;
        sts128(mine + t * 32, make_uint4(__float_as_uint(a[0]), __float_as_uint(a[1]), __float_as_uint(a[2]), __float_as_uint(a[3])));
        sts128(mine + t * 32 + 16, make_uint4(__float_as_uint(a[4]), __float_as_uint(a[5]), __float_as_uint(a[6]), __float_as_uint(a[7])));
        sts64f(mine + 128, a[8], mx);
        named_sync(3 + wg, 128);
        float o = 0.f, l = 0.f;
        mx = -INFINITY;
        #pragma unroll 1
        for (int i = 0; i < 4; i++) {
            const float2 e = lds64f(scr + 16 + i * 144 + 128);
            const float mn = fmaxf(mx, e.y), al = ex2((mx - mn) * isc), be = ex2((e.y - mn) * isc);
            mx = mn;
            o = fmaf(o, al, be * ldsf(scr + 16 + i * 144 + lane * 4)); l = fmaf(l, al, be * e.x);
        }
        if (w == 0) *reinterpret_cast<unsigned short*>(o_block(wg, pass) + ro + (lane >> 3) * 1024 + (lane & 7) * 2) = (unsigned short)pack_bf16(o * ivs * rcp(l), 0.f);
    }
}

__device__ __forceinline__ void attention_phase(int L, int wg) {
    const uint32_t rb = L * 32;
    constexpr uint64_t dk0 = desc_plain(SB, 4096, 128), dv0 = desc_plain(SB + 16384, 128, 4096);
    constexpr int T1 = 2048 >> 4;
    uint32_t st = 0, ph = 0;
    #pragma unroll 1
    for (int pass = 0; pass < 2; pass++) {
        QOp dqa, dqc;
        dqa.d = desc_plain(SB + OFF_QA + 2048, 1024, 128) + (pass * 4 + wg * 2) * (4096 >> 4); dqc.d = dqa.d + (4096 >> 4);
        {
            const int tid = tid_now();
            const uint32_t a0 = SB + OFF_QA + (pass * 4 + wg * 2) * 4096 + ((tid >> 4) & 1) * 1024 + (((tid >> 5) & 3) * 16 + (tid & 15)) * 16;
            ldsm4(dqa.r[0], dqa.r[1], dqa.r[2], dqa.r[3], a0); ldsm4(dqc.r[0], dqc.r[1], dqc.r[2], dqc.r[3], a0 + 4096);
        }
        Unit a, c;
        st = warp_uniform(st); ph = warp_uniform(ph);
        uint32_t SA[32], SC[32], PA[32], PC[32], ha[10], hc[10], bad;
        #pragma unroll
        for (int i = 0; i < 10; i++) hc[i] = 0u;
        #pragma unroll
        for (int i = 0; i < 32; i++) PC[i] = 0u;
        const uint32_t ok = lds32(SB + OFF_M + M_OK + pass * 4);
        mbar_wait(rb + B_AF + 8 * st, ph);
        wg_fence();
        issue_qk(SA, dqa, dk0 + st * (A_WIN >> 4));
        issue_qk(SC, dqc, dk0 + st * (A_WIN >> 4));
        wg_wait<1>();
        unit_init(a, SA, ok);
        exp_tile(PA, SA, a);
        wg_wait<0>();
        unit_init(c, SC, ok);
        uint32_t eb = 0;
        #pragma unroll 1
        for (int s = 0;; s++) {
            const uint64_t dkb = dk0 + st * (A_WIN >> 4), dvb = dv0 + st * (A_WIN >> 4);
            if (__builtin_expect(s == 8 * gridDim.y, 0)) {
                wg_wait<0>();
                bad = 0;
                #pragma unroll
                for (int i = 0; i < 32; i++) bad |= PC[i];
                break;
            }
            wg_fence();
            issue_pv<true>(ha, PA, dvb); issue_qk(SA, dqa, dkb + T1);
            wg_wait<2>();
            if (s > 0) { mbar_arrive_elect(eb); unit_flush<true>(c, hc); }
            exp_tile(PC, SC, c);
            wg_fence();
            issue_pv<true>(hc, PC, dvb); issue_qk(SC, dqc, dkb + T1);
            wg_wait<2>();
            exp_tile(PA, SA, a);
            eb = rb + B_AE + 8 * st;
            if (++st == 3) { st = 0; ph ^= 1; }
            if (s == 7) {
                wg_fence(); issue_pv<false>(ha, PA, dvb + T1);
                wg_wait<1>();
                exp_tile(PC, SC, c);
                wg_fence(); issue_pv<false>(hc, PC, dvb + T1);
                wg_wait<1>();
                const int tid = tid_now();
                const float ivs = ldsf(SB + OFF_M + M_IVS + pass * 4);
                char* dst = o_block(wg, pass) + (tid & 96) * 8 + (tid & 31) * 4;
                unit_flush<false>(a, ha);
                bad = unit_finish(a, ivs);
                wg_wait<0>();
                mbar_arrive_elect(eb);
                unit_store(a, dst);
                unit_flush<false>(c, hc);
                bad |= unit_finish(c, ivs) << 2;
                unit_store(c, dst + 4096);
                break;
            }
            const uint64_t dkn = dk0 + st * (A_WIN >> 4);
            mbar_wait(rb + B_AF + 8 * st, ph);
            wg_fence();
            issue_pv<false>(ha, PA, dvb + T1); issue_qk(SA, dqa, dkn);
            wg_wait<2>();
            exp_tile(PC, SC, c);
            wg_fence();
            issue_pv<false>(hc, PC, dvb + T1); issue_qk(SC, dqc, dkn);
            wg_wait<2>();
            unit_flush<true>(a, ha);
            exp_tile(PA, SA, a);
        }
        if (__builtin_expect(named_any(bad != 0, 3 + wg), 0)) {
            exact_rows(L, pass, wg, bad);
        }
        named_arrive(N_OST + 2 * pass + wg, pass > wg ? 192 : 160);
    }
}

template <bool INIT>
__device__ __forceinline__ void oproj_step(float (&acc)[64], uint32_t s, int wg) {
    const uint64_t da = desc_plain(SB, 1024, 128) + ((o_stage(s) + wg * 4096) >> 4);
    const uint64_t db = desc_sw128(SB + 16384, 8192, 1024) + (o_stage(s) >> 4);
    wg_fence();
    if (INIT) wg_gemm_n128_init(acc, da, db);
    #pragma unroll
    for (int kk = INIT ? 1 : 0; kk < 4; kk++) wg_gemm_n128(acc, da + (kk >> 1) * 512 + (kk & 1) * 128, db + kk * 128);
    wg_commit();
}
__device__ __forceinline__ void oproj_phase(int L, int wg, bf16* __restrict__ out) {
    const int c = cta_now(), tid = tid_now(), lane = tid & 31, W = tid >> 5, g = lane >> 2, t = lane & 3;
    const int row0 = (c >> 4) * 256 + (c & 1) * 128, col0 = ((c & 15) >> 1) * 128;
    float acc[64];
    mbar_wait(B_OF, 0);
    oproj_step<true>(acc, 0, wg);
    const uint32_t xa = SB + OFF_XT + (W * 16 + ((lane >> 3) & 1) * 8 + (lane & 7)) * 128, xs = (lane >> 4) ^ (lane & 7);
    mbar_wait(B_RES2, L);
    const float2 c0 = lds64f(SB + OFF_LC + (W * 16 + g) * 8), c1 = lds64f(SB + OFF_LC + (W * 16 + g + 8) * 8);
    #pragma unroll 1
    for (int k = 1; k < 16; k++) {
        wg_wait<0>();
        if ((tid & 127) == 0) mbar_arrive(B_OE + 8 * ((k - 1) & 3));
        mbar_wait(B_OF + 8 * (k & 3), (k >> 2) & 1);
        oproj_step<false>(acc, k & 3, wg);
        if (L == 1 && (k & 1)) {
            const uint32_t a = xa + (k & 8) * 2048 + ((xs ^ (k & 6)) << 4);
            uint32_t v0, v1, v2, v3;
            ldsm4(v0, v1, v2, v3, a);
            stsm4(a, add_ln2(v0, c0.x, c0.y), add_ln2(v1, c1.x, c1.y), add_ln2(v2, c0.x, c0.y), add_ln2(v3, c1.x, c1.y));
        }
    }
    uint32_t x[32];
    const uint32_t wra = SB + OFF_WR + (g == 4 ? t * 8 : 256), wrs = g == 4 ? 32 : 0;
    float2 wb[8];
    #pragma unroll
    for (int ks = 0; ks < 8; ks++) {
        ldsm4(x[4*ks], x[4*ks+1], x[4*ks+2], x[4*ks+3], xa + (ks >> 2) * 16384 + ((xs ^ ((ks & 3) * 2)) << 4));
        wb[ks] = lds64f(wra + ks * wrs);
    }
    wg_wait<0>();
    if ((tid & 127) == 0) mbar_arrive(B_OE + 24);
    {
        float sd[4] = {0.f, 0.f, 0.f, 0.f}, z0[4] = {0.f, 0.f, 0.f, 0.f}, z1[4] = {0.f, 0.f, 0.f, 0.f};
        #pragma unroll
        for (int ks = 0; ks < 8; ks++) {
            #pragma unroll
            for (int i = 0; i < 4; i++) x[4*ks + i] = badd2(x[4*ks + i], pack_bf16(acc[8*ks + 2*i], acc[8*ks + 2*i + 1]));
            mma_bf16(sd, x[4*ks], x[4*ks+1], x[4*ks+2], x[4*ks+3], __float_as_uint(wb[ks].x), __float_as_uint(wb[ks].y));
            mma_bf16(z0, x[4*ks], x[4*ks+1], x[4*ks+2], x[4*ks+3], x[4*ks], x[4*ks+2]);
            mma_bf16(z1, x[4*ks], x[4*ks+1], x[4*ks+2], x[4*ks+3], x[4*ks+1], x[4*ks+3]);
        }
        const float s0 = __shfl_sync(0xffffffffu, (g & 1) ? z0[1] : z0[0], 4 * g + (g >> 1));
        const float s1 = __shfl_sync(0xffffffffu, (g & 1) ? z1[3] : z1[2], 4 * g + (g >> 1));
        double* p = &g_acc[L][row0 + W * 16 + g][t];
        asm volatile("red.relaxed.gpu.global.add.f64 [%0], %1;" :: "l"(p), "d"((double)sel4(t, sd[0], s0, sd[0], 1.f)) : "memory");
        asm volatile("red.relaxed.gpu.global.add.f64 [%0], %1;" :: "l"(p + 32), "d"((double)sel4(t, sd[2], s1, sd[2], 1.f)) : "memory");
    }
    if (L == 0) {
        #pragma unroll
        for (int ks = 0; ks < 8; ks++) stsm4(xa + (ks >> 2) * 16384 + ((xs ^ ((ks & 3) * 2)) << 4), x[4*ks], x[4*ks+1], x[4*ks+2], x[4*ks+3]);
        fence_async_smem();
        named_arrive(N_XST + wg, 160);
    }
    const bool ffn = c < NFC;
    uint4 fa[32], fd[16];
    const uint32_t ga = SB + W * 2048 + ((lane >> 4) * 8 + (lane & 7)) * 64 + ((((lane >> 3) & 1) ^ ((lane >> 1) & 3)) << 4);
    if (ffn) mbar_wait(B_FE, L);
    #pragma unroll
    for (int i = 0; i < 12; i++) ldsm4t(fa[i].x, fa[i].y, fa[i].z, fa[i].w, (ga ^ ((i & 1) * 32)) + gu_piece(i >> 2) + (i & 2) * 512);
    float2 r0, r1;
    {
        const float ws = ldsf(SB + OFF_M + M_WS);
        const uint32_t row = row0 + W * 16 + g;
        const bool odd = t & 1, up = t & 2;
        const uint32_t me = row + (odd ? 8 : 0);
        uint4 v;
        uint32_t n = 0;
        do { v = ld_relaxed4(&g_acc[L][me][t & 2]); } while (__any_sync(0xffffffffu, up && v.w != 0x40200000u) && ++n < SPIN_MAX);
        spin_check(n);
        const float f0 = (float)__hiloint2double(v.y, v.x), f1 = (float)__hiloint2double(v.w, v.z);
        const float e0 = __shfl_xor_sync(0xffffffffu, f0, 2), e1 = __shfl_xor_sync(0xffffffffu, f1, 2);
        const float a[3] = {up ? e0 : f0, up ? e1 : f1, up ? f0 : e0};
        const uint4 tot = make_uint4(not_sent(a[0]), not_sent(a[1]), 0u, 0u);
        st_relaxed4_if(&g_sums[me], tot, L == 0 && col0 == 0 && t < 2);
        const float2 r = ln_coef(tot), ro = make_float2(__shfl_xor_sync(0xffffffffu, r.x, 1), __shfl_xor_sync(0xffffffffu, r.y, 1));
        r0 = odd ? ro : r; r1 = odd ? r : ro;
        const uint32_t k = min(order_bits(r.x * fmaf(-r.y, ws, a[2])), SENT - 1);
        const uint32_t m = redux_max(k), mrow = redux_min(k == m ? me : 0x7FFFFFFFu);
        if (me == mrow) sts128(SB + OFF_RT + W * 16, make_uint4(k, me, not_sent(r.y), not_sent(r.x)));
    }
    named_sync(1, 256);
    {
        const uint4 e = lds128(SB + OFF_RT + (lane & 7) * 16);
        const uint32_t m = redux_max(e.x), row = redux_min(e.x == m ? e.y : 0x7FFFFFFFu);
        const int lr = row - row0;
        st_relaxed4_if(&g_tab[L][(c & 15) >> 1][row0 >> 7][(lane >> 3) & 1], e, W == ((lr >> 4) ^ 1) && e.y == row && lane < 16);
        if ((lr >> 4) == W) {
            const bool hi = lr & 8;
            uint32_t* dst = &g_xrow[L][row0 >> 7][(col0 & 128) * 2 + (col0 >> 8) * 16 + t * 4];
            #pragma unroll
            for (int i = 0; i < 4; i++)
                st_relaxed4_if(dst + i * 64, make_uint4(min(hi ? x[8*i+1] : x[8*i], SENT - 1), min(hi ? x[8*i+3] : x[8*i+2], SENT - 1),
                               min(hi ? x[8*i+5] : x[8*i+4], SENT - 1), min(hi ? x[8*i+7] : x[8*i+6], SENT - 1)), g == (lr & 7));
        }
        __syncwarp();
    }
    if (L == 1) {
        const float b0 = -r0.x * r0.y, b1 = -r1.x * r1.y;
        #pragma unroll
        for (int ks = 0; ks < 8; ks++)
            stsm4(xa + (ks >> 2) * 16384 + ((xs ^ ((ks & 3) * 2)) << 4), add_ln2(x[4*ks], r0.x, b0), add_ln2(x[4*ks+1], r1.x, b1),
                  add_ln2(x[4*ks+2], r0.x, b0), add_ln2(x[4*ks+3], r1.x, b1));
        fence_async_smem();
        named_arrive(N_XST + wg, 160);
    }
    RouteOut rt;
    {
        const uint4* tp = &g_tab[L][(c & 15) >> 1][lane & 15][0];
        uint4 e = ld_relaxed4(tp);
        if (ffn) mbar_wait(B_FL, L);
        #pragma unroll
        for (int i = 12; i < 32; i++) ldsm4t(fa[i].x, fa[i].y, fa[i].z, fa[i].w, (ga ^ ((i & 1) * 32)) + gu_piece(i >> 2) + (i & 2) * 512);
        if (L == 0) named_arrive(N_GD, 288);
        uint32_t n = 0;
        while (has_sent(e) && ++n < SPIN_MAX) e = ld_relaxed4(tp);
        spin_check(n);
        __syncwarp();
        e = warp_best(e);
        rt = route_out(e);
        if (W == 7 && L == 0) { sts128(SB + OFF_RT + 128, e); named_arrive(N_RT, 128); }
    }
    uint2 xrow;
    {
        const uint32_t* xp = &g_xrow[L][rt.idx >> 7][W * 64 + (g >> 1) * 16 + t * 4 + (g & 1) * 2];
        xrow = ld_relaxed2(xp);
        if (ffn) mbar_wait(B_FD, L);
        const uint32_t wa = SB + OFF_FD + W * 8192 + ((lane >> 4) * 8 + (lane & 7)) * 128 + ((((lane >> 3) & 1) ^ (lane & 7)) << 4);
        #pragma unroll
        for (int i = 0; i < 16; i++) ldsm4t(fd[i].x, fd[i].y, fd[i].z, fd[i].w, (wa ^ (((i >> 1) & 3) * 32)) + (i >> 3) * 4096 + (i & 1) * 2048);
        if (L == 0) named_arrive(N_DD, 288);
        uint32_t n = 0;
        while ((xrow.x == SENT || xrow.y == SENT) && ++n < SPIN_MAX) xrow = ld_relaxed2(xp);
        spin_check(n);
        __syncwarp();
    }
    {
        const float nb = -rt.mean * rt.rstd;
        const uint32_t n0 = pack_bf16(fmaf(bf_lo(xrow.x), rt.rstd, nb), fmaf(bf_hi(xrow.x), rt.rstd, nb));
        const uint32_t n1 = pack_bf16(fmaf(bf_lo(xrow.y), rt.rstd, nb), fmaf(bf_hi(xrow.y), rt.rstd, nb));
        float gu[4][4];
        #pragma unroll
        for (int i = 0; i < 4; i++) { gu[i][0] = 0.f; gu[i][1] = 0.f; gu[i][2] = 0.f; gu[i][3] = 0.f; }
        #pragma unroll
        for (int ks = 0; ks < 8; ks++) {
            const uint32_t b0 = __shfl_sync(0xffffffffu, n0, 4 * ks + t), b1 = __shfl_sync(0xffffffffu, n1, 4 * ks + t);
            #pragma unroll
            for (int i = 0; i < 4; i++) {
                const uint4& a = fa[(ks >> 1) * 8 + (i >> 1) * 4 + (ks & 1) * 2 + (i & 1)];
                mma_bf16(gu[i], a.x, a.y, a.z, a.w, b0, b1);
            }
        }
        stsf(SB + OFF_PART + (W * 64 + t * 16 + g) * 4, sel4(t, gu[0][0], gu[1][0], gu[2][0], gu[3][0]));
        stsf(SB + OFF_PART + (W * 64 + t * 16 + g + 8) * 4, sel4(t, gu[0][2], gu[1][2], gu[2][2], gu[3][2]));
    }
    named_sync(1, 256);
    {
        float gp[8], up[8];
        #pragma unroll
        for (int i = 0; i < 8; i++) gp[i] = ldsf(SB + OFF_PART + (i * 64 + lane) * 4);
        #pragma unroll
        for (int i = 0; i < 8; i++) up[i] = ldsf(SB + OFF_PART + (i * 64 + 32 + lane) * 4);
        const float gv = bf_round(((gp[0] + gp[1]) + (gp[2] + gp[3])) + ((gp[4] + gp[5]) + (gp[6] + gp[7])));
        const float uv = bf_round(((up[0] + up[1]) + (up[2] + up[3])) + ((up[4] + up[5]) + (up[6] + up[7])));
        const float hv = bf_round(gv * rcp(1.f + ex2(gv * -1.4426950408889634f))) * uv;
        const uint32_t hp = pack_bf16(hv, __shfl_down_sync(0xffffffffu, hv, 1));
        uint32_t hb[4];
        #pragma unroll
        for (int i = 0; i < 4; i++) hb[i] = __shfl_sync(0xffffffffu, hp, 8 * i + 2 * t);
        float y[8][4];
        #pragma unroll
        for (int mb = 0; mb < 8; mb++) {
            y[mb][0] = 0.f; y[mb][1] = 0.f; y[mb][2] = 0.f; y[mb][3] = 0.f;
            #pragma unroll
            for (int ks = 0; ks < 2; ks++) mma_bf16(y[mb], fd[2*mb + ks].x, fd[2*mb + ks].y, fd[2*mb + ks].z, fd[2*mb + ks].w, hb[2 * ks], hb[2 * ks + 1]);
        }
        st_relaxed4_if(&g_ypart[L][min(c, NFC - 1)][tid * 4], make_uint4(not_sent(sel4(t, y[0][0], y[2][0], y[4][0], y[6][0])), not_sent(sel4(t, y[0][2], y[2][2], y[4][2], y[6][2])),
                       not_sent(sel4(t, y[1][0], y[3][0], y[5][0], y[7][0])), not_sent(sel4(t, y[1][2], y[3][2], y[5][2], y[7][2]))), ffn);
    }
    if (L == 1) {
        if (W == 7) ctr_wait(&g_xc[1][rt.idx >> 8], 32);
        unsigned short* dst = reinterpret_cast<unsigned short*>(out) + (size_t)rt.idx * D_ + ypos_col(c * 8 + (tid & 7));
        asm volatile("" : "+l"(dst));
        const float v = ffn_finish<256>(1, rt, tid, SB + OFF_FE, 1);
        if (tid < 8) asm volatile("st.global.u16 [%0], %1;" :: "l"(dst), "h"((unsigned short)(__float_as_uint(v) >> 16)) : "memory");
    }
}

constexpr int KW1 = 4, FW0 = 9;
constexpr int RK0 = 7;
static_assert(FW0 >= 8 && KW1 >= 3 && KW1 < 7, "buffer reuse");
__device__ __forceinline__ void qkv_fill(const CUtensorMap* tx, const CUtensorMap* tw, uint32_t bar, int st, int k) {
    const uint32_t sa = SB + st * Q_STB;
    mbar_expect_tx(bar, Q_STB);
    tma_load(sa, tx, k * 64, (blockIdx.x >> 4) * 256, bar);
    tma_load3(sa + Q_ABYTES, tw, (blockIdx.x & 15) * 64, k * 64, 0, bar);
}
__device__ __forceinline__ void oproj_fill(const Maps& mp, const char* osrc, int s, int par, int pair) {
    const uint32_t fb = B_OF + 8 * s, sa = SB + o_stage(s);
    mbar_expect_tx(fb, 32768);
    bulk_load(sa, osrc + (par * 16 + pair) * 8192, 16384, fb);
    tma_load5(sa + 16384, &mp.wo, 0, 0, par, pair, blockIdx.x & 14, fb);
}
__device__ __forceinline__ void producer_role(const Maps& mp) {
    const int c = blockIdx.x, mt = c >> 4, nt = c & 15, lane = threadIdx.x & 31;
    #pragma unroll 1
    for (int i = 2; i < 13; i++) tm_prefetch(&mp.xa0 + i);
    #pragma unroll 1
    for (int L = 0; L < 2; L++) {
        const uint32_t rb = L * 32;
        uint32_t st = 0, ph = L;
        #pragma unroll 1
        for (int k = L == 0 ? 3 : 0; k < 16; k++) {
            if (k == 0) { ctr_wait_all(&g_xc[0][mt], 32); fence_async_global(); named_sync(N_GD, 288); }
            if (k == 1) named_sync(N_DD, 288);
            mbar_wait(rb + B_QE + 8 * st, ph);
            qkv_fill(L == 0 ? &mp.xa0 : &mp.xa, &mp.wqkv, rb + B_QF + 8 * st, st, k);
            if (L == 1 && k >= RK0 && k < RK0 + 4) {
                if (k == RK0) mbar_expect_tx(B_SW, 4 * 12288);
                tma_load(SB + OFF_SIDE + (k - RK0) * 12288, &mp.r, c * 24, (k - RK0) * 256, B_SW);
            }
            if (++st == 3) { st = 0; ph ^= 1; }
        }
        mbar_wait(B_KV0, L);
        mbar_arrive_elect(rb + B_AF);
        {
            const int win = nt * 16 + ((mt + 1) & 7);
            mbar_expect_tx(rb + B_AF + 8, KV_WIN);
            #pragma unroll 1
            for (int h = 0; h < 2; h++) {
                ctr_wait_all(&g_kvc[L][0][0] + win, 2 + h);
                fence_async_global();
                bulk_load(SB + A_WIN + h * 16384, g_kv + (size_t)win * KV_WIN + h * 16384, 16384, rb + B_AF + 8);
            }
        }
        st = 2; ph = 1;
        #pragma unroll 1
        for (int w = 2; w < 16; w++) {
            const int win = nt * 16 + (w & 8) + ((mt + w) & 7);
            if (w <= 3 || w == 8) {
                ctr_wait_all(&g_kvc[L][0][0] + (w < 3 ? win : (win & ~7) + (lane & 7)), 3);
                fence_async_global();
            }
            mbar_wait(rb + B_AE + 8 * st, ph);
            mbar_expect_tx(rb + B_AF + 8 * st, KV_WIN);
            bulk_load(SB + st * A_WIN, g_kv + (size_t)win * KV_WIN, KV_WIN, rb + B_AF + 8 * st);
            if (w == KW1 || w == FW0) named_arrive(w == FW0 ? N_FW : N_KV1, 64);
            if (++st == 3) { st = 0; ph ^= 1; }
        }
        ctr_wait_all(&g_oc[L][mt * 2 + (nt & 1)][0][lane & 15], 1);
        fence_async_global();
        const char* osrc = g_o + (size_t)(mt * 2 + (nt & 1)) * 32 * 8192;
        #pragma unroll
        for (int k = 0; k < 4; k++) {
            mbar_wait(k < 2 ? rb + B_AE + 8 + 8 * k : k == 2 ? rb + B_AE : B_QAF, k < 2 ? 0 : k == 2 ? 1 : L);
            oproj_fill(mp, osrc, k, 0, 2 * k);
        }
        uint32_t ready = 0xFFFFu;
        #pragma unroll 1
        for (int k4 = 1; k4 < 4; k4++) {
            #pragma unroll
            for (int s = 0; s < 4; s++) {
                const int p = k4 * 8 + 2 * s;
                if (!((ready >> p) & 1)) {
                    ready = smem_wait_any(SB + OFF_M + M_ORDY + 4 * L, 1u << p);
                    fence_async_global();
                }
                mbar_wait(B_OE + 8 * s, (k4 - 1) & 1);
                oproj_fill(mp, osrc, s, p >> 4, p & 15);
            }
        }
        if (c < NFC) {
            mbar_expect_tx(B_FL, 5 * 16384);
            mbar_expect_tx(B_FD, 4 * 16384);
            #pragma unroll 1
            for (int i = 3; i < 12; i++) {
                mbar_wait(B_OE + (i < 5 ? 0 : i == 5 ? 8 : i < 9 ? 16 : 24), 1);
                if (i == 8) mbar_wait(B_FL, L);
                ffn_load(mp, c, i, SB + (i < 8 ? gu_piece(i) : OFF_FD + (i - 8) * 16384), i < 8 ? B_FL : B_FD, true);
            }
        }
    }
}

__global__ void __launch_bounds__(384, 1) k_all(const bf16* __restrict__ x0, const bf16* __restrict__ wo, const bf16* __restrict__ w_r, bf16* __restrict__ out,
                                                const __grid_constant__ Maps mp) {
    extern __shared__ __align__(1024) char smem[];
    if (smem_u32(smem) != SB) __trap();
    const int warp = warp_uniform(threadIdx.x >> 5), wg = warp >> 2;
    {
        const int grp = warp >= 8 ? warp - 8 : warp + 4;
        #pragma unroll
        for (int i = 0; i < 4; i++) mbar_init(BB + grp * 32 + i * 8, grp < 7 ? 1 : grp < 10 ? 2 : 8);
        fence_mbar_init();
    }
    if (warp == 8) {
        #pragma unroll 1
        for (int s = 0; s < 3; s++) qkv_fill(&mp.xa0, &mp.wqkv, B_QF + 8 * s, s, s);
    }
    __syncthreads();
    if (wg == 2) {
        reg_dec<40>();
        if (warp == 8) producer_role(mp);
        else side_role(mp, x0, wo, w_r);
        if (gridDim.y == 2) {
            uint32_t v = threadIdx.x;
            #pragma unroll
            for (int i = 0; i < 1500; i++) asm volatile("fma.rn.f16x2 %0, %0, %0, %0;" : "+r"(v));
            sts32(SB, v);
        }
    } else {
        reg_inc<232>();
        #pragma unroll 1
        for (int L = 0; L < 2; L++) {
            qkv_phase(L, wg);
            attention_phase(L, wg);
            oproj_phase(L, wg, out);
        }
    }
}

typedef CUresult (*EncodeFn)(CUtensorMap*, CUtensorMapDataType, cuuint32_t, void*, const cuuint64_t*, const cuuint64_t*, const cuuint32_t*,
                             const cuuint32_t*, CUtensorMapInterleave, CUtensorMapSwizzle, CUtensorMapL2promotion, CUtensorMapFloatOOBfill);

void make_map(EncodeFn enc, CUtensorMap* tm, const void* ptr, int rank, const cuuint64_t* dims, const cuuint64_t* strides, const cuuint32_t* box, CUtensorMapSwizzle sw) {
    const cuuint32_t es[5] = {1, 1, 1, 1, 1};
    enc(tm, CU_TENSOR_MAP_DATA_TYPE_BFLOAT16, rank, const_cast<void*>(ptr), dims, strides, box, es, CU_TENSOR_MAP_INTERLEAVE_NONE, sw,
        box[0] == 64 ? CU_TENSOR_MAP_L2_PROMOTION_L2_128B : CU_TENSOR_MAP_L2_PROMOTION_NONE, CU_TENSOR_MAP_FLOAT_OOB_FILL_NONE);
}
void make_map2(EncodeFn enc, CUtensorMap* tm, const void* ptr, uint64_t cols, uint64_t rows, uint32_t bc, uint32_t br, CUtensorMapSwizzle sw) {
    const cuuint64_t dims[2] = {cols, rows}, strides[1] = {cols * 2};
    const cuuint32_t box[2] = {bc, br};
    make_map(enc, tm, ptr, 2, dims, strides, box, sw);
}

}

extern "C" void kernel_launch(void* const* d_in, const int* in_sizes, int n_in, void* d_out, int out_size) {
    const bf16* x0 = (const bf16*)d_in[0];
    const bf16* wqkv = (const bf16*)d_in[1];
    const bf16* wo = (const bf16*)d_in[2];
    const bf16* w_r = (const bf16*)d_in[4];
    const bf16* w_gate = (const bf16*)d_in[5];
    const bf16* w_up = (const bf16*)d_in[6];
    const bf16* w_down = (const bf16*)d_in[7];

    EncodeFn enc = nullptr;
    cudaDriverEntryPointQueryResult qr;
    cudaGetDriverEntryPoint("cuTensorMapEncodeTiled", (void**)&enc, cudaEnableDefault, &qr);
    void* p_x;
    cudaGetSymbolAddress(&p_x, g_x);
    Maps mp;
    const CUtensorMapSwizzle S128 = CU_TENSOR_MAP_SWIZZLE_128B;
    make_map2(enc, &mp.x0, x0, D_, S_, 64, 64, S128);
    make_map2(enc, &mp.x, p_x, D_, S_, 64, 64, S128);
    make_map2(enc, &mp.out, d_out, D_, S_, 64, 16, S128);
    make_map2(enc, &mp.xs, p_x, D_, S_, 64, 16, S128);
    make_map2(enc, &mp.xa0, x0, D_, S_, 64, 256, S128);
    make_map2(enc, &mp.xa, p_x, D_, S_, 64, 256, S128);
    make_map2(enc, &mp.w64, wqkv, 3 * D_, D_, 64, 64, S128);
    {
        const cuuint64_t dims[3] = {D_, D_, 3}, strides[2] = {3 * D_ * 2, D_ * 2};
        const cuuint32_t box[3] = {64, 64, 3};
        make_map(enc, &mp.wqkv, wqkv, 3, dims, strides, box, S128);
    }
    make_map2(enc, &mp.r, wqkv, 3 * D_, D_, 24, 256, CU_TENSOR_MAP_SWIZZLE_NONE);
    make_map2(enc, &mp.g, w_gate, FF, D_, 32, 256, CU_TENSOR_MAP_SWIZZLE_64B);
    make_map2(enc, &mp.u, w_up, FF, D_, 32, 256, CU_TENSOR_MAP_SWIZZLE_64B);
    {
        const cuuint64_t dims[5] = {64, 32, 2, 16, 16}, strides[4] = {D_ * 2, 32 * D_ * 2, 64 * D_ * 2, 128};
        const cuuint32_t box[5] = {64, 32, 1, 2, 2};
        make_map(enc, &mp.wo, wo, 5, dims, strides, box, S128);
    }
    {
        const cuuint64_t dims[3] = {64, FF, 16}, strides[2] = {D_ * 2, 128};
        const cuuint32_t box[3] = {64, 32, 4};
        make_map(enc, &mp.d, w_down, 3, dims, strides, box, S128);
    }
    cudaFuncSetAttribute(k_all, cudaFuncAttributeMaxDynamicSharedMemorySize, K_SMEM);
    k_all<<<128, 384, K_SMEM, cudaStreamPerThread>>>(x0, wo, w_r, (bf16*)d_out, mp);
}
```

```cpp
#include <cuda_runtime.h>
#include <cuda_bf16.h>
#include <cuda_fp16.h>
#include <cuda.h>
#include <cudaTypedefs.h>
#include <stdint.h>

namespace {

typedef __nv_bfloat16 bf16;

constexpr int S_ = 2048, D_ = 1024, NH = 32, FF = 3584, NFC = FF / 32;
constexpr float LN_EPS = 1e-5f;
constexpr float QSCALE = 0.17677669529663687f * 1.4426950408889634f;
constexpr uint32_t SENT = 0xFFFFFFFFu;

constexpr int KV_WIN = 32768;
__device__ __align__(1024) char g_kv[NH * 8 * KV_WIN];
__device__ __align__(1024) char g_o[32 * 2 * 16 * 4096];
__device__ __align__(1024) bf16 g_x[S_ * D_];
__device__ float g_csum[8 * 3 * D_];
__device__ float g_wsq[8 * 96];
__device__ float2 g_rs0[S_];
__device__ __align__(128) double g_acc[2][S_][4];
__device__ __align__(128) uint4 g_sums[S_];
__device__ __align__(128) uint32_t g_ypart[2][NFC][D_];
__device__ __align__(128) uint4 g_tab[2][8][16][2];
__device__ __align__(128) uint32_t g_xrow[2][16][D_ / 2];
__device__ __align__(128) uint32_t g_x2row[D_];
__device__ __align__(128) uint32_t g_fix[3 * D_];
__device__ uint32_t g_c0;
__device__ __align__(128) uint32_t g_kvc[2][NH][8];
__device__ __align__(128) uint32_t g_oc[2][16][2][16];
__device__ __align__(128) uint32_t g_xc[2][8];
struct RouteOut { int idx; float r; float mean; float rstd; };

constexpr uint32_t SB = 1024;

__device__ __forceinline__ uint32_t smem_u32(const void* p) { return (uint32_t)__cvta_generic_to_shared(p); }
__device__ __forceinline__ void mbar_arrive(uint32_t bar) { asm volatile("mbarrier.arrive.shared::cta.b64 _, [%0];" :: "r"(bar) : "memory"); }
__device__ __forceinline__ void mbar_wait(uint32_t bar, uint32_t parity) {
    asm volatile("{\n.reg .pred p, q;\n.reg .u32 n;\nmov.u32 n, 0;\n"
                 "LAB_WAIT:\nadd.u32 n, n, 1;\nmbarrier.try_wait.parity.shared::cta.b64 p, [%0], %1;\n"
                 "setp.lt.and.u32 q, n, 0x800000, !p;\n@q bra LAB_WAIT;\n@!p st.shared.u32 [n], n;\n}" :: "r"(bar), "r"(parity) : "memory");
}
__device__ __forceinline__ void mbar_arrive_elect(uint32_t bar) {
    asm volatile("{\n.reg .pred p;\nelect.sync _|p, 0xffffffff;\n@p mbarrier.arrive.shared::cta.b64 _, [%0];\n}" :: "r"(bar) : "memory");
}
__device__ __forceinline__ int tid_now() { int v; asm volatile("mov.u32 %0, %%tid.x;" : "=r"(v)); return v; }
__device__ __forceinline__ int cta_now() { int v; asm volatile("mov.u32 %0, %%ctaid.x;" : "=r"(v)); return v; }
__device__ __forceinline__ int warp_uniform(int v) { return __shfl_sync(0xffffffffu, v, 0); }
__device__ __forceinline__ void fence_mbar_init() { asm volatile("fence.mbarrier_init.release.cluster;" ::: "memory"); }
__device__ __forceinline__ void fence_async_smem() { asm volatile("fence.proxy.async.shared::cta;" ::: "memory"); }
__device__ __forceinline__ void fence_async_global() { asm volatile("fence.proxy.async.global;" ::: "memory"); }
__device__ __forceinline__ void named_sync(int id, int n) { asm volatile("bar.sync %0, %1;" :: "r"(id), "r"(n) : "memory"); }
__device__ __forceinline__ void named_arrive(int id, int n) { asm volatile("bar.arrive %0, %1;" :: "r"(id), "r"(n) : "memory"); }
__device__ __forceinline__ bool named_any(bool p, int id) {
    uint32_t r;
    asm volatile("{\n.reg .pred a, b;\nsetp.ne.u32 a, %1, 0;\nbarrier.cta.red.or.pred b, %2, 128, a;\nselp.u32 %0, 1, 0, b;\n}" : "=r"(r) : "r"((uint32_t)p), "r"(id) : "memory");
    return r != 0;
}
#define ELECT(op) "{\n.reg .pred e;\nelect.sync _|e, 0xffffffff;\n@e " op "\n}"
__device__ __forceinline__ void mbar_init(uint32_t bar, int cnt) { asm volatile(ELECT("mbarrier.init.shared::cta.b64 [%0], %1;") :: "r"(bar), "r"(cnt) : "memory"); }
__device__ __forceinline__ void mbar_expect_tx(uint32_t bar, uint32_t bytes) { asm volatile(ELECT("mbarrier.arrive.expect_tx.shared::cta.b64 _, [%0], %1;") :: "r"(bar), "r"(bytes) : "memory"); }
__device__ __forceinline__ void bulk_load(uint32_t dst, const void* src, uint32_t bytes, uint32_t bar) {
    asm volatile(ELECT("cp.async.bulk.shared::cluster.global.mbarrier::complete_tx::bytes [%0], [%1], %2, [%3];") :: "r"(dst), "l"(src), "r"(bytes), "r"(bar) : "memory");
}
__device__ __forceinline__ void bulk_store(void* dst, uint32_t src, uint32_t bytes) {
    asm volatile(ELECT("cp.async.bulk.global.shared::cta.bulk_group [%0], [%1], %2;") :: "l"(dst), "r"(src), "r"(bytes) : "memory");
}
__device__ __forceinline__ void bulk_commit() { asm volatile("cp.async.bulk.commit_group;" ::: "memory"); }
__device__ __forceinline__ void bulk_wait() { asm volatile("cp.async.bulk.wait_group 0;" ::: "memory"); }
__device__ __forceinline__ void l2_prefetch(const void* src, uint32_t bytes) {
    asm volatile(ELECT("cp.async.bulk.prefetch.L2.global [%0], %1;") :: "l"(src), "r"(bytes) : "memory");
}
__device__ __forceinline__ void tma_load(uint32_t dst, const CUtensorMap* tm, int c0, int c1, uint32_t bar) {
    asm volatile(ELECT("cp.async.bulk.tensor.2d.shared::cluster.global.mbarrier::complete_tx::bytes [%0], [%1, {%3, %4}], [%2];")
                 :: "r"(dst), "l"(tm), "r"(bar), "r"(c0), "r"(c1) : "memory");
}
__device__ __forceinline__ void tma_load3(uint32_t dst, const CUtensorMap* tm, int c0, int c1, int c2, uint32_t bar) {
    asm volatile(ELECT("cp.async.bulk.tensor.3d.shared::cluster.global.mbarrier::complete_tx::bytes [%0], [%1, {%3, %4, %5}], [%2];")
                 :: "r"(dst), "l"(tm), "r"(bar), "r"(c0), "r"(c1), "r"(c2) : "memory");
}
__device__ __forceinline__ uint64_t evict_first() { uint64_t a; asm("createpolicy.fractional.L2::evict_first.b64 %0, 1.0;" : "=l"(a)); return a; }
__device__ __forceinline__ void tma_load_h(uint32_t dst, const CUtensorMap* tm, int c0, int c1, uint32_t bar, bool ef) {
    if (!ef) tma_load(dst, tm, c0, c1, bar);
    else asm volatile(ELECT("cp.async.bulk.tensor.2d.shared::cluster.global.mbarrier::complete_tx::bytes.L2::cache_hint [%0], [%1, {%3, %4}], [%2], %5;")
                      :: "r"(dst), "l"(tm), "r"(bar), "r"(c0), "r"(c1), "l"(evict_first()) : "memory");
}
__device__ __forceinline__ void tma_load3_h(uint32_t dst, const CUtensorMap* tm, int c0, int c1, int c2, uint32_t bar, bool ef) {
    if (!ef) tma_load3(dst, tm, c0, c1, c2, bar);
    else asm volatile(ELECT("cp.async.bulk.tensor.3d.shared::cluster.global.mbarrier::complete_tx::bytes.L2::cache_hint [%0], [%1, {%3, %4, %5}], [%2], %6;")
                      :: "r"(dst), "l"(tm), "r"(bar), "r"(c0), "r"(c1), "r"(c2), "l"(evict_first()) : "memory");
}
__device__ __forceinline__ void tma_load5(uint32_t dst, const CUtensorMap* tm, int c0, int c1, int c2, int c3, int c4, uint32_t bar) {
    asm volatile(ELECT("cp.async.bulk.tensor.5d.shared::cluster.global.mbarrier::complete_tx::bytes [%0], [%1, {%3, %4, %5, %6, %7}], [%2];")
                 :: "r"(dst), "l"(tm), "r"(bar), "r"(c0), "r"(c1), "r"(c2), "r"(c3), "r"(c4) : "memory");
}
__device__ __forceinline__ void tma_store(const CUtensorMap* tm, uint32_t src, int c0, int c1) {
    asm volatile(ELECT("cp.async.bulk.tensor.2d.global.shared::cta.bulk_group [%0, {%2, %3}], [%1];") :: "l"(tm), "r"(src), "r"(c0), "r"(c1) : "memory");
}
__device__ __forceinline__ void tm_prefetch(const CUtensorMap* tm) { asm volatile(ELECT("prefetch.tensormap [%0];") :: "l"(tm) : "memory"); }
__device__ __forceinline__ uint32_t lds32(uint32_t a) { uint32_t v; asm volatile("ld.shared.b32 %0, [%1];" : "=r"(v) : "r"(a) : "memory"); return v; }
__device__ __forceinline__ float ldsf(uint32_t a) { return __uint_as_float(lds32(a)); }
__device__ __forceinline__ float2 lds64f(uint32_t a) { float2 v; asm volatile("ld.shared.v2.f32 {%0, %1}, [%2];" : "=f"(v.x), "=f"(v.y) : "r"(a) : "memory"); return v; }
__device__ __forceinline__ uint4 lds128(uint32_t a) { uint4 v; asm volatile("ld.shared.v4.b32 {%0, %1, %2, %3}, [%4];" : "=r"(v.x), "=r"(v.y), "=r"(v.z), "=r"(v.w) : "r"(a) : "memory"); return v; }
__device__ __forceinline__ void sts32(uint32_t a, uint32_t v) { asm volatile("st.shared.b32 [%0], %1;" :: "r"(a), "r"(v) : "memory"); }
__device__ __forceinline__ void stsf(uint32_t a, float v) { sts32(a, __float_as_uint(v)); }
__device__ __forceinline__ void sts64f(uint32_t a, float x, float y) { asm volatile("st.shared.v2.f32 [%0], {%1, %2};" :: "r"(a), "f"(x), "f"(y) : "memory"); }
__device__ __forceinline__ void sts128(uint32_t a, const uint4& v) { asm volatile("st.shared.v4.b32 [%0], {%1, %2, %3, %4};" :: "r"(a), "r"(v.x), "r"(v.y), "r"(v.z), "r"(v.w) : "memory"); }
__device__ __forceinline__ void stsm4(uint32_t a, uint32_t x, uint32_t y, uint32_t z, uint32_t w) {
    asm volatile("stmatrix.sync.aligned.m8n8.x4.shared.b16 [%0], {%1, %2, %3, %4};" :: "r"(a), "r"(x), "r"(y), "r"(z), "r"(w) : "memory");
}
__device__ __forceinline__ void ldsm4(uint32_t& a0, uint32_t& a1, uint32_t& a2, uint32_t& a3, uint32_t addr) {
    asm volatile("ldmatrix.sync.aligned.m8n8.x4.shared.b16 {%0,%1,%2,%3}, [%4];" : "=r"(a0), "=r"(a1), "=r"(a2), "=r"(a3) : "r"(addr) : "memory");
}
__device__ __forceinline__ void ldsm4t(uint32_t& a0, uint32_t& a1, uint32_t& a2, uint32_t& a3, uint32_t addr) {
    asm volatile("ldmatrix.sync.aligned.m8n8.x4.trans.shared.b16 {%0,%1,%2,%3}, [%4];" : "=r"(a0), "=r"(a1), "=r"(a2), "=r"(a3) : "r"(addr) : "memory");
}
__device__ __forceinline__ void mma_bf16(float (&c)[4], uint32_t a0, uint32_t a1, uint32_t a2, uint32_t a3, uint32_t b0, uint32_t b1) {
    asm("mma.sync.aligned.m16n8k16.row.col.f32.bf16.bf16.f32 {%0,%1,%2,%3}, {%4,%5,%6,%7}, {%8,%9}, {%0,%1,%2,%3};"
        : "+f"(c[0]), "+f"(c[1]), "+f"(c[2]), "+f"(c[3]) : "r"(a0), "r"(a1), "r"(a2), "r"(a3), "r"(b0), "r"(b1));
}
__device__ __forceinline__ void mma_f16(float (&c)[4], uint32_t a0, uint32_t a1, uint32_t a2, uint32_t a3, uint32_t b0, uint32_t b1) {
    asm("mma.sync.aligned.m16n8k16.row.col.f32.f16.f16.f32 {%0,%1,%2,%3}, {%4,%5,%6,%7}, {%8,%9}, {%0,%1,%2,%3};"
        : "+f"(c[0]), "+f"(c[1]), "+f"(c[2]), "+f"(c[3]) : "r"(a0), "r"(a1), "r"(a2), "r"(a3), "r"(b0), "r"(b1));
}
__device__ __forceinline__ uint32_t ld_acquire(const void* p) { uint32_t v; asm volatile("ld.acquire.gpu.global.u32 %0, [%1];" : "=r"(v) : "l"(p) : "memory"); return v; }
__device__ __forceinline__ void sts_release(uint32_t a, uint32_t v) { asm volatile("st.release.cta.shared.u32 [%0], %1;" :: "r"(a), "r"(v) : "memory"); }
__device__ __forceinline__ uint32_t ld_relaxed(const void* p) { uint32_t v; asm volatile("ld.relaxed.gpu.global.u32 %0, [%1];" : "=r"(v) : "l"(p) : "memory"); return v; }
__device__ __forceinline__ uint4 ld_relaxed4(const void* p) {
    uint4 v; asm volatile("ld.relaxed.gpu.global.v4.b32 {%0, %1, %2, %3}, [%4];" : "=r"(v.x), "=r"(v.y), "=r"(v.z), "=r"(v.w) : "l"(p) : "memory"); return v;
}
__device__ __forceinline__ uint2 ld_relaxed2(const void* p) { uint2 v; asm volatile("ld.relaxed.gpu.global.v2.b32 {%0, %1}, [%2];" : "=r"(v.x), "=r"(v.y) : "l"(p) : "memory"); return v; }
__device__ __forceinline__ void st_relaxed(void* p, uint32_t v) { asm volatile("st.relaxed.gpu.global.u32 [%0], %1;" :: "l"(p), "r"(v) : "memory"); }
__device__ __forceinline__ void st_relaxed4_if(void* p, const uint4& v, bool on) {
    asm volatile("{\n.reg .pred q;\nsetp.ne.u32 q, %5, 0;\n@q st.relaxed.gpu.global.v4.b32 [%0], {%1, %2, %3, %4};\n}"
                 :: "l"(p), "r"(v.x), "r"(v.y), "r"(v.z), "r"(v.w), "r"((uint32_t)on) : "memory");
}
__device__ __forceinline__ uint32_t not_sent(float v) { const uint32_t u = __float_as_uint(v); return u == SENT ? 0x7FFFFFFFu : u; }
__device__ __forceinline__ bool has_sent(const uint4& v) { return max(max(v.x, v.y), max(v.z, v.w)) == SENT; }
constexpr uint32_t SPIN_MAX = 1u << 22;
__device__ __forceinline__ void spin_check(uint32_t n) { asm volatile("{\n.reg .pred p;\nsetp.ge.u32 p, %0, %1;\n@p st.global.u32 [%2], %0;\n}" :: "r"(n), "n"(SPIN_MAX), "l"(0ull) : "memory"); }
__device__ __forceinline__ void ctr_arrive(uint32_t* c, uint32_t n = 1) { asm volatile(ELECT("red.release.gpu.global.add.u32 [%0], %1;") :: "l"(c), "r"(n) : "memory"); }
__device__ __forceinline__ void ctr_wait(const uint32_t* c, uint32_t target) {
    asm volatile("{\n.reg .pred p;\n.reg .u32 n, v;\nmov.u32 n, 0;\n"
                 "LAB_WAIT:\nld.acquire.gpu.global.u32 v, [%0];\nsetp.ge.u32 p, v, %1;\n@p bra LAB_DONE;\n"
                 "add.u32 n, n, 1;\nsetp.lt.u32 p, n, 0x400000;\n@p bra LAB_WAIT;\ntrap;\nLAB_DONE:\n}" :: "l"(c), "r"(target) : "memory");
}
__device__ __forceinline__ void ctr_wait_all(const uint32_t* c, uint32_t target) {
    asm volatile("{\n.reg .pred p;\n.reg .u32 n, v;\nmov.u32 n, 0;\n"
                 "LAB_WAIT:\nld.acquire.gpu.global.u32 v, [%0];\nsetp.ge.u32 p, v, %1;\nvote.sync.all.pred p, p, 0xffffffff;\n@p bra.uni LAB_DONE;\n"
                 "add.u32 n, n, 1;\nsetp.lt.u32 p, n, 0x400000;\n@p bra.uni LAB_WAIT;\ntrap;\nLAB_DONE:\n}" :: "l"(c), "r"(target) : "memory");
}
__device__ __forceinline__ uint32_t smem_wait_any(uint32_t a, uint32_t mask) {
    uint32_t v;
    asm volatile("{\n.reg .pred p;\n.reg .u32 n, t;\nmov.u32 n, 0;\n"
                 "LAB_WAIT:\nld.acquire.cta.shared.u32 %0, [%1];\nand.b32 t, %0, %2;\nsetp.ne.u32 p, t, 0;\nvote.sync.all.pred p, p, 0xffffffff;\n@p bra.uni LAB_DONE;\n"
                 "add.u32 n, n, 1;\nsetp.lt.u32 p, n, 0x4000000;\n@p bra.uni LAB_WAIT;\ntrap;\nLAB_DONE:\n}" : "=r"(v) : "r"(a), "r"(mask) : "memory");
    return warp_uniform(v);
}
__device__ __forceinline__ void publish(uint32_t* c, uint32_t n = 1) { bulk_wait(); fence_async_global(); ctr_arrive(c, n); }

__device__ __forceinline__ void wg_fence() { asm volatile("wgmma.fence.sync.aligned;" ::: "memory"); }
__device__ __forceinline__ void wg_commit() { asm volatile("wgmma.commit_group.sync.aligned;" ::: "memory"); }
template <int N> __device__ __forceinline__ void wg_wait() { asm volatile("wgmma.wait_group.sync.aligned %0;" :: "n"(N) : "memory"); }
template <int N> __device__ __forceinline__ void reg_inc() { asm volatile("setmaxnreg.inc.sync.aligned.u32 %0;" :: "n"(N)); }
template <int N> __device__ __forceinline__ void reg_dec() { asm volatile("setmaxnreg.dec.sync.aligned.u32 %0;" :: "n"(N)); }
__host__ __device__ constexpr uint64_t desc_plain(uint32_t addr, uint32_t lbo, uint32_t sbo) {
    return (uint64_t)((addr & 0x3FFFF) >> 4) | ((uint64_t)(lbo >> 4) << 16) | ((uint64_t)(sbo >> 4) << 32);
}
__host__ __device__ constexpr uint64_t desc_sw128(uint32_t addr, uint32_t lbo, uint32_t sbo) { return desc_plain(addr, lbo, sbo) | (1ull << 62); }

__device__ __forceinline__ float ex2(float x) { float y; asm("ex2.approx.ftz.f32 %0, %1;" : "=f"(y) : "f"(x)); return y; }
__device__ __forceinline__ float rcp(float x) { float y; asm("rcp.approx.ftz.f32 %0, %1;" : "=f"(y) : "f"(x)); return y; }
__device__ __forceinline__ float rsq(float x) { float y; asm("rsqrt.approx.ftz.f32 %0, %1;" : "=f"(y) : "f"(x)); return y; }
__device__ __forceinline__ uint32_t pack_bf16(float lo, float hi) { uint32_t r; asm("cvt.rn.bf16x2.f32 %0, %1, %2;" : "=r"(r) : "f"(hi), "f"(lo)); return r; }
__device__ __forceinline__ uint32_t pack_f16(float lo, float hi) { uint32_t r; asm("cvt.rn.f16x2.f32 %0, %1, %2;" : "=r"(r) : "f"(hi), "f"(lo)); return r; }
__device__ __forceinline__ uint32_t round8(uint32_t v) { return (v + 0x00040004u) & 0xFFF8FFF8u; }
__device__ __forceinline__ float bf_lo(uint32_t v) { return __uint_as_float(v << 16); }
__device__ __forceinline__ float bf_hi(uint32_t v) { return __uint_as_float(v & 0xFFFF0000u); }
__device__ __forceinline__ float bf_round(float x) { return __uint_as_float(pack_bf16(0.f, x)); }
__device__ __forceinline__ uint32_t badd2(uint32_t a, uint32_t b) { uint32_t r; asm("add.rn.bf16x2 %0, %1, %2;" : "=r"(r) : "r"(a), "r"(b)); return r; }
__device__ __forceinline__ void h2_unpack(uint32_t v, float& lo, float& hi) {
    asm("{.reg .f16 l, h; mov.b32 {l, h}, %2; cvt.f32.f16 %0, l; cvt.f32.f16 %1, h;}" : "=f"(lo), "=f"(hi) : "r"(v));
}
__device__ __forceinline__ uint32_t add_ln2(uint32_t x, float rstd, float nb) { return badd2(x, pack_bf16(fmaf(bf_lo(x), rstd, nb), fmaf(bf_hi(x), rstd, nb))); }
__device__ __forceinline__ float sel4(int t, float a0, float a1, float a2, float a3) {
    float r;
    asm("{\n.reg .pred p, q;\n.reg .f32 x, y;\nsetp.ne.u32 p, %1, 0;\nsetp.ne.u32 q, %2, 0;\nselp.f32 x, %4, %3, p;\nselp.f32 y, %6, %5, p;\nselp.f32 %0, y, x, q;\n}"
        : "=f"(r) : "r"(t & 1), "r"(t & 2), "f"(a0), "f"(a1), "f"(a2), "f"(a3));
    return r;
}
__device__ __forceinline__ float warp_sum(float v) {
    #pragma unroll
    for (int o = 16; o > 0; o >>= 1) v += __shfl_xor_sync(0xffffffffu, v, o);
    return v;
}
__device__ __forceinline__ uint32_t redux_or(uint32_t v) { uint32_t r; asm volatile("redux.sync.or.b32 %0, %1, 0xffffffff;" : "=r"(r) : "r"(v)); return r; }
__device__ __forceinline__ uint32_t redux_max(uint32_t v) { uint32_t r; asm volatile("redux.sync.max.u32 %0, %1, 0xffffffff;" : "=r"(r) : "r"(v)); return r; }
__device__ __forceinline__ uint32_t redux_min(uint32_t v) { uint32_t r; asm volatile("redux.sync.min.u32 %0, %1, 0xffffffff;" : "=r"(r) : "r"(v)); return r; }


__device__ __forceinline__ void wg_gemm_n128(float (&d)[64], uint64_t desca, uint64_t desc) {
    asm volatile("{\n.reg .pred p;\nsetp.ne.b32 p, 1, 0;\n"
        "wgmma.mma_async.sync.aligned.m64n128k16.f32.bf16.bf16 "
        "{%0,%1,%2,%3,%4,%5,%6,%7,%8,%9,%10,%11,%12,%13,%14,%15,%16,%17,%18,%19,%20,%21,%22,%23,%24,%25,%26,%27,%28,%29,%30,%31,%32,%33,%34,%35,%36,%37,%38,%39,%40,%41,%42,%43,%44,%45,%46,%47,%48,%49,%50,%51,%52,%53,%54,%55,%56,%57,%58,%59,%60,%61,%62,%63}, "
        "%64, %65, p, 1, 1, 0, 1;\n}\n"
        : "+f"(d[0]), "+f"(d[1]), "+f"(d[2]), "+f"(d[3]), "+f"(d[4]), "+f"(d[5]), "+f"(d[6]), "+f"(d[7]),
          "+f"(d[8]), "+f"(d[9]), "+f"(d[10]), "+f"(d[11]), "+f"(d[12]), "+f"(d[13]), "+f"(d[14]), "+f"(d[15]),
          "+f"(d[16]), "+f"(d[17]), "+f"(d[18]), "+f"(d[19]), "+f"(d[20]), "+f"(d[21]), "+f"(d[22]), "+f"(d[23]),
          "+f"(d[24]), "+f"(d[25]), "+f"(d[26]), "+f"(d[27]), "+f"(d[28]), "+f"(d[29]), "+f"(d[30]), "+f"(d[31]),
          "+f"(d[32]), "+f"(d[33]), "+f"(d[34]), "+f"(d[35]), "+f"(d[36]), "+f"(d[37]), "+f"(d[38]), "+f"(d[39]),
          "+f"(d[40]), "+f"(d[41]), "+f"(d[42]), "+f"(d[43]), "+f"(d[44]), "+f"(d[45]), "+f"(d[46]), "+f"(d[47]),
          "+f"(d[48]), "+f"(d[49]), "+f"(d[50]), "+f"(d[51]), "+f"(d[52]), "+f"(d[53]), "+f"(d[54]), "+f"(d[55]),
          "+f"(d[56]), "+f"(d[57]), "+f"(d[58]), "+f"(d[59]), "+f"(d[60]), "+f"(d[61]), "+f"(d[62]), "+f"(d[63])
        : "l"(desca), "l"(desc));
}
__device__ __forceinline__ void wg_gemm_n128_init(float (&d)[64], uint64_t desca, uint64_t desc) {
    asm volatile("{\n.reg .pred p;\nsetp.ne.b32 p, 0, 0;\n"
        "wgmma.mma_async.sync.aligned.m64n128k16.f32.bf16.bf16 "
        "{%0,%1,%2,%3,%4,%5,%6,%7,%8,%9,%10,%11,%12,%13,%14,%15,%16,%17,%18,%19,%20,%21,%22,%23,%24,%25,%26,%27,%28,%29,%30,%31,%32,%33,%34,%35,%36,%37,%38,%39,%40,%41,%42,%43,%44,%45,%46,%47,%48,%49,%50,%51,%52,%53,%54,%55,%56,%57,%58,%59,%60,%61,%62,%63}, "
        "%64, %65, p, 1, 1, 0, 1;\n}\n"
        : "=f"(d[0]), "=f"(d[1]), "=f"(d[2]), "=f"(d[3]), "=f"(d[4]), "=f"(d[5]), "=f"(d[6]), "=f"(d[7]),
          "=f"(d[8]), "=f"(d[9]), "=f"(d[10]), "=f"(d[11]), "=f"(d[12]), "=f"(d[13]), "=f"(d[14]), "=f"(d[15]),
          "=f"(d[16]), "=f"(d[17]), "=f"(d[18]), "=f"(d[19]), "=f"(d[20]), "=f"(d[21]), "=f"(d[22]), "=f"(d[23]),
          "=f"(d[24]), "=f"(d[25]), "=f"(d[26]), "=f"(d[27]), "=f"(d[28]), "=f"(d[29]), "=f"(d[30]), "=f"(d[31]),
          "=f"(d[32]), "=f"(d[33]), "=f"(d[34]), "=f"(d[35]), "=f"(d[36]), "=f"(d[37]), "=f"(d[38]), "=f"(d[39]),
          "=f"(d[40]), "=f"(d[41]), "=f"(d[42]), "=f"(d[43]), "=f"(d[44]), "=f"(d[45]), "=f"(d[46]), "=f"(d[47]),
          "=f"(d[48]), "=f"(d[49]), "=f"(d[50]), "=f"(d[51]), "=f"(d[52]), "=f"(d[53]), "=f"(d[54]), "=f"(d[55]),
          "=f"(d[56]), "=f"(d[57]), "=f"(d[58]), "=f"(d[59]), "=f"(d[60]), "=f"(d[61]), "=f"(d[62]), "=f"(d[63])
        : "l"(desca), "l"(desc));
}
__device__ __forceinline__ void wg_gemm_n192(float (&d)[96], uint64_t desca, uint64_t desc) {
    asm volatile("{\n.reg .pred p;\nsetp.ne.b32 p, 1, 0;\n"
        "wgmma.mma_async.sync.aligned.m64n192k16.f32.bf16.bf16 "
        "{%0,%1,%2,%3,%4,%5,%6,%7,%8,%9,%10,%11,%12,%13,%14,%15,%16,%17,%18,%19,%20,%21,%22,%23,%24,%25,%26,%27,%28,%29,%30,%31,%32,%33,%34,%35,%36,%37,%38,%39,%40,%41,%42,%43,%44,%45,%46,%47,%48,%49,%50,%51,%52,%53,%54,%55,%56,%57,%58,%59,%60,%61,%62,%63,%64,%65,%66,%67,%68,%69,%70,%71,%72,%73,%74,%75,%76,%77,%78,%79,%80,%81,%82,%83,%84,%85,%86,%87,%88,%89,%90,%91,%92,%93,%94,%95}, "
        "%96, %97, p, 1, 1, 0, 1;\n}\n"
        : "+f"(d[0]), "+f"(d[1]), "+f"(d[2]), "+f"(d[3]), "+f"(d[4]), "+f"(d[5]), "+f"(d[6]), "+f"(d[7]),
          "+f"(d[8]), "+f"(d[9]), "+f"(d[10]), "+f"(d[11]), "+f"(d[12]), "+f"(d[13]), "+f"(d[14]), "+f"(d[15]),
          "+f"(d[16]), "+f"(d[17]), "+f"(d[18]), "+f"(d[19]), "+f"(d[20]), "+f"(d[21]), "+f"(d[22]), "+f"(d[23]),
          "+f"(d[24]), "+f"(d[25]), "+f"(d[26]), "+f"(d[27]), "+f"(d[28]), "+f"(d[29]), "+f"(d[30]), "+f"(d[31]),
          "+f"(d[32]), "+f"(d[33]), "+f"(d[34]), "+f"(d[35]), "+f"(d[36]), "+f"(d[37]), "+f"(d[38]), "+f"(d[39]),
          "+f"(d[40]), "+f"(d[41]), "+f"(d[42]), "+f"(d[43]), "+f"(d[44]), "+f"(d[45]), "+f"(d[46]), "+f"(d[47]),
          "+f"(d[48]), "+f"(d[49]), "+f"(d[50]), "+f"(d[51]), "+f"(d[52]), "+f"(d[53]), "+f"(d[54]), "+f"(d[55]),
          "+f"(d[56]), "+f"(d[57]), "+f"(d[58]), "+f"(d[59]), "+f"(d[60]), "+f"(d[61]), "+f"(d[62]), "+f"(d[63]),
          "+f"(d[64]), "+f"(d[65]), "+f"(d[66]), "+f"(d[67]), "+f"(d[68]), "+f"(d[69]), "+f"(d[70]), "+f"(d[71]),
          "+f"(d[72]), "+f"(d[73]), "+f"(d[74]), "+f"(d[75]), "+f"(d[76]), "+f"(d[77]), "+f"(d[78]), "+f"(d[79]),
          "+f"(d[80]), "+f"(d[81]), "+f"(d[82]), "+f"(d[83]), "+f"(d[84]), "+f"(d[85]), "+f"(d[86]), "+f"(d[87]),
          "+f"(d[88]), "+f"(d[89]), "+f"(d[90]), "+f"(d[91]), "+f"(d[92]), "+f"(d[93]), "+f"(d[94]), "+f"(d[95])
        : "l"(desca), "l"(desc));
}
__device__ __forceinline__ void wg_gemm_n192_init(float (&d)[96], uint64_t desca, uint64_t desc) {
    asm volatile("{\n.reg .pred p;\nsetp.ne.b32 p, 0, 0;\n"
        "wgmma.mma_async.sync.aligned.m64n192k16.f32.bf16.bf16 "
        "{%0,%1,%2,%3,%4,%5,%6,%7,%8,%9,%10,%11,%12,%13,%14,%15,%16,%17,%18,%19,%20,%21,%22,%23,%24,%25,%26,%27,%28,%29,%30,%31,%32,%33,%34,%35,%36,%37,%38,%39,%40,%41,%42,%43,%44,%45,%46,%47,%48,%49,%50,%51,%52,%53,%54,%55,%56,%57,%58,%59,%60,%61,%62,%63,%64,%65,%66,%67,%68,%69,%70,%71,%72,%73,%74,%75,%76,%77,%78,%79,%80,%81,%82,%83,%84,%85,%86,%87,%88,%89,%90,%91,%92,%93,%94,%95}, "
        "%96, %97, p, 1, 1, 0, 1;\n}\n"
        : "=f"(d[0]), "=f"(d[1]), "=f"(d[2]), "=f"(d[3]), "=f"(d[4]), "=f"(d[5]), "=f"(d[6]), "=f"(d[7]),
          "=f"(d[8]), "=f"(d[9]), "=f"(d[10]), "=f"(d[11]), "=f"(d[12]), "=f"(d[13]), "=f"(d[14]), "=f"(d[15]),
          "=f"(d[16]), "=f"(d[17]), "=f"(d[18]), "=f"(d[19]), "=f"(d[20]), "=f"(d[21]), "=f"(d[22]), "=f"(d[23]),
          "=f"(d[24]), "=f"(d[25]), "=f"(d[26]), "=f"(d[27]), "=f"(d[28]), "=f"(d[29]), "=f"(d[30]), "=f"(d[31]),
          "=f"(d[32]), "=f"(d[33]), "=f"(d[34]), "=f"(d[35]), "=f"(d[36]), "=f"(d[37]), "=f"(d[38]), "=f"(d[39]),
          "=f"(d[40]), "=f"(d[41]), "=f"(d[42]), "=f"(d[43]), "=f"(d[44]), "=f"(d[45]), "=f"(d[46]), "=f"(d[47]),
          "=f"(d[48]), "=f"(d[49]), "=f"(d[50]), "=f"(d[51]), "=f"(d[52]), "=f"(d[53]), "=f"(d[54]), "=f"(d[55]),
          "=f"(d[56]), "=f"(d[57]), "=f"(d[58]), "=f"(d[59]), "=f"(d[60]), "=f"(d[61]), "=f"(d[62]), "=f"(d[63]),
          "=f"(d[64]), "=f"(d[65]), "=f"(d[66]), "=f"(d[67]), "=f"(d[68]), "=f"(d[69]), "=f"(d[70]), "=f"(d[71]),
          "=f"(d[72]), "=f"(d[73]), "=f"(d[74]), "=f"(d[75]), "=f"(d[76]), "=f"(d[77]), "=f"(d[78]), "=f"(d[79]),
          "=f"(d[80]), "=f"(d[81]), "=f"(d[82]), "=f"(d[83]), "=f"(d[84]), "=f"(d[85]), "=f"(d[86]), "=f"(d[87]),
          "=f"(d[88]), "=f"(d[89]), "=f"(d[90]), "=f"(d[91]), "=f"(d[92]), "=f"(d[93]), "=f"(d[94]), "=f"(d[95])
        : "l"(desca), "l"(desc));
}
__device__ __forceinline__ void wg_qk_init(uint32_t (&d)[32], uint32_t a0, uint32_t a1, uint32_t a2, uint32_t a3, uint64_t desc) {
    asm volatile("{\n.reg .pred p;\nsetp.ne.b32 p, 0, 0;\n"
        "wgmma.mma_async.sync.aligned.m64n128k16.f16.f16.f16 "
        "{%0,%1,%2,%3,%4,%5,%6,%7,%8,%9,%10,%11,%12,%13,%14,%15,%16,%17,%18,%19,%20,%21,%22,%23,%24,%25,%26,%27,%28,%29,%30,%31}, "
        "{%32,%33,%34,%35}, %36, p, 1, 1, 0;\n}\n"
        : "=r"(d[0]), "=r"(d[1]), "=r"(d[2]), "=r"(d[3]), "=r"(d[4]), "=r"(d[5]), "=r"(d[6]), "=r"(d[7]),
          "=r"(d[8]), "=r"(d[9]), "=r"(d[10]), "=r"(d[11]), "=r"(d[12]), "=r"(d[13]), "=r"(d[14]), "=r"(d[15]),
          "=r"(d[16]), "=r"(d[17]), "=r"(d[18]), "=r"(d[19]), "=r"(d[20]), "=r"(d[21]), "=r"(d[22]), "=r"(d[23]),
          "=r"(d[24]), "=r"(d[25]), "=r"(d[26]), "=r"(d[27]), "=r"(d[28]), "=r"(d[29]), "=r"(d[30]), "=r"(d[31])
        : "r"(a0), "r"(a1), "r"(a2), "r"(a3), "l"(desc));
}
__device__ __forceinline__ void wg_qk_acc(uint32_t (&d)[32], uint64_t desca, uint64_t desc) {
    asm volatile("{\n.reg .pred p;\nsetp.ne.b32 p, 1, 0;\n"
        "wgmma.mma_async.sync.aligned.m64n128k16.f16.f16.f16 "
        "{%0,%1,%2,%3,%4,%5,%6,%7,%8,%9,%10,%11,%12,%13,%14,%15,%16,%17,%18,%19,%20,%21,%22,%23,%24,%25,%26,%27,%28,%29,%30,%31}, "
        "%32, %33, p, 1, 1, 0, 0;\n}\n"
        : "+r"(d[0]), "+r"(d[1]), "+r"(d[2]), "+r"(d[3]), "+r"(d[4]), "+r"(d[5]), "+r"(d[6]), "+r"(d[7]),
          "+r"(d[8]), "+r"(d[9]), "+r"(d[10]), "+r"(d[11]), "+r"(d[12]), "+r"(d[13]), "+r"(d[14]), "+r"(d[15]),
          "+r"(d[16]), "+r"(d[17]), "+r"(d[18]), "+r"(d[19]), "+r"(d[20]), "+r"(d[21]), "+r"(d[22]), "+r"(d[23]),
          "+r"(d[24]), "+r"(d[25]), "+r"(d[26]), "+r"(d[27]), "+r"(d[28]), "+r"(d[29]), "+r"(d[30]), "+r"(d[31])
        : "l"(desca), "l"(desc));
}
__device__ __forceinline__ void wg_pv_init(uint32_t (&d)[10], uint32_t a0, uint32_t a1, uint32_t a2, uint32_t a3, uint64_t desc) {
    asm volatile("{\n.reg .pred p;\nsetp.ne.b32 p, 0, 0;\n"
        "wgmma.mma_async.sync.aligned.m64n40k16.f16.f16.f16 "
        "{%0,%1,%2,%3,%4,%5,%6,%7,%8,%9}, "
        "{%10,%11,%12,%13}, %14, p, 1, 1, 1;\n}\n"
        : "=r"(d[0]), "=r"(d[1]), "=r"(d[2]), "=r"(d[3]), "=r"(d[4]), "=r"(d[5]), "=r"(d[6]), "=r"(d[7]),
          "=r"(d[8]), "=r"(d[9])
        : "r"(a0), "r"(a1), "r"(a2), "r"(a3), "l"(desc));
}
__device__ __forceinline__ void wg_pv_acc(uint32_t (&d)[10], uint32_t a0, uint32_t a1, uint32_t a2, uint32_t a3, uint64_t desc) {
    asm volatile("{\n.reg .pred p;\nsetp.ne.b32 p, 1, 0;\n"
        "wgmma.mma_async.sync.aligned.m64n40k16.f16.f16.f16 "
        "{%0,%1,%2,%3,%4,%5,%6,%7,%8,%9}, "
        "{%10,%11,%12,%13}, %14, p, 1, 1, 1;\n}\n"
        : "+r"(d[0]), "+r"(d[1]), "+r"(d[2]), "+r"(d[3]), "+r"(d[4]), "+r"(d[5]), "+r"(d[6]), "+r"(d[7]),
          "+r"(d[8]), "+r"(d[9])
        : "r"(a0), "r"(a1), "r"(a2), "r"(a3), "l"(desc));
}

constexpr int Q_ABYTES = 256 * 64 * 2, Q_STB = Q_ABYTES + 192 * 64 * 2;
constexpr int OFF_SIDE = 3 * Q_STB;
constexpr int OFF_XS = OFF_SIDE + 49152;
constexpr int OFF_CS = OFF_XS + 4096;
constexpr int OFF_RC = OFF_CS + 768;
constexpr int OFF_FIX = OFF_RC + 2048;
constexpr int A_WIN = KV_WIN + 4096;
constexpr int OFF_QA = 3 * A_WIN;
constexpr int OFF_LC = OFF_QA + 32768;
constexpr int OFF_FE = 147456;
constexpr int OFF_XT = 196608;
__host__ __device__ constexpr uint32_t o_stage(uint32_t s) { return s == 3 ? OFF_QA : s == 2 ? 0 : (s + 1) * A_WIN; }
__host__ __device__ constexpr uint32_t gu_piece(uint32_t i) { return i < 3 ? OFF_FE + i * 16384 : i < 6 ? (i - 1) * 16384 : (i - 6) * 16384; }
constexpr int OFF_FD = 5 * 16384;
constexpr int OFF_BAR = OFF_XT + 32768;
constexpr int OFF_PART = OFF_BAR + 384;
constexpr int OFF_RED = OFF_PART + 2048;
constexpr int OFF_RT = OFF_RED + 96;
constexpr int OFF_M = OFF_RT + 144;
constexpr int OFF_WR = OFF_M + 72;
constexpr int K_SMEM = OFF_WR + 264;
static_assert(K_SMEM <= 232448 && OFF_FIX + 768 <= OFF_BAR && OFF_QA + 32768 <= OFF_FE, "smem");
constexpr uint32_t CH_OK = 0x38003800u;
constexpr int M_SC = 0,
              M_IVS = 24,
              M_ISC = 32,
              M_OK = 40,
              M_WS = 48,
              M_RIDX = 60,
              M_ORDY = 64;
constexpr uint32_t BB = SB + OFF_BAR;
constexpr uint32_t B_QF = BB, B_EPI = BB + 24, B_RES2 = BB + 56, B_AF = BB + 64, B_RES = BB + 120, B_OF = BB + 128,
                   B_FE = BB + 160, B_FL = BB + 168, B_FD = BB + 184, B_PR = BB + 192, B_FW = B_PR, B_SW = BB + 216,
                   B_QE = BB + 224, B_QAF = BB + 248, B_OE = BB + 288, B_AE = BB + 320, B_K0 = BB + 344, B_KV0 = BB + 376;

constexpr int N_OST = 5, N_XST = 9, N_RT = 11, N_KV1 = 12, N_FW = 13, N_GD = 14, N_DD = 15;

struct Maps { CUtensorMap xa0, wqkv, xa, x0, x, out, w64, wo, r, g, u, d; };

__device__ __forceinline__ float2 ln_coef(const uint4& s) {
    const float mean = __uint_as_float(s.x) * (1.f / D_);
    return make_float2(rsq(fmaxf(fmaf(-mean, mean, fmaf(__uint_as_float(s.y), 1.f / D_, LN_EPS)), LN_EPS)), mean);
}
__device__ __forceinline__ uint32_t order_bits(float r) { const uint32_t u = __float_as_uint(r); return (u & 0x80000000u) ? ~u : (u | 0x80000000u); }
__device__ __forceinline__ uint4 warp_best(const uint4& e) {
    const uint32_t m = redux_max(e.x), row = redux_min(e.x == m ? e.y : 0x7FFFFFFFu);
    const int src = __ffs(__ballot_sync(0xffffffffu, e.y == row)) - 1;
    return make_uint4(m, row, __shfl_sync(0xffffffffu, e.z, src), __shfl_sync(0xffffffffu, e.w, src));
}
__device__ __forceinline__ RouteOut route_out(const uint4& e) {
    RouteOut rt;
    rt.idx = e.y; rt.r = __uint_as_float((e.x & 0x80000000u) ? e.x & 0x7FFFFFFFu : ~e.x); rt.mean = __uint_as_float(e.z); rt.rstd = __uint_as_float(e.w);
    return rt;
}

__device__ __forceinline__ void prep_work(const bf16* __restrict__ x0, const CUtensorMap* tmW, int t) {
    const int c = blockIdx.x, lane = t & 31, warp = warp_uniform(t >> 5);
    const int ki = c >> 4, n = c & 15;
    constexpr uint32_t red = SB + OFF_SIDE, xs = red + 4096;
    if (warp == 0) {
        mbar_expect_tx(B_PR, 32768);
        bulk_load(xs, x0 + (size_t)c * 16 * D_, 32768, B_PR);
        mbar_expect_tx(B_PR + 8, 16384);
        tma_load(xs + 32768, tmW, 2 * D_ + n * 64, ki * 128, B_PR + 8);
        tma_load(xs + 32768 + 8192, tmW, 2 * D_ + n * 64, ki * 128 + 64, B_PR + 8);
    }
    const uint4 sent = make_uint4(SENT, SENT, SENT, SENT);
    for (int i = t; i < 2 * NFC * 2; i += 96) reinterpret_cast<uint4*>(&g_ypart[0][0][0])[c * (2 * NFC * 2) + i] = sent;
    if (t < 64) reinterpret_cast<uint4*>(&g_acc[0][0][0])[c * 64 + t] = make_uint4(0u, 0u, 0u, 0u);
    if (t >= 64 && t < 80) g_sums[c * 16 + t - 64] = sent;
    if (t < 2) reinterpret_cast<uint4*>(g_x2row)[c * 2 + t] = sent;
    else if (t < 8) reinterpret_cast<uint4*>(g_fix)[c * 6 + t - 2] = sent;
    else if (t < 12) (&g_kvc[0][0][0])[c * 4 + t - 8] = 0u;
    else if (t >= 24 && t < 32) (&g_oc[0][0][0][0])[c * 8 + t - 24] = 0u;
    else if (t == 13 && c < 16) (&g_xc[0][0])[c] = 0u;
    else if (t >= 16 && t < 20) (&g_tab[0][0][0][0])[c * 4 + t - 16] = sent;
    else if (t >= 32 && t < 64) reinterpret_cast<uint4*>(&g_xrow[0][0][0])[c * 32 + t - 32] = sent;
    mbar_wait(B_PR, 0);
    #pragma unroll 1
    for (int r = warp; r < 16; r += 3) {
        float s = 0.f, q = 0.f;
        #pragma unroll
        for (int i = 0; i < 4; i++) {
            const uint4 u = lds128(xs + r * 2048 + (lane + 32 * i) * 16);
            const float f[8] = {bf_lo(u.x), bf_hi(u.x), bf_lo(u.y), bf_hi(u.y), bf_lo(u.z), bf_hi(u.z), bf_lo(u.w), bf_hi(u.w)};
            #pragma unroll
            for (int e = 0; e < 8; e++) { s += f[e]; q = fmaf(f[e], f[e], q); }
        }
        #pragma unroll
        for (int o = 16; o > 0; o >>= 1) { s += __shfl_xor_sync(0xffffffffu, s, o); q += __shfl_xor_sync(0xffffffffu, q, o); }
        const float mean = s * (1.f / D_);
        const float var = fmaxf(q * (1.f / D_) - mean * mean, 0.f);
        if (lane == 0) g_rs0[c * 16 + r] = make_float2(rsqrtf(var + LN_EPS), mean);
    }
    named_sync(2, 96);
    if (warp == 0) {
        mbar_expect_tx(B_PR + 16, 32768);
        #pragma unroll
        for (int b = 0; b < 4; b++) tma_load(xs + b * 8192, tmW, (b >> 1) * D_ + n * 64, ki * 128 + (b & 1) * 64, B_PR + 16);
    }
    const int j = t & 7, rg = t >> 3;
    #pragma unroll 1
    for (int blk = 0; blk < 3; blk++) {
        const int type = blk == 0 ? 2 : blk - 1;
        const uint32_t wb = xs + type * 16384;
        if (blk < 2) mbar_wait(B_PR + 8 + 8 * blk, 0);
        float cs[8];
        uint32_t z2[4] = {0u, 0u, 0u, 0u};
        #pragma unroll
        for (int i = 0; i < 8; i++) cs[i] = 0.f;
        #pragma unroll 4
        for (int r = rg; r < 128; r += 12) {
            const uint4 u = lds128(wb + r * 128 + ((j ^ (r & 7)) << 4));
            cs[0] += bf_lo(u.x); cs[1] += bf_hi(u.x); cs[2] += bf_lo(u.y); cs[3] += bf_hi(u.y);
            cs[4] += bf_lo(u.z); cs[5] += bf_hi(u.z); cs[6] += bf_lo(u.w); cs[7] += bf_hi(u.w);
            asm("fma.rn.bf16x2 %0, %1, %1, %0;" : "+r"(z2[0]) : "r"(u.x));
            asm("fma.rn.bf16x2 %0, %1, %1, %0;" : "+r"(z2[1]) : "r"(u.y));
            asm("fma.rn.bf16x2 %0, %1, %1, %0;" : "+r"(z2[2]) : "r"(u.z));
            asm("fma.rn.bf16x2 %0, %1, %1, %0;" : "+r"(z2[3]) : "r"(u.w));
        }
        #pragma unroll
        for (int i = 0; i < 8; i++) { cs[i] += __shfl_xor_sync(0xffffffffu, cs[i], 8); cs[i] += __shfl_xor_sync(0xffffffffu, cs[i], 16); }
        float z = ((bf_lo(z2[0]) + bf_hi(z2[0])) + (bf_lo(z2[1]) + bf_hi(z2[1]))) + ((bf_lo(z2[2]) + bf_hi(z2[2])) + (bf_lo(z2[3]) + bf_hi(z2[3])));
        z += __shfl_xor_sync(0xffffffffu, z, 1); z += __shfl_xor_sync(0xffffffffu, z, 2);
        z += __shfl_xor_sync(0xffffffffu, z, 8); z += __shfl_xor_sync(0xffffffffu, z, 16);
        if (lane < 8) {
            #pragma unroll
            for (int i = 0; i < 8; i++) stsf(red + (warp * 200 + type * 64 + j * 8 + i) * 4, cs[i]);
            if ((lane & 3) == 0) stsf(red + (warp * 200 + 192 + type * 2 + (lane >> 2)) * 4, z);
        }
    }
    named_sync(2, 96);
    for (int i = t; i < 198; i += 96) {
        const float v = ldsf(red + i * 4) + ldsf(red + (200 + i) * 4) + ldsf(red + (400 + i) * 4);
        if (i < 192) g_csum[ki * (3 * D_) + (i >> 6) * D_ + n * 64 + (i & 63)] = v;
        else g_wsq[ki * 96 + ((i - 192) >> 1) * 32 + n * 2 + (i & 1)] = v;
    }
    named_sync(2, 96);
    if (warp == 0) { ctr_arrive(&g_c0); ctr_wait(&g_c0, 128); }
    named_sync(2, 96);
}

__device__ __forceinline__ float pow2_inv(float b) {
    const int e = min(max((int)(__float_as_uint(b) >> 23) + 1, 20), 234);
    return __uint_as_float((uint32_t)(254 - e) << 23);
}
__device__ __forceinline__ void epi_inputs(int L) {
    const int t = tid_now() - 288, mt = cta_now() >> 4, nt = cta_now() & 15;
    float p[2][8], r0[3], r1[3];
    #pragma unroll
    for (int k = 0; k < 2; k++)
        #pragma unroll
        for (int q = 0; q < 8; q++) p[k][q] = __ldcg(g_csum + q * (3 * D_) + ((t + 96 * k) >> 6) * D_ + nt * 64 + ((t + 96 * k) & 63));
    #pragma unroll
    for (int k = 0; k < 2; k++) stsf(SB + OFF_CS + (t + 96 * k) * 4, ((p[k][0] + p[k][1]) + (p[k][2] + p[k][3])) + ((p[k][4] + p[k][5]) + (p[k][6] + p[k][7])));
    bool wait;
    uint32_t n = 0;
    do {
        wait = false;
        #pragma unroll
        for (int k = 0; k < 3; k++) {
            const int row = mt * 256 + min(t + 96 * k, 255);
            if (L == 0) { const float2 s = __ldcg(&g_rs0[row]); r0[k] = s.x; r1[k] = s.y; }
            else { const uint4 s = ld_relaxed4(&g_sums[row]); r0[k] = __uint_as_float(s.x); r1[k] = __uint_as_float(s.y); wait = wait || has_sent(s); }
        }
    } while (wait && ++n < SPIN_MAX);
    #pragma unroll
    for (int k = 0; k < 3; k++) {
        if (L != 0) {
            const float mean = r0[k] * (1.f / D_);
            const float var = fmaxf(r1[k] * (1.f / D_) - mean * mean, 0.f);
            const float a = 1.f + rsqrtf(var + LN_EPS);
            r0[k] = a * rsqrtf(a * a * var + LN_EPS); r1[k] = mean;
        }
        if (t + 96 * k < 256) sts64f(SB + OFF_RC + (t + 96 * k) * 8, r0[k], r1[k]);
    }
    if (L == 0 && t < 32) {
        float z = 0.f;
        if (t < 6) {
            #pragma unroll
            for (int q = 0; q < 8; q++) z += __ldcg(g_wsq + q * 96 + (t >> 1) * 32 + nt * 2 + (t & 1));
        }
        const float b = sqrtf(z) * (t < 2 ? 34.f * QSCALE : 34.f);
        const float sc = t < 4 ? fminf(pow2_inv(b) * 32768.f, 1.f) : pow2_inv(b);
        const float bk = __shfl_down_sync(0xffffffffu, b, 2), sk = __shfl_down_sync(0xffffffffu, sc, 2);
        if (t < 6) stsf(SB + OFF_M + M_SC + t * 4, t < 2 ? sc * QSCALE : sc);
        if (t < 2) { stsf(SB + OFF_M + M_ISC + t * 4, 1.f / (sc * sk)); sts32(SB + OFF_M + M_OK + t * 4, sc == 1.f && sk == 1.f && b * bk < 60000.f ? CH_OK : 0u); }
        if (t == 4 || t == 5) stsf(SB + OFF_M + M_IVS + (t - 4) * 4, 1.f / sc);
    }
}

__device__ __forceinline__ int ypos_col(int p) { return (p >> 7) * 128 + ((p >> 1) & 7) * 16 + (p & 1) * 8 + ((p >> 4) & 7); }

template <int NT>
__device__ __forceinline__ float ffn_finish(int L, const RouteOut& rt, int t, uint32_t red, int bid) {
    constexpr int NL = (2 * NFC + NT - 1) / NT;
    const int c = cta_now(), col = ypos_col(c * 8 + (t & 7));
    const uint32_t* src = &g_ypart[L][t >> 1][c * 8 + (t & 1) * 4];
    uint32_t n = 0, xp;
    do { xp = ld_relaxed(&g_xrow[L][rt.idx >> 7][((col >> 5) & 7) * 64 + (col >> 8) * 16 + (col & 6) * 2 + ((col >> 3) & 3)]); } while (xp == SENT && ++n < SPIN_MAX);
    uint4 v[NL];
    #pragma unroll
    for (int i = 0; i < NL; i++) v[i] = t + NT * i < 2 * NFC ? ld_relaxed4(src + i * (NT / 2) * D_) : make_uint4(0u, 0u, 0u, 0u);
    const float xv = (col & 1) ? bf_hi(xp) : bf_lo(xp);
    float rsel = bf_round(rcp(1.f + ex2(bf_round(rt.r) * -1.4426950408889634f))), xn = bf_round((xv - rt.mean) * rt.rstd);
    asm volatile("" : "+f"(rsel), "+f"(xn));
    while (true) {
        bool wait = false;
        #pragma unroll
        for (int i = 0; i < NL; i++) wait = wait || has_sent(v[i]);
        if (!wait || ++n >= SPIN_MAX) break;
        #pragma unroll
        for (int i = 0; i < NL; i++) if (t + NT * i < 2 * NFC) v[i] = ld_relaxed4(src + i * (NT / 2) * D_);
    }
    spin_check(n);
    __syncwarp();
    float a[4] = {0.f, 0.f, 0.f, 0.f};
    #pragma unroll
    for (int i = 0; i < NL; i++) { a[0] += __uint_as_float(v[i].x); a[1] += __uint_as_float(v[i].y); a[2] += __uint_as_float(v[i].z); a[3] += __uint_as_float(v[i].w); }
    const bool b1 = t & 2, b2 = t & 4;
    a[0] = (b1 ? a[1] : a[0]) + __shfl_xor_sync(0xffffffffu, b1 ? a[0] : a[1], 2);
    a[2] = (b1 ? a[3] : a[2]) + __shfl_xor_sync(0xffffffffu, b1 ? a[2] : a[3], 2);
    a[0] = (b2 ? a[2] : a[0]) + __shfl_xor_sync(0xffffffffu, b2 ? a[0] : a[2], 4);
    a[0] += __shfl_xor_sync(0xffffffffu, a[0], 8); a[0] += __shfl_xor_sync(0xffffffffu, a[0], 16);
    if ((t & 31) < 8) stsf(red + (t >> 5) * 32 + (t & 1) * 16 + (t & 6) * 2, a[0]);
    named_sync(bid, NT);
    float y = 0.f, y2 = 0.f;
    #pragma unroll
    for (int i = 0; i < NT / 32; i++) { const float p = ldsf(red + (t & 7) * 4 + i * 32); if (i & 1) y2 += p; else y += p; }
    y += y2;
    return bf_round(xv + bf_round(xn + bf_round(bf_round(y) * rsel)));
}

__device__ __forceinline__ void routed_qkv(int ridx) {
    const int t = tid_now() - 288, c = cta_now(), lane = t & 31, warp = t >> 5;
    constexpr uint32_t red = SB + OFF_RED;
    {
        uint4 v[3];
        uint32_t n = 0;
        do {
            v[0] = ld_relaxed4(g_x2row + t * 4); v[1] = ld_relaxed4(g_x2row + (t + 96) * 4);
            v[2] = t < 64 ? ld_relaxed4(g_x2row + (t + 192) * 4) : make_uint4(0u, 0u, 0u, 0u);
        } while ((has_sent(v[0]) || has_sent(v[1]) || has_sent(v[2])) && ++n < SPIN_MAX);
        spin_check(n);
        __syncwarp();
        float f[12];
        float s = 0.f;
        #pragma unroll
        for (int i = 0; i < 3; i++) { f[4*i] = __uint_as_float(v[i].x); f[4*i+1] = __uint_as_float(v[i].y); f[4*i+2] = __uint_as_float(v[i].z); f[4*i+3] = __uint_as_float(v[i].w); }
        #pragma unroll
        for (int i = 0; i < 12; i++) s += f[i];
        s = warp_sum(s);
        if (lane == 0) stsf(red + warp * 4, s);
        named_sync(2, 96);
        const float mean = (ldsf(red) + ldsf(red + 4) + ldsf(red + 8)) * (1.f / D_);
        float q = 0.f;
        #pragma unroll
        for (int i = 0; i < 12; i++) { f[i] -= mean; if (i < 8 || t < 64) q = fmaf(f[i], f[i], q); }
        q = warp_sum(q);
        if (lane == 0) stsf(red + 16 + warp * 4, q);
        named_sync(2, 96);
        const float rstd = rsqrtf((ldsf(red + 16) + ldsf(red + 20) + ldsf(red + 24)) * (1.f / D_) + LN_EPS);
        #pragma unroll
        for (int i = 0; i < 3; i++)
            if (i < 2 || t < 64) sts128(SB + OFF_XS + (t + 96 * i) * 16, make_uint4(pack_bf16(0.f, f[4*i] * rstd), pack_bf16(0.f, f[4*i+1] * rstd), pack_bf16(0.f, f[4*i+2] * rstd), pack_bf16(0.f, f[4*i+3] * rstd)));
    }
    named_sync(2, 96);
    mbar_wait(B_SW, 0);
    float a[8];
    #pragma unroll
    for (int i = 0; i < 8; i++) a[i] = 0.f;
    const uint32_t wa = SB + OFF_SIDE + t * 16, xa = SB + OFF_XS + (t / 3) * 4;
    #pragma unroll 4
    for (int i = 0; i < 32; i++) {
        const uint4 u = lds128(wa + i * 1536);
        const float xv = ldsf(xa + i * 128);
        a[0] = fmaf(xv, bf_lo(u.x), a[0]); a[1] = fmaf(xv, bf_hi(u.x), a[1]); a[2] = fmaf(xv, bf_lo(u.y), a[2]); a[3] = fmaf(xv, bf_hi(u.y), a[3]);
        a[4] = fmaf(xv, bf_lo(u.z), a[4]); a[5] = fmaf(xv, bf_hi(u.z), a[5]); a[6] = fmaf(xv, bf_lo(u.w), a[6]); a[7] = fmaf(xv, bf_hi(u.w), a[7]);
    }
    named_sync(2, 96);
    sts128(SB + OFF_SIDE + t * 32, make_uint4(__float_as_uint(a[0]), __float_as_uint(a[1]), __float_as_uint(a[2]), __float_as_uint(a[3])));
    sts128(SB + OFF_SIDE + t * 32 + 16, make_uint4(__float_as_uint(a[4]), __float_as_uint(a[5]), __float_as_uint(a[6]), __float_as_uint(a[7])));
    named_sync(2, 96);
    {
        float y = 0.f;
        #pragma unroll
        for (int i = 0; i < 8; i++) y += ldsf(SB + OFF_SIDE + ((t & 3) * 8 + i) * 96 + (t >> 2) * 4);
        y += __shfl_xor_sync(0xffffffffu, y, 1); y += __shfl_xor_sync(0xffffffffu, y, 2);
        if ((t & 3) == 0) st_relaxed(g_fix + c * 24 + (t >> 2), not_sent(y));
    }
    if ((ridx >> 8) == (c >> 4) && t < 24) {
        const uint32_t* src = g_fix + (t >> 3) * D_ + (c & 15) * 64 + (t & 7) * 8;
        uint4 a, b;
        uint32_t n = 0;
        do { a = ld_relaxed4(src); b = ld_relaxed4(src + 4); } while ((has_sent(a) || has_sent(b)) && ++n < SPIN_MAX);
        spin_check(n);
        const int hh = t >> 2, ch = t & 3, lr = ridx & 255;
        const float hs = ldsf(SB + OFF_M + M_SC + hh * 4);
        sts128(SB + OFF_FIX + t * 16, make_uint4(pack_f16(__uint_as_float(a.x) * hs, __uint_as_float(a.y) * hs), pack_f16(__uint_as_float(a.z) * hs, __uint_as_float(a.w) * hs),
                                                 pack_f16(__uint_as_float(b.x) * hs, __uint_as_float(b.y) * hs), pack_f16(__uint_as_float(b.z) * hs, __uint_as_float(b.w) * hs)));
        sts32(SB + OFF_FIX + 512 + t * 4, SB + (hh < 2 ? OFF_QA + hh * 16384 + (lr >> 6) * 4096 + ch * 1024 + (lr & 63) * 16
                                                        : (hh & 1) * OFF_FE + (hh >> 2) * 16384 + ch * 4096 + lr * 16));
    }
    __syncwarp();
}

__device__ __forceinline__ void ffn_load(const Maps& mp, int c, int i, uint32_t dst, uint32_t bar, bool last_use) {
    if (i < 8) tma_load_h(dst, (i & 1) ? &mp.u : &mp.g, c * 32, (i >> 1) * 256, bar, last_use);
    else tma_load3_h(dst, &mp.d, 0, c * 32, (i - 8) * 4, bar, last_use);
}
__device__ __forceinline__ void side_role(const Maps& mp, const bf16* __restrict__ x0, const bf16* __restrict__ wo, const bf16* __restrict__ w_r) {
    prep_work(x0, &mp.w64, threadIdx.x - 288);
    epi_inputs(0);
    #pragma unroll 1
    for (int L = 0; L < 2; L++) {
        const int t = tid_now() - 288, lane = t & 31, sw = warp_uniform(t >> 5);
        const int c = cta_now(), mt = c >> 4, nt = c & 15;
        named_sync(2, 96);
        if (t == 0) mbar_arrive(B_EPI);
        __syncwarp();
        char* kv = g_kv + (size_t)(nt * 16 + mt) * KV_WIN;
        if (sw < 2) {
            mbar_wait(sw ? B_K0 : B_KV0, L);
            bulk_store(kv + (1 - sw) * 16384, SB + (1 - sw) * 16384, 16384);
            bulk_commit();
            publish(&g_kvc[L][nt * 2][mt], 1 + sw);
        }
        if (sw == 0) {
            named_sync(N_KV1, 64);
            bulk_store(kv + 8 * KV_WIN, SB + OFF_FE, KV_WIN);
            bulk_commit();
            publish(&g_kvc[L][nt * 2 + 1][mt], 3);
        }
        if (sw < 2) {
            #pragma unroll 1
            for (int p = 0; p < 2; p++) {
                named_sync(N_OST + 2 * p + sw, p > sw ? 192 : 160);
                if (p == 1) mbar_arrive_elect(B_QAF);
                ctr_arrive(&g_oc[L][mt * 2 + sw][p][nt]);
            }
        } else {
            if (L == 0) {
                float ws = 0.f;
                #pragma unroll
                for (int i = 0; i < 4; i++) {
                    const uint4 v = reinterpret_cast<const uint4*>(w_r)[i * 32 + lane];
                    ws += ((bf_lo(v.x) + bf_hi(v.x)) + (bf_lo(v.y) + bf_hi(v.y))) + ((bf_lo(v.z) + bf_hi(v.z)) + (bf_lo(v.w) + bf_hi(v.w)));
                }
                const uint32_t* wp = reinterpret_cast<const uint32_t*>(w_r) + (nt >> 1) * 64 + (lane >> 2) * 8 + (lane & 3);
                sts64f(SB + OFF_WR + lane * 8, __uint_as_float(wp[0]), __uint_as_float(wp[4]));
                ws = warp_sum(ws);
                if (lane == 0) { stsf(SB + OFF_M + M_WS, ws); sts64f(SB + OFF_M + M_ORDY, 0.f, 0.f); sts64f(SB + OFF_WR + 256, __uint_as_float(0x3F803F80u), __uint_as_float(0x3F803F80u)); }
                __syncwarp();
            }
            named_sync(N_FW, 64);
            mbar_expect_tx(B_RES, 32768);
            #pragma unroll
            for (int i = 0; i < 4; i++) tma_load_h(SB + OFF_XT + i * 8192, L == 0 ? &mp.x0 : &mp.x, (nt >> 1) * 128 + (i >> 1) * 64, mt * 256 + (nt & 1) * 128 + (i & 1) * 64, B_RES, true);
            if (c < NFC) {
                #pragma unroll 1
                for (int r = 0; r < 4; r++) {
                    __nanosleep(100);
                    if (r > 0) mbar_wait(B_FW, (r + L) & 1);
                    const uint32_t bar = r < 3 ? B_FW : B_FE;
                    mbar_expect_tx(bar, 3 * 16384);
                    #pragma unroll 1
                    for (int b = 0; b < 3; b++) ffn_load(mp, c, 9 - 3 * r + b, SB + OFF_FE + b * 16384, bar, r == 3);
                }
            }
        }
        if (sw == 2) {
            l2_prefetch(reinterpret_cast<const char*>(wo) + (size_t)c * 16384, 16384);
            mbar_wait(B_RES, L);
            const uint32_t lr = lds32(SB + OFF_M + M_RIDX) - (mt * 256 + (nt & 1) * 128);
            if (L == 1 && lr < 128u && lane < 16) {
                const uint4 a = ld_relaxed4(g_x2row + (nt >> 1) * 128 + lane * 8), b = ld_relaxed4(g_x2row + (nt >> 1) * 128 + lane * 8 + 4);
                sts128(SB + OFF_XT + (lane >> 3) * 16384 + lr * 128 + (((lane & 7) ^ (lr & 7)) << 4),
                       make_uint4(__byte_perm(a.x, a.y, 0x7632), __byte_perm(a.z, a.w, 0x7632), __byte_perm(b.x, b.y, 0x7632), __byte_perm(b.z, b.w, 0x7632)));
            }
            if (L == 1) {
                #pragma unroll
                for (int i = 0; i < 4; i++) {
                    const float2 r = ln_coef(ld_relaxed4(&g_sums[mt * 256 + (nt & 1) * 128 + i * 32 + lane]));
                    const float a = i * 32 + lane == lr ? 0.f : r.x;
                    sts64f(SB + OFF_LC + (i * 32 + lane) * 8, a, -a * r.y);
                }
            }
            __syncwarp();
            mbar_arrive_elect(B_RES2);
            named_sync(N_OST + 2, 192);
            l2_prefetch(&g_ypart[L][0][0] + c * (NFC * 8), NFC * 32);
            l2_prefetch(&g_acc[L][c * 16][0], 512);
            l2_prefetch(&g_sums[c * 16], 256);
            l2_prefetch(&g_xrow[L][0][0] + c * 64, 256);
            l2_prefetch(&g_tab[L][0][0][0] + c * 2, 32);
            l2_prefetch(c < 32 ? &g_x2row[c * 32] : c < 40 ? &g_kvc[1][(c - 32) * 4][0] : &g_xc[0][0], c < 40 ? 128 : 64);
            l2_prefetch(&g_fix[c * 24], 96);
            uint32_t ready, n = 0;
            do {
                ready = __ballot_sync(0xffffffffu, ld_acquire(&g_oc[L][mt * 2 + (nt & 1)][1][lane & 15]) != 0);
                fence_async_global();
                if (lane == 0) sts_release(SB + OFF_M + M_ORDY + 4 * L, ready & ready >> 1);
            } while (ready != 0xFFFFFFFFu && ++n < SPIN_MAX);
            spin_check(n);
        }
        if (sw < 2) {
            named_sync(N_XST + sw, 160);
            #pragma unroll
            for (int h = 0; h < 2; h++)
                tma_store(L == 0 ? &mp.x : &mp.out, SB + OFF_XT + h * 16384 + sw * 8192, (nt >> 1) * 128 + h * 64, mt * 256 + (nt & 1) * 128 + sw * 64);
            bulk_commit();
            publish(&g_xc[L][mt]);
        }
        if (L == 0) {
            __syncwarp();
            named_sync(N_RT, 128);
            const RouteOut rt = route_out(lds128(SB + OFF_RT + 128));
            if (t == 0) { sts32(SB + OFF_M + M_RIDX, rt.idx); if (c == 0) g_c0 = 0u; }
            epi_inputs(1);
            const float v = ffn_finish<96>(0, rt, t, SB + OFF_RED, 2);
            if (t < 8) st_relaxed(g_x2row + ypos_col(c * 8 + t), not_sent(v));
            routed_qkv(rt.idx);
        }
    }
}

struct EpiIn { float2 c2[4]; float hs; };
template <int HH>
__device__ __forceinline__ EpiIn qkv_epi_in(int t) {
    EpiIn e;
    #pragma unroll
    for (int jj = 0; jj < 4; jj++) e.c2[jj] = lds64f(SB + OFF_CS + (HH * 32 + jj * 8) * 4 + t * 8);
    e.hs = ldsf(SB + OFF_M + M_SC + HH * 4);
    return e;
}
template <int HH, int NEXT>
__device__ __forceinline__ void qkv_epi_head(const float (&acc0)[96], const float (&acc1)[96], const float (&cf)[4], const float (&nm)[4], EpiIn& in, uint32_t dst, int t) {
    const EpiIn e = in;
    #pragma unroll
    for (int i = 0; i < 4; i++) {
        const float* a = (i >> 1) ? acc1 : acc0;
        const float sc = cf[i] * e.hs;
        uint32_t pk[4];
        #pragma unroll
        for (int jj = 0; jj < 4; jj++)
            pk[jj] = pack_f16(fmaf(nm[i], e.c2[jj].x, a[4 * (4 * HH + jj) + 2 * (i & 1)]) * sc, fmaf(nm[i], e.c2[jj].y, a[4 * (4 * HH + jj) + 2 * (i & 1) + 1]) * sc);
        #pragma unroll
        for (int jj = 0; jj < 4; jj++) if (HH >= 2) pk[jj] = round8(pk[jj]);
        stsm4(dst + (i >> 1) * (HH < 2 ? 4096 : 1024) + (i & 1) * 128, pk[0], pk[1], pk[2], pk[3]);
        if (i == 1 && NEXT >= 0) in = qkv_epi_in<NEXT < 0 ? 0 : NEXT>(t);
    }
}
__device__ __forceinline__ void qkv_patch(int lane, uint32_t mask) {
    const uint4 v = lds128(SB + OFF_FIX + lane * 16);
    const uint32_t dst = lds32(SB + OFF_FIX + 512 + lane * 4);
    __syncwarp();
    asm volatile("{\n.reg .pred q;\nsetp.ne.u32 q, %5, 0;\n@q st.shared.v4.b32 [%0], {%1, %2, %3, %4};\n}"
                 :: "r"(dst), "r"(v.x), "r"(v.y), "r"(v.z), "r"(v.w), "r"((mask >> lane) & 1) : "memory");
}

template <bool INIT>
__device__ __forceinline__ void qkv_step(float (&acc0)[96], float (&acc1)[96], uint32_t st, int wg) {
    const uint64_t da = desc_sw128(SB, 16, 1024) + ((st * Q_STB + wg * 16384) >> 4);
    const uint64_t db = desc_sw128(SB + Q_ABYTES, 8192, 1024) + ((st * Q_STB) >> 4);
    wg_fence();
    if (INIT) { wg_gemm_n192_init(acc0, da, db); wg_gemm_n192_init(acc1, da + (8192 >> 4), db); }
    #pragma unroll
    for (int kk = INIT ? 1 : 0; kk < 4; kk++) {
        wg_gemm_n192(acc0, da + kk * 2, db + kk * 128);
        wg_gemm_n192(acc1, da + (8192 >> 4) + kk * 2, db + kk * 128);
    }
    wg_commit();
}
__device__ __forceinline__ void qkv_phase(int L, int wg) {
    const uint32_t rb = L * 32;
    float acc0[96], acc1[96];
    const bool leader = (tid_now() & 127) == 0;
    mbar_wait(rb + B_QF, 0);
    qkv_step<true>(acc0, acc1, 0, wg);
    uint32_t st = 1, ph = 0;
    #pragma unroll 1
    for (int k = 1; k < 16; k++) {
        mbar_wait(rb + B_QF + 8 * st, ph);
        qkv_step<false>(acc0, acc1, st, wg);
        wg_wait<1>();
        if (leader) mbar_arrive(rb + B_QE + 8 * (st == 0 ? 2 : st - 1));
        if (++st == 3) { st = 0; ph ^= 1; }
    }
    const int tid = tid_now(), lane = tid & 31, w = (tid >> 5) & 3, g = lane >> 2, t = lane & 3;
    mbar_wait(B_EPI, L);
    float cf[4], nm[4];
    #pragma unroll
    for (int i = 0; i < 4; i++) { const float2 r = lds64f(SB + OFF_RC + (wg * 128 + w * 16 + g + (i >> 1) * 64 + (i & 1) * 8) * 8); cf[i] = r.x; nm[i] = -r.y; }
    const int d = (int)lds32(SB + OFF_M + M_RIDX) - (cta_now() >> 4) * 256;
    const bool own = L == 1 && (d >> 7) == wg && ((d >> 4) & 3) == w;
    EpiIn in = qkv_epi_in<2>(t);
    wg_wait<0>();
    named_sync(1, 256);
    const uint32_t dk = SB + wg * 2048 + (lane >> 3) * 4096 + (w * 16 + (lane & 7)) * 16;
    const uint32_t dq = SB + OFF_QA + wg * 8192 + (lane >> 3) * 1024 + (w * 16 + (lane & 7)) * 16;
    qkv_epi_head<2, 4>(acc0, acc1, cf, nm, in, dk, t);
    if (own) qkv_patch(lane, 0x000F00u);
    fence_async_smem();
    __syncwarp();
    mbar_arrive_elect(B_K0);
    qkv_epi_head<4, 0>(acc0, acc1, cf, nm, in, dk + 16384, t);
    if (own) qkv_patch(lane, 0x0F0000u);
    #pragma unroll
    for (int s = 0; s < 3; s++) sts128(SB + s * A_WIN + KV_WIN + tid * 16, make_uint4(0x3C003C00u, 0x3C003C00u, 0x3C003C00u, 0x3C003C00u));
    fence_async_smem();
    __syncwarp();
    mbar_arrive_elect(B_KV0);
    qkv_epi_head<0, 1>(acc0, acc1, cf, nm, in, dq, t);
    qkv_epi_head<1, 3>(acc0, acc1, cf, nm, in, dq + 16384, t);
    qkv_epi_head<3, 5>(acc0, acc1, cf, nm, in, dk + OFF_FE, t);
    qkv_epi_head<5, -1>(acc0, acc1, cf, nm, in, dk + OFF_FE + 16384, t);
    if (own) qkv_patch(lane, 0xF0F0FFu);
    fence_async_smem();
    named_sync(3 + wg, 128);
}

struct Unit {
    uint32_t o[8];
    uint32_t l, bz, sc;
    uint32_t ch[2];
};
template <int H> __device__ __forceinline__ uint32_t hdup(uint32_t v) {
    uint32_t r;
    if (H) asm("{.reg .b16 l, h; mov.b32 {l, h}, %1; mov.b32 %0, {h, h};}" : "=r"(r) : "r"(v));
    else asm("{.reg .b16 l, h; mov.b32 {l, h}, %1; mov.b32 %0, {l, l};}" : "=r"(r) : "r"(v));
    return r;
}
__device__ __forceinline__ uint32_t hmax2(uint32_t a, uint32_t b) { uint32_t r; asm("max.f16x2 %0, %1, %2;" : "=r"(r) : "r"(a), "r"(b)); return r; }
__device__ __forceinline__ uint32_t hadd2(uint32_t a, uint32_t b) { uint32_t r; asm("add.rn.f16x2 %0, %1, %2;" : "=r"(r) : "r"(a), "r"(b)); return r; }
__device__ __forceinline__ uint32_t hsub2(uint32_t a, uint32_t b) { uint32_t r; asm("sub.rn.f16x2 %0, %1, %2;" : "=r"(r) : "r"(a), "r"(b)); return r; }
__device__ __forceinline__ uint32_t hfma2(uint32_t a, uint32_t b, uint32_t c) { uint32_t r; asm("fma.rn.f16x2 %0, %1, %2, %3;" : "=r"(r) : "r"(a), "r"(b), "r"(c)); return r; }
__device__ __forceinline__ uint32_t exp2_h2(uint32_t s, uint32_t bz, uint32_t& ch) {
    uint32_t z, w, d;
    asm("fma.rn.relu.f16x2 %0, %1, %2, %3;" : "=r"(z) : "r"(s), "r"(0x00400040u), "r"(bz));
    asm("lop3.b32 %0, %1, 0x003F003F, %0, 0xC2;" : "+r"(ch) : "r"(z));
    asm("fma.rn.f16x2 %0, %1, %2, %3;" : "=r"(w) : "r"(ch), "r"(0x30A630A6u), "r"(0xACCCACCCu));
    asm("{.reg .b32 n; neg.f16x2 n, %1; fma.rn.relu.f16x2 %0, n, %1, %2;}" : "=r"(d) : "r"(w), "r"(0x00580058u));
    return (z << 4) - d;
}
__device__ __forceinline__ void exp_tile(uint32_t (&p)[32], const uint32_t (&s)[32], Unit& u) {
    #pragma unroll
    for (int j = 0; j < 32; j++) {
        const int i = (j & 1) | (j & 6) << 2 | (j & 24) >> 2;
        p[i] = exp2_h2(s[i], (i & 1) ? hdup<1>(u.bz) : hdup<0>(u.bz), u.ch[i & 1]);
    }
}
struct QOp { uint32_t r[4]; uint64_t d; };
__device__ __forceinline__ void issue_qk(uint32_t (&s)[32], const QOp& q, uint64_t dk) {
    wg_qk_init(s, q.r[0], q.r[1], q.r[2], q.r[3], dk); wg_qk_acc(s, q.d, dk + (8192 >> 4));
    wg_commit();
}
template <bool INIT>
__device__ __forceinline__ void issue_pv(uint32_t (&h)[10], const uint32_t (&p)[32], uint64_t dv) {
    #pragma unroll
    for (int k = 0; k < 8; k++) {
        if (INIT && k == 0) wg_pv_init(h, p[0], p[1], p[2], p[3], dv);
        else wg_pv_acc(h, p[4*k], p[4*k+1], p[4*k+2], p[4*k+3], dv + k * 16);
    }
    wg_commit();
}
__device__ __forceinline__ void unit_init(Unit& u, const uint32_t (&s)[32], uint32_t ok) {
    uint32_t m0 = s[0], m1 = s[1];
    #pragma unroll
    for (int i = 1; i < 16; i++) { m0 = hmax2(m0, s[2 * i]); m1 = hmax2(m1, s[2 * i + 1]); }
    uint32_t m = hmax2(__byte_perm(m0, m1, 0x5410), __byte_perm(m0, m1, 0x7632));
    m = hmax2(m, __shfl_xor_sync(0xffffffffu, m, 1)); m = hmax2(m, __shfl_xor_sync(0xffffffffu, m, 2));
    const uint32_t q = hfma2(m, 0x80048004u, 0x003E003Eu);
    u.bz = hfma2(q, 0x4C004C00u, 0x80008000u);
    u.ch[0] = u.ch[1] = ok & ~hadd2(q, q);
    u.sc = 0u; u.l = 0u;
    #pragma unroll
    for (int i = 0; i < 8; i++) u.o[i] = 0u;
}
template <bool MORE>
__device__ __forceinline__ void unit_flush(Unit& u, const uint32_t (&h)[10]) {
    u.l = hfma2(u.l, u.sc, __byte_perm(h[8], h[9], 0x5410));
    #pragma unroll
    for (int i = 0; i < 8; i++) u.o[i] = hfma2(u.o[i], (i & 1) ? hdup<1>(u.sc) : hdup<0>(u.sc), h[i]);
    if (MORE) {
        const uint32_t ex = u.l & 0x7C007C00u;
        u.sc = 0x84008400u - ex;
        u.bz = hsub2(hadd2(u.bz, 0x04800480u), ex >> 4);
    }
}
__device__ __forceinline__ char* o_block(int wg, int pass) { const int c = cta_now(); return g_o + (size_t)((((c >> 4) * 2 + wg) * 2 + pass) * 16 + (c & 15)) * 8192; }
__device__ __forceinline__ uint32_t unit_finish(Unit& u, float ivs) {
    float lf[2]; h2_unpack(u.l, lf[0], lf[1]);
    #pragma unroll
    for (int i = 0; i < 8; i++) { float x, y; h2_unpack(u.o[i], x, y); const float inv = ivs * rcp(lf[i & 1]); u.o[i] = pack_bf16(x * inv, y * inv); }
    return ((~u.ch[0] & CH_OK) != 0 || (u.l << 16) - 0x40000000u >= 0x3C000000u ? 1u : 0u) | ((~u.ch[1] & CH_OK) != 0 || u.l - 0x40000000u >= 0x3C000000u ? 2u : 0u);
}
__device__ __forceinline__ void unit_store(const Unit& u, char* dst) {
    #pragma unroll
    for (int i = 0; i < 8; i++) *reinterpret_cast<uint32_t*>(dst + (i >> 1) * 1024 + (i & 1) * 128) = u.o[i];
}
__device__ __noinline__ void exact_rows(int L, int pass, int wg, uint32_t bad) {
    const int tid = tid_now() & 127, lane = tid & 31, w = tid >> 5, t = lane & 3;
    const int head = (cta_now() & 15) * 2 + pass;
    const uint32_t scr = SB + OFF_PART + wg * 1024;
    bad = redux_or(bad << (lane & 28));
    if (lane == 0) sts32(scr + w * 4, bad);
    ctr_wait_all(&g_kvc[L][head][lane & 7], 3);
    named_sync(3 + wg, 128);
    const float isc = ldsf(SB + OFF_M + M_ISC + pass * 4), ivs = ldsf(SB + OFF_M + M_IVS + pass * 4);
    const char* kv = g_kv + (size_t)(head * 8 + w * 2) * KV_WIN + t * 4096 + (lane >> 2) * 16;
    #pragma unroll 1
    for (int ww = 0; ww < 4; ww++)
    #pragma unroll 1
    for (uint32_t m = lds32(scr + ww * 4); m; m &= m - 1) {
        const int bit = __ffs(m) - 1;
        const uint32_t ro = (bit & 2) * 2048 + (ww * 16 + (bit & 1) * 8 + (bit >> 2)) * 16;
        const uint4 q = lds128(SB + OFF_QA + pass * 16384 + wg * 8192 + ro + t * 1024);
        float a[9], mx = -INFINITY;
        #pragma unroll
        for (int i = 0; i < 9; i++) a[i] = 0.f;
        #pragma unroll 1
        for (int it = 0; it < 8; it++) {
            uint4 k[8], v[8];
            #pragma unroll
            for (int i = 0; i < 8; i++) {
                const char* p = kv + (it >> 2) * KV_WIN + (it & 3) * 1024 + i * 128;
                k[i] = __ldcg(reinterpret_cast<const uint4*>(p)); v[i] = __ldcg(reinterpret_cast<const uint4*>(p + 16384));
            }
            float s[8], mn = mx;
            #pragma unroll
            for (int i = 0; i < 8; i += 2) {
                float c[4] = {0.f, 0.f, 0.f, 0.f};
                mma_f16(c, k[i].x, k[i + 1].x, k[i].y, k[i + 1].y, q.x, q.y);
                mma_f16(c, k[i].z, k[i + 1].z, k[i].w, k[i + 1].w, q.z, q.w);
                s[i] = c[0]; s[i + 1] = c[2];
                mn = fmaxf(mn, fmaxf(c[0], c[2]));
            }
            const float al = ex2((mx - mn) * isc);
            mx = mn;
            #pragma unroll
            for (int i = 0; i < 9; i++) a[i] *= al;
            #pragma unroll
            for (int i = 0; i < 8; i++) {
                const float p = ex2((s[i] - mx) * isc);
                const uint32_t u[4] = {v[i].x, v[i].y, v[i].z, v[i].w};
                a[8] += p;
                #pragma unroll
                for (int e = 0; e < 4; e++) { float x, y; h2_unpack(u[e], x, y); a[2 * e] = fmaf(p, x, a[2 * e]); a[2 * e + 1] = fmaf(p, y, a[2 * e + 1]); }
            }
        }
        #pragma unroll 1
        for (int o = 4; o < 32; o <<= 1) {
            const float mn = fmaxf(mx, __shfl_xor_sync(0xffffffffu, mx, o)), al = ex2((mx - mn) * isc);
            mx = mn;
            #pragma unroll
            for (int i = 0; i < 9; i++) { a[i] *= al; a[i] += __shfl_xor_sync(0xffffffffu, a[i], o); }
        }
        named_sync(3 + wg, 128);
        const uint32_t mine = scr + 16 + w * 144;
        sts128(mine + t * 32, make_uint4(__float_as_uint(a[0]), __float_as_uint(a[1]), __float_as_uint(a[2]), __float_as_uint(a[3])));
        sts128(mine + t * 32 + 16, make_uint4(__float_as_uint(a[4]), __float_as_uint(a[5]), __float_as_uint(a[6]), __float_as_uint(a[7])));
        sts64f(mine + 128, a[8], mx);
        named_sync(3 + wg, 128);
        float o = 0.f, l = 0.f;
        mx = -INFINITY;
        #pragma unroll 1
        for (int i = 0; i < 4; i++) {
            const float2 e = lds64f(scr + 16 + i * 144 + 128);
            const float mn = fmaxf(mx, e.y), al = ex2((mx - mn) * isc), be = ex2((e.y - mn) * isc);
            mx = mn;
            o = fmaf(o, al, be * ldsf(scr + 16 + i * 144 + lane * 4)); l = fmaf(l, al, be * e.x);
        }
        if (w == 0) *reinterpret_cast<unsigned short*>(o_block(wg, pass) + ro + (lane >> 3) * 1024 + (lane & 7) * 2) = (unsigned short)pack_bf16(o * ivs * rcp(l), 0.f);
    }
}

__device__ __forceinline__ void attention_phase(int L, int wg) {
    const uint32_t rb = L * 32;
    constexpr uint64_t dk0 = desc_plain(SB, 4096, 128), dv0 = desc_plain(SB + 16384, 128, 4096);
    constexpr int T1 = 2048 >> 4;
    uint32_t st = 0, ph = 0;
    #pragma unroll 1
    for (int pass = 0; pass < 2; pass++) {
        QOp dqa, dqc;
        dqa.d = desc_plain(SB + OFF_QA + 2048, 1024, 128) + (pass * 4 + wg * 2) * (4096 >> 4); dqc.d = dqa.d + (4096 >> 4);
        {
            const int tid = tid_now();
            const uint32_t a0 = SB + OFF_QA + (pass * 4 + wg * 2) * 4096 + ((tid >> 4) & 1) * 1024 + (((tid >> 5) & 3) * 16 + (tid & 15)) * 16;
            ldsm4(dqa.r[0], dqa.r[1], dqa.r[2], dqa.r[3], a0); ldsm4(dqc.r[0], dqc.r[1], dqc.r[2], dqc.r[3], a0 + 4096);
        }
        Unit a, c;
        st = warp_uniform(st); ph = warp_uniform(ph);
        uint32_t SA[32], SC[32], PA[32], PC[32], ha[10], hc[10], bad;
        #pragma unroll
        for (int i = 0; i < 10; i++) hc[i] = 0u;
        #pragma unroll
        for (int i = 0; i < 32; i++) PC[i] = 0u;
        const uint32_t ok = lds32(SB + OFF_M + M_OK + pass * 4);
        mbar_wait(rb + B_AF + 8 * st, ph);
        wg_fence();
        issue_qk(SA, dqa, dk0 + st * (A_WIN >> 4));
        issue_qk(SC, dqc, dk0 + st * (A_WIN >> 4));
        wg_wait<1>();
        unit_init(a, SA, ok);
        exp_tile(PA, SA, a);
        wg_wait<0>();
        unit_init(c, SC, ok);
        uint32_t eb = 0;
        #pragma unroll 1
        for (int s = 0;; s++) {
            const uint64_t dkb = dk0 + st * (A_WIN >> 4), dvb = dv0 + st * (A_WIN >> 4);
            if (__builtin_expect(s == 8 * gridDim.y, 0)) {
                wg_wait<0>();
                bad = 0;
                #pragma unroll
                for (int i = 0; i < 32; i++) bad |= PC[i];
                break;
            }
            wg_fence();
            issue_pv<true>(ha, PA, dvb); issue_qk(SA, dqa, dkb + T1);
            wg_wait<2>();
            if (s > 0) { mbar_arrive_elect(eb); unit_flush<true>(c, hc); }
            exp_tile(PC, SC, c);
            wg_fence();
            issue_pv<true>(hc, PC, dvb); issue_qk(SC, dqc, dkb + T1);
            wg_wait<2>();
            exp_tile(PA, SA, a);
            eb = rb + B_AE + 8 * st;
            if (++st == 3) { st = 0; ph ^= 1; }
            if (s == 7) {
                wg_fence(); issue_pv<false>(ha, PA, dvb + T1);
                wg_wait<1>();
                exp_tile(PC, SC, c);
                wg_fence(); issue_pv<false>(hc, PC, dvb + T1);
                wg_wait<1>();
                const int tid = tid_now();
                const float ivs = ldsf(SB + OFF_M + M_IVS + pass * 4);
                char* dst = o_block(wg, pass) + (tid & 96) * 8 + (tid & 31) * 4;
                unit_flush<false>(a, ha);
                bad = unit_finish(a, ivs);
                wg_wait<0>();
                mbar_arrive_elect(eb);
                unit_store(a, dst);
                unit_flush<false>(c, hc);
                bad |= unit_finish(c, ivs) << 2;
                unit_store(c, dst + 4096);
                break;
            }
            const uint64_t dkn = dk0 + st * (A_WIN >> 4);
            mbar_wait(rb + B_AF + 8 * st, ph);
            wg_fence();
            issue_pv<false>(ha, PA, dvb + T1); issue_qk(SA, dqa, dkn);
            wg_wait<2>();
            exp_tile(PC, SC, c);
            wg_fence();
            issue_pv<false>(hc, PC, dvb + T1); issue_qk(SC, dqc, dkn);
            wg_wait<2>();
            unit_flush<true>(a, ha);
            exp_tile(PA, SA, a);
        }
        if (__builtin_expect(named_any(bad != 0, 3 + wg), 0)) {
            exact_rows(L, pass, wg, bad);
        }
        named_arrive(N_OST + 2 * pass + wg, pass > wg ? 192 : 160);
    }
}

template <bool INIT>
__device__ __forceinline__ void oproj_step(float (&acc)[64], uint32_t s, int wg) {
    const uint64_t da = desc_plain(SB, 1024, 128) + ((o_stage(s) + wg * 4096) >> 4);
    const uint64_t db = desc_sw128(SB + 16384, 8192, 1024) + (o_stage(s) >> 4);
    wg_fence();
    if (INIT) wg_gemm_n128_init(acc, da, db);
    #pragma unroll
    for (int kk = INIT ? 1 : 0; kk < 4; kk++) wg_gemm_n128(acc, da + (kk >> 1) * 512 + (kk & 1) * 128, db + kk * 128);
    wg_commit();
}
__device__ __forceinline__ void oproj_phase(int L, int wg, bf16* __restrict__ out) {
    const int c = cta_now(), tid = tid_now(), lane = tid & 31, W = tid >> 5, g = lane >> 2, t = lane & 3;
    const int row0 = (c >> 4) * 256 + (c & 1) * 128, col0 = ((c & 15) >> 1) * 128;
    float acc[64];
    mbar_wait(B_OF, 0);
    oproj_step<true>(acc, 0, wg);
    const uint32_t xa = SB + OFF_XT + (W * 16 + ((lane >> 3) & 1) * 8 + (lane & 7)) * 128, xs = (lane >> 4) ^ (lane & 7);
    mbar_wait(B_RES2, L);
    const float2 c0 = lds64f(SB + OFF_LC + (W * 16 + g) * 8), c1 = lds64f(SB + OFF_LC + (W * 16 + g + 8) * 8);
    #pragma unroll 1
    for (int k = 1; k < 16; k++) {
        mbar_wait(B_OF + 8 * (k & 3), (k >> 2) & 1);
        oproj_step<false>(acc, k & 3, wg);
        wg_wait<1>();
        if ((tid & 127) == 0) mbar_arrive(B_OE + 8 * ((k - 1) & 3));
        if (L == 1 && (k & 1)) {
            const uint32_t a = xa + (k & 8) * 2048 + ((xs ^ (k & 6)) << 4);
            uint32_t v0, v1, v2, v3;
            ldsm4(v0, v1, v2, v3, a);
            stsm4(a, add_ln2(v0, c0.x, c0.y), add_ln2(v1, c1.x, c1.y), add_ln2(v2, c0.x, c0.y), add_ln2(v3, c1.x, c1.y));
        }
    }
    uint32_t x[32];
    const uint32_t wra = SB + OFF_WR + (g == 4 ? t * 8 : 256), wrs = g == 4 ? 32 : 0;
    float2 wb[8];
    #pragma unroll
    for (int ks = 0; ks < 8; ks++) {
        ldsm4(x[4*ks], x[4*ks+1], x[4*ks+2], x[4*ks+3], xa + (ks >> 2) * 16384 + ((xs ^ ((ks & 3) * 2)) << 4));
        wb[ks] = lds64f(wra + ks * wrs);
    }
    wg_wait<0>();
    if ((tid & 127) == 0) mbar_arrive(B_OE + 24);
    {
        float sd[4] = {0.f, 0.f, 0.f, 0.f}, z0[4] = {0.f, 0.f, 0.f, 0.f}, z1[4] = {0.f, 0.f, 0.f, 0.f};
        #pragma unroll
        for (int ks = 0; ks < 8; ks++) {
            #pragma unroll
            for (int i = 0; i < 4; i++) x[4*ks + i] = badd2(x[4*ks + i], pack_bf16(acc[8*ks + 2*i], acc[8*ks + 2*i + 1]));
            mma_bf16(sd, x[4*ks], x[4*ks+1], x[4*ks+2], x[4*ks+3], __float_as_uint(wb[ks].x), __float_as_uint(wb[ks].y));
            mma_bf16(z0, x[4*ks], x[4*ks+1], x[4*ks+2], x[4*ks+3], x[4*ks], x[4*ks+2]);
            mma_bf16(z1, x[4*ks], x[4*ks+1], x[4*ks+2], x[4*ks+3], x[4*ks+1], x[4*ks+3]);
        }
        const float s0 = __shfl_sync(0xffffffffu, (g & 1) ? z0[1] : z0[0], 4 * g + (g >> 1));
        const float s1 = __shfl_sync(0xffffffffu, (g & 1) ? z1[3] : z1[2], 4 * g + (g >> 1));
        double* p = &g_acc[L][row0 + W * 16 + g][t];
        asm volatile("red.relaxed.gpu.global.add.f64 [%0], %1;" :: "l"(p), "d"((double)sel4(t, sd[0], s0, sd[0], 1.f)) : "memory");
        asm volatile("red.relaxed.gpu.global.add.f64 [%0], %1;" :: "l"(p + 32), "d"((double)sel4(t, sd[2], s1, sd[2], 1.f)) : "memory");
    }
    if (L == 0) {
        #pragma unroll
        for (int ks = 0; ks < 8; ks++) stsm4(xa + (ks >> 2) * 16384 + ((xs ^ ((ks & 3) * 2)) << 4), x[4*ks], x[4*ks+1], x[4*ks+2], x[4*ks+3]);
        fence_async_smem();
        named_arrive(N_XST + wg, 160);
    }
    const bool ffn = c < NFC;
    uint4 fa[32], fd[16];
    const uint32_t ga = SB + W * 2048 + ((lane >> 4) * 8 + (lane & 7)) * 64 + ((((lane >> 3) & 1) ^ ((lane >> 1) & 3)) << 4);
    if (ffn) mbar_wait(B_FE, L);
    #pragma unroll
    for (int i = 0; i < 12; i++) ldsm4t(fa[i].x, fa[i].y, fa[i].z, fa[i].w, (ga ^ ((i & 1) * 32)) + gu_piece(i >> 2) + (i & 2) * 512);
    float2 r0, r1;
    {
        const float ws = ldsf(SB + OFF_M + M_WS);
        const uint32_t row = row0 + W * 16 + g;
        const bool odd = t & 1, up = t & 2;
        const uint32_t me = row + (odd ? 8 : 0);
        uint4 v;
        uint32_t n = 0;
        do { v = ld_relaxed4(&g_acc[L][me][t & 2]); } while (__any_sync(0xffffffffu, up && v.w != 0x40200000u) && ++n < SPIN_MAX);
        spin_check(n);
        const float f0 = (float)__hiloint2double(v.y, v.x), f1 = (float)__hiloint2double(v.w, v.z);
        const float e0 = __shfl_xor_sync(0xffffffffu, f0, 2), e1 = __shfl_xor_sync(0xffffffffu, f1, 2);
        const float a[3] = {up ? e0 : f0, up ? e1 : f1, up ? f0 : e0};
        const uint4 tot = make_uint4(not_sent(a[0]), not_sent(a[1]), 0u, 0u);
        st_relaxed4_if(&g_sums[me], tot, L == 0 && col0 == 0 && t < 2);
        const float2 r = ln_coef(tot), ro = make_float2(__shfl_xor_sync(0xffffffffu, r.x, 1), __shfl_xor_sync(0xffffffffu, r.y, 1));
        r0 = odd ? ro : r; r1 = odd ? r : ro;
        const uint32_t k = min(order_bits(r.x * fmaf(-r.y, ws, a[2])), SENT - 1);
        const uint32_t m = redux_max(k), mrow = redux_min(k == m ? me : 0x7FFFFFFFu);
        if (me == mrow) sts128(SB + OFF_RT + W * 16, make_uint4(k, me, not_sent(r.y), not_sent(r.x)));
    }
    named_sync(1, 256);
    {
        const uint4 e = lds128(SB + OFF_RT + (lane & 7) * 16);
        const uint32_t m = redux_max(e.x), row = redux_min(e.x == m ? e.y : 0x7FFFFFFFu);
        const int lr = row - row0;
        st_relaxed4_if(&g_tab[L][(c & 15) >> 1][row0 >> 7][(lane >> 3) & 1], e, W == ((lr >> 4) ^ 1) && e.y == row && lane < 16);
        if ((lr >> 4) == W) {
            const bool hi = lr & 8;
            uint32_t* dst = &g_xrow[L][row0 >> 7][(col0 & 128) * 2 + (col0 >> 8) * 16 + t * 4];
            #pragma unroll
            for (int i = 0; i < 4; i++)
                st_relaxed4_if(dst + i * 64, make_uint4(min(hi ? x[8*i+1] : x[8*i], SENT - 1), min(hi ? x[8*i+3] : x[8*i+2], SENT - 1),
                               min(hi ? x[8*i+5] : x[8*i+4], SENT - 1), min(hi ? x[8*i+7] : x[8*i+6], SENT - 1)), g == (lr & 7));
        }
        __syncwarp();
    }
    if (L == 1) {
        const float b0 = -r0.x * r0.y, b1 = -r1.x * r1.y;
        #pragma unroll
        for (int ks = 0; ks < 8; ks++)
            stsm4(xa + (ks >> 2) * 16384 + ((xs ^ ((ks & 3) * 2)) << 4), add_ln2(x[4*ks], r0.x, b0), add_ln2(x[4*ks+1], r1.x, b1),
                  add_ln2(x[4*ks+2], r0.x, b0), add_ln2(x[4*ks+3], r1.x, b1));
        fence_async_smem();
        named_arrive(N_XST + wg, 160);
    }
    RouteOut rt;
    {
        const uint4* tp = &g_tab[L][(c & 15) >> 1][lane & 15][0];
        uint4 e = ld_relaxed4(tp);
        if (ffn) mbar_wait(B_FL, L);
        #pragma unroll
        for (int i = 12; i < 32; i++) ldsm4t(fa[i].x, fa[i].y, fa[i].z, fa[i].w, (ga ^ ((i & 1) * 32)) + gu_piece(i >> 2) + (i & 2) * 512);
        if (L == 0) named_arrive(N_GD, 288);
        uint32_t n = 0;
        while (has_sent(e) && ++n < SPIN_MAX) e = ld_relaxed4(tp);
        spin_check(n);
        __syncwarp();
        e = warp_best(e);
        rt = route_out(e);
        if (W == 7 && L == 0) { sts128(SB + OFF_RT + 128, e); named_arrive(N_RT, 128); }
    }
    uint2 xrow;
    {
        const uint32_t* xp = &g_xrow[L][rt.idx >> 7][W * 64 + (g >> 1) * 16 + t * 4 + (g & 1) * 2];
        xrow = ld_relaxed2(xp);
        if (ffn) mbar_wait(B_FD, L);
        const uint32_t wa = SB + OFF_FD + W * 8192 + ((lane >> 4) * 8 + (lane & 7)) * 128 + ((((lane >> 3) & 1) ^ (lane & 7)) << 4);
        #pragma unroll
        for (int i = 0; i < 16; i++) ldsm4t(fd[i].x, fd[i].y, fd[i].z, fd[i].w, (wa ^ (((i >> 1) & 3) * 32)) + (i >> 3) * 4096 + (i & 1) * 2048);
        if (L == 0) named_arrive(N_DD, 288);
        uint32_t n = 0;
        while ((xrow.x == SENT || xrow.y == SENT) && ++n < SPIN_MAX) xrow = ld_relaxed2(xp);
        spin_check(n);
        __syncwarp();
    }
    {
        const float nb = -rt.mean * rt.rstd;
        const uint32_t n0 = pack_bf16(fmaf(bf_lo(xrow.x), rt.rstd, nb), fmaf(bf_hi(xrow.x), rt.rstd, nb));
        const uint32_t n1 = pack_bf16(fmaf(bf_lo(xrow.y), rt.rstd, nb), fmaf(bf_hi(xrow.y), rt.rstd, nb));
        float gu[4][4];
        #pragma unroll
        for (int i = 0; i < 4; i++) { gu[i][0] = 0.f; gu[i][1] = 0.f; gu[i][2] = 0.f; gu[i][3] = 0.f; }
        #pragma unroll
        for (int ks = 0; ks < 8; ks++) {
            const uint32_t b0 = __shfl_sync(0xffffffffu, n0, 4 * ks + t), b1 = __shfl_sync(0xffffffffu, n1, 4 * ks + t);
            #pragma unroll
            for (int i = 0; i < 4; i++) {
                const uint4& a = fa[(ks >> 1) * 8 + (i >> 1) * 4 + (ks & 1) * 2 + (i & 1)];
                mma_bf16(gu[i], a.x, a.y, a.z, a.w, b0, b1);
            }
        }
        stsf(SB + OFF_PART + (W * 64 + t * 16 + g) * 4, sel4(t, gu[0][0], gu[1][0], gu[2][0], gu[3][0]));
        stsf(SB + OFF_PART + (W * 64 + t * 16 + g + 8) * 4, sel4(t, gu[0][2], gu[1][2], gu[2][2], gu[3][2]));
    }
    named_sync(1, 256);
    {
        float gp[8], up[8];
        #pragma unroll
        for (int i = 0; i < 8; i++) gp[i] = ldsf(SB + OFF_PART + (i * 64 + lane) * 4);
        #pragma unroll
        for (int i = 0; i < 8; i++) up[i] = ldsf(SB + OFF_PART + (i * 64 + 32 + lane) * 4);
        const float gv = bf_round(((gp[0] + gp[1]) + (gp[2] + gp[3])) + ((gp[4] + gp[5]) + (gp[6] + gp[7])));
        const float uv = bf_round(((up[0] + up[1]) + (up[2] + up[3])) + ((up[4] + up[5]) + (up[6] + up[7])));
        const float hv = bf_round(gv * rcp(1.f + ex2(gv * -1.4426950408889634f))) * uv;
        const uint32_t hp = pack_bf16(hv, __shfl_down_sync(0xffffffffu, hv, 1));
        uint32_t hb[4];
        #pragma unroll
        for (int i = 0; i < 4; i++) hb[i] = __shfl_sync(0xffffffffu, hp, 8 * i + 2 * t);
        float y[8][4];
        #pragma unroll
        for (int mb = 0; mb < 8; mb++) {
            y[mb][0] = 0.f; y[mb][1] = 0.f; y[mb][2] = 0.f; y[mb][3] = 0.f;
            #pragma unroll
            for (int ks = 0; ks < 2; ks++) mma_bf16(y[mb], fd[2*mb + ks].x, fd[2*mb + ks].y, fd[2*mb + ks].z, fd[2*mb + ks].w, hb[2 * ks], hb[2 * ks + 1]);
        }
        st_relaxed4_if(&g_ypart[L][min(c, NFC - 1)][tid * 4], make_uint4(not_sent(sel4(t, y[0][0], y[2][0], y[4][0], y[6][0])), not_sent(sel4(t, y[0][2], y[2][2], y[4][2], y[6][2])),
                       not_sent(sel4(t, y[1][0], y[3][0], y[5][0], y[7][0])), not_sent(sel4(t, y[1][2], y[3][2], y[5][2], y[7][2]))), ffn);
    }
    if (L == 1) {
        if (W == 7) ctr_wait(&g_xc[1][rt.idx >> 8], 32);
        unsigned short* dst = reinterpret_cast<unsigned short*>(out) + (size_t)rt.idx * D_ + ypos_col(c * 8 + (tid & 7));
        asm volatile("" : "+l"(dst));
        const float v = ffn_finish<256>(1, rt, tid, SB + OFF_FE, 1);
        if (tid < 8) asm volatile("st.global.u16 [%0], %1;" :: "l"(dst), "h"((unsigned short)(__float_as_uint(v) >> 16)) : "memory");
    }
}

constexpr int KW1 = 4, FW0 = 11;
constexpr int RK0 = 7;
static_assert(FW0 >= 8 && KW1 >= 3 && KW1 < 7, "buffer reuse");
__device__ __forceinline__ void qkv_fill(const CUtensorMap* tx, const CUtensorMap* tw, uint32_t bar, int st, int k) {
    const uint32_t sa = SB + st * Q_STB;
    mbar_expect_tx(bar, Q_STB);
    tma_load(sa, tx, k * 64, (blockIdx.x >> 4) * 256, bar);
    tma_load3(sa + Q_ABYTES, tw, (blockIdx.x & 15) * 64, k * 64, 0, bar);
}
__device__ __forceinline__ void oproj_fill(const Maps& mp, const char* osrc, int s, int par, int pair, int parts) {
    const uint32_t fb = B_OF + 8 * s, sa = SB + o_stage(s);
    if (parts & 1) { mbar_expect_tx(fb, 32768); bulk_load(sa, osrc + (par * 16 + pair) * 8192, 16384, fb); }
    if (parts & 2) tma_load5(sa + 16384, &mp.wo, 0, 0, par, pair, blockIdx.x & 14, fb);
}
__device__ __forceinline__ void producer_role(const Maps& mp) {
    const int c = blockIdx.x, mt = c >> 4, nt = c & 15, lane = threadIdx.x & 31;
    #pragma unroll 1
    for (int i = 2; i < 12; i++) tm_prefetch(&mp.xa0 + i);
    #pragma unroll 1
    for (int L = 0; L < 2; L++) {
        const uint32_t rb = L * 32;
        uint32_t st = 0, ph = L;
        #pragma unroll 1
        for (int k = L == 0 ? 3 : 0; k < 16; k++) {
            if (k == 0) { ctr_wait_all(&g_xc[0][mt], 32); fence_async_global(); named_sync(N_GD, 288); }
            if (k == 1) named_sync(N_DD, 288);
            mbar_wait(rb + B_QE + 8 * st, ph);
            qkv_fill(L == 0 ? &mp.xa0 : &mp.xa, &mp.wqkv, rb + B_QF + 8 * st, st, k);
            if (L == 1 && k >= RK0 && k < RK0 + 4) {
                if (k == RK0) mbar_expect_tx(B_SW, 4 * 12288);
                tma_load(SB + OFF_SIDE + (k - RK0) * 12288, &mp.r, c * 24, (k - RK0) * 256, B_SW);
            }
            if (++st == 3) { st = 0; ph ^= 1; }
        }
        mbar_wait(B_KV0, L);
        mbar_arrive_elect(rb + B_AF);
        {
            const int win = nt * 16 + ((mt + 1) & 7);
            mbar_expect_tx(rb + B_AF + 8, KV_WIN);
            #pragma unroll 1
            for (int h = 0; h < 2; h++) {
                ctr_wait_all(&g_kvc[L][0][0] + win, 2 + h);
                fence_async_global();
                bulk_load(SB + A_WIN + h * 16384, g_kv + (size_t)win * KV_WIN + h * 16384, 16384, rb + B_AF + 8);
            }
        }
        st = 2; ph = 1;
        #pragma unroll 1
        for (int w = 2; w < 16; w++) {
            const int win = nt * 16 + (w & 8) + ((mt + w) & 7);
            if (w <= 3 || w == 8) {
                ctr_wait_all(&g_kvc[L][0][0] + (w < 3 ? win : (win & ~7) + (lane & 7)), 3);
                fence_async_global();
            }
            mbar_wait(rb + B_AE + 8 * st, ph);
            mbar_expect_tx(rb + B_AF + 8 * st, KV_WIN);
            bulk_load(SB + st * A_WIN, g_kv + (size_t)win * KV_WIN, KV_WIN, rb + B_AF + 8 * st);
            if (w == KW1 || w == FW0) named_arrive(w == FW0 ? N_FW : N_KV1, 64);
            if (++st == 3) { st = 0; ph ^= 1; }
        }
        ctr_wait_all(&g_oc[L][mt * 2 + (nt & 1)][0][lane & 15], 1);
        fence_async_global();
        const char* osrc = g_o + (size_t)(mt * 2 + (nt & 1)) * 32 * 8192;
        oproj_fill(mp, osrc, 3, 0, 6, 1);
        #pragma unroll
        for (int k = 0; k < 4; k++) {
            mbar_wait(k < 2 ? rb + B_AE + 8 + 8 * k : k == 2 ? rb + B_AE : B_QAF, k < 2 ? 0 : k == 2 ? 1 : L);
            oproj_fill(mp, osrc, k, 0, 2 * k, k == 3 ? 2 : 3);
        }
        uint32_t ready = 0xFFFFu;
        #pragma unroll 1
        for (int k4 = 1; k4 < 4; k4++) {
            #pragma unroll
            for (int s = 0; s < 4; s++) {
                const int p = k4 * 8 + 2 * s;
                if (!((ready >> p) & 1)) {
                    ready = smem_wait_any(SB + OFF_M + M_ORDY + 4 * L, 1u << p);
                    fence_async_global();
                }
                mbar_wait(B_OE + 8 * s, (k4 - 1) & 1);
                oproj_fill(mp, osrc, s, p >> 4, p & 15, 3);
            }
        }
        if (c < NFC) {
            mbar_expect_tx(B_FL, 5 * 16384);
            mbar_expect_tx(B_FD, 4 * 16384);
            #pragma unroll 1
            for (int i = 3; i < 12; i++) {
                mbar_wait(B_OE + (i < 5 ? 0 : i == 5 ? 8 : i < 9 ? 16 : 24), 1);
                if (i == 10) mbar_wait(B_FL, L);
                ffn_load(mp, c, i, SB + (i < 8 ? gu_piece(i) : OFF_FD + (i - 8) * 16384), i < 8 ? B_FL : B_FD, true);
            }
        }
    }
}

__global__ void __launch_bounds__(384, 1) k_all(const bf16* __restrict__ x0, const bf16* __restrict__ wo, const bf16* __restrict__ w_r, bf16* __restrict__ out,
                                                const __grid_constant__ Maps mp) {
    extern __shared__ __align__(1024) char smem[];
    if (smem_u32(smem) != SB) __trap();
    const int warp = warp_uniform(threadIdx.x >> 5), wg = warp >> 2;
    {
        const int grp = warp >= 8 ? warp - 8 : warp + 4;
        #pragma unroll
        for (int i = 0; i < 4; i++) mbar_init(BB + grp * 32 + i * 8, grp < 7 ? 1 : grp < 10 ? 2 : 8);
        fence_mbar_init();
    }
    if (warp == 8) {
        #pragma unroll 1
        for (int s = 0; s < 3; s++) qkv_fill(&mp.xa0, &mp.wqkv, B_QF + 8 * s, s, s);
    }
    __syncthreads();
    if (wg == 2) {
        reg_dec<40>();
        if (warp == 8) producer_role(mp);
        else side_role(mp, x0, wo, w_r);
        if (gridDim.y == 2) {
            uint32_t v = threadIdx.x;
            #pragma unroll
            for (int i = 0; i < 1500; i++) asm volatile("fma.rn.f16x2 %0, %0, %0, %0;" : "+r"(v));
            sts32(SB, v);
        }
    } else {
        reg_inc<232>();
        #pragma unroll 1
        for (int L = 0; L < 2; L++) {
            qkv_phase(L, wg);
            attention_phase(L, wg);
            oproj_phase(L, wg, out);
        }
    }
}

typedef CUresult (*EncodeFn)(CUtensorMap*, CUtensorMapDataType, cuuint32_t, void*, const cuuint64_t*, const cuuint64_t*, const cuuint32_t*,
                             const cuuint32_t*, CUtensorMapInterleave, CUtensorMapSwizzle, CUtensorMapL2promotion, CUtensorMapFloatOOBfill);

void make_map(EncodeFn enc, CUtensorMap* tm, const void* ptr, int rank, const cuuint64_t* dims, const cuuint64_t* strides, const cuuint32_t* box, CUtensorMapSwizzle sw) {
    const cuuint32_t es[5] = {1, 1, 1, 1, 1};
    enc(tm, CU_TENSOR_MAP_DATA_TYPE_BFLOAT16, rank, const_cast<void*>(ptr), dims, strides, box, es, CU_TENSOR_MAP_INTERLEAVE_NONE, sw,
        box[0] == 64 ? CU_TENSOR_MAP_L2_PROMOTION_L2_128B : CU_TENSOR_MAP_L2_PROMOTION_NONE, CU_TENSOR_MAP_FLOAT_OOB_FILL_NONE);
}
void make_map2(EncodeFn enc, CUtensorMap* tm, const void* ptr, uint64_t cols, uint64_t rows, uint32_t bc, uint32_t br, CUtensorMapSwizzle sw) {
    const cuuint64_t dims[2] = {cols, rows}, strides[1] = {cols * 2};
    const cuuint32_t box[2] = {bc, br};
    make_map(enc, tm, ptr, 2, dims, strides, box, sw);
}

}

extern "C" void kernel_launch(void* const* d_in, const int* in_sizes, int n_in, void* d_out, int out_size) {
    const bf16* x0 = (const bf16*)d_in[0];
    const bf16* wqkv = (const bf16*)d_in[1];
    const bf16* wo = (const bf16*)d_in[2];
    const bf16* w_r = (const bf16*)d_in[4];
    const bf16* w_gate = (const bf16*)d_in[5];
    const bf16* w_up = (const bf16*)d_in[6];
    const bf16* w_down = (const bf16*)d_in[7];

    EncodeFn enc = nullptr;
    cudaDriverEntryPointQueryResult qr;
    cudaGetDriverEntryPoint("cuTensorMapEncodeTiled", (void**)&enc, cudaEnableDefault, &qr);
    void* p_x;
    cudaGetSymbolAddress(&p_x, g_x);
    Maps mp;
    const CUtensorMapSwizzle S128 = CU_TENSOR_MAP_SWIZZLE_128B;
    make_map2(enc, &mp.x0, x0, D_, S_, 64, 64, S128);
    make_map2(enc, &mp.x, p_x, D_, S_, 64, 64, S128);
    make_map2(enc, &mp.out, d_out, D_, S_, 64, 64, S128);
    make_map2(enc, &mp.xa0, x0, D_, S_, 64, 256, S128);
    make_map2(enc, &mp.xa, p_x, D_, S_, 64, 256, S128);
    make_map2(enc, &mp.w64, wqkv, 3 * D_, D_, 64, 64, S128);
    {
        const cuuint64_t dims[3] = {D_, D_, 3}, strides[2] = {3 * D_ * 2, D_ * 2};
        const cuuint32_t box[3] = {64, 64, 3};
        make_map(enc, &mp.wqkv, wqkv, 3, dims, strides, box, S128);
    }
    make_map2(enc, &mp.r, wqkv, 3 * D_, D_, 24, 256, CU_TENSOR_MAP_SWIZZLE_NONE);
    make_map2(enc, &mp.g, w_gate, FF, D_, 32, 256, CU_TENSOR_MAP_SWIZZLE_64B);
    make_map2(enc, &mp.u, w_up, FF, D_, 32, 256, CU_TENSOR_MAP_SWIZZLE_64B);
    {
        const cuuint64_t dims[5] = {64, 32, 2, 16, 16}, strides[4] = {D_ * 2, 32 * D_ * 2, 64 * D_ * 2, 128};
        const cuuint32_t box[5] = {64, 32, 1, 2, 2};
        make_map(enc, &mp.wo, wo, 5, dims, strides, box, S128);
    }
    {
        const cuuint64_t dims[3] = {64, FF, 16}, strides[2] = {D_ * 2, 128};
        const cuuint32_t box[3] = {64, 32, 4};
        make_map(enc, &mp.d, w_down, 3, dims, strides, box, S128);
    }
    cudaFuncSetAttribute(k_all, cudaFuncAttributeMaxDynamicSharedMemorySize, K_SMEM);
    k_all<<<128, 384, K_SMEM, cudaStreamPerThread>>>(x0, wo, w_r, (bf16*)d_out, mp);
}
```

```cpp
#include <cuda_runtime.h>
#include <cuda_bf16.h>
#include <cuda_fp16.h>
#include <cuda.h>
#include <cudaTypedefs.h>
#include <stdint.h>

namespace {

typedef __nv_bfloat16 bf16;

constexpr int S_ = 2048, D_ = 1024, NH = 32, FF = 3584, NFC = FF / 32;
constexpr float LN_EPS = 1e-5f;
constexpr float QSCALE = 0.17677669529663687f * 1.4426950408889634f;
constexpr uint32_t SENT = 0xFFFFFFFFu;

constexpr int KV_WIN = 32768;
__device__ __align__(1024) char g_kv[NH * 8 * KV_WIN];
__device__ __align__(1024) char g_o[32 * 2 * 16 * 4096];
__device__ __align__(1024) bf16 g_x[S_ * D_];
__device__ float g_csum[8 * 3 * D_];
__device__ float g_wsq[8 * 96];
__device__ float2 g_rs0[S_];
__device__ __align__(128) double g_acc[2][S_][4];
__device__ __align__(128) uint4 g_sums[S_];
__device__ __align__(128) uint32_t g_ypart[2][NFC][D_];
__device__ __align__(128) uint4 g_tab[2][8][16][2];
__device__ __align__(128) uint32_t g_xrow[2][16][D_ / 2];
__device__ __align__(128) uint32_t g_x2row[D_];
__device__ __align__(128) uint32_t g_fix[3 * D_];
__device__ uint32_t g_c0;
__device__ __align__(128) uint32_t g_kvc[2][NH][8];
__device__ __align__(128) uint32_t g_oc[2][16][2][16];
__device__ __align__(128) uint32_t g_xc[2][8];
struct RouteOut { int idx; float r; float mean; float rstd; };

constexpr uint32_t SB = 1024;

__device__ __forceinline__ uint32_t smem_u32(const void* p) { return (uint32_t)__cvta_generic_to_shared(p); }
__device__ __forceinline__ void mbar_arrive(uint32_t bar) { asm volatile("mbarrier.arrive.shared::cta.b64 _, [%0];" :: "r"(bar) : "memory"); }
__device__ __forceinline__ void mbar_wait(uint32_t bar, uint32_t parity) {
    asm volatile("{\n.reg .pred p, q;\n.reg .u32 n;\nmov.u32 n, 0;\n"
                 "LAB_WAIT:\nadd.u32 n, n, 1;\nmbarrier.try_wait.parity.shared::cta.b64 p, [%0], %1;\n"
                 "setp.lt.and.u32 q, n, 0x800000, !p;\n@q bra LAB_WAIT;\n@!p st.shared.u32 [n], n;\n}" :: "r"(bar), "r"(parity) : "memory");
}
__device__ __forceinline__ void mbar_arrive_elect(uint32_t bar) {
    asm volatile("{\n.reg .pred p;\nelect.sync _|p, 0xffffffff;\n@p mbarrier.arrive.shared::cta.b64 _, [%0];\n}" :: "r"(bar) : "memory");
}
__device__ __forceinline__ int tid_now() { int v; asm volatile("mov.u32 %0, %%tid.x;" : "=r"(v)); return v; }
__device__ __forceinline__ int cta_now() { int v; asm volatile("mov.u32 %0, %%ctaid.x;" : "=r"(v)); return v; }
__device__ __forceinline__ int warp_uniform(int v) { return __shfl_sync(0xffffffffu, v, 0); }
__device__ __forceinline__ void fence_mbar_init() { asm volatile("fence.mbarrier_init.release.cluster;" ::: "memory"); }
__device__ __forceinline__ void fence_async_smem() { asm volatile("fence.proxy.async.shared::cta;" ::: "memory"); }
__device__ __forceinline__ void fence_async_global() { asm volatile("fence.proxy.async.global;" ::: "memory"); }
__device__ __forceinline__ void named_sync(int id, int n) { asm volatile("bar.sync %0, %1;" :: "r"(id), "r"(n) : "memory"); }
__device__ __forceinline__ void named_arrive(int id, int n) { asm volatile("bar.arrive %0, %1;" :: "r"(id), "r"(n) : "memory"); }
__device__ __forceinline__ bool named_any(bool p, int id) {
    uint32_t r;
    asm volatile("{\n.reg .pred a, b;\nsetp.ne.u32 a, %1, 0;\nbarrier.cta.red.or.pred b, %2, 128, a;\nselp.u32 %0, 1, 0, b;\n}" : "=r"(r) : "r"((uint32_t)p), "r"(id) : "memory");
    return r != 0;
}
#define ELECT(op) "{\n.reg .pred e;\nelect.sync _|e, 0xffffffff;\n@e " op "\n}"
__device__ __forceinline__ void mbar_init(uint32_t bar, int cnt) { asm volatile(ELECT("mbarrier.init.shared::cta.b64 [%0], %1;") :: "r"(bar), "r"(cnt) : "memory"); }
__device__ __forceinline__ void mbar_expect_tx(uint32_t bar, uint32_t bytes) { asm volatile(ELECT("mbarrier.arrive.expect_tx.shared::cta.b64 _, [%0], %1;") :: "r"(bar), "r"(bytes) : "memory"); }
__device__ __forceinline__ void bulk_load(uint32_t dst, const void* src, uint32_t bytes, uint32_t bar) {
    asm volatile(ELECT("cp.async.bulk.shared::cluster.global.mbarrier::complete_tx::bytes [%0], [%1], %2, [%3];") :: "r"(dst), "l"(src), "r"(bytes), "r"(bar) : "memory");
}
__device__ __forceinline__ void bulk_store(void* dst, uint32_t src, uint32_t bytes) {
    asm volatile(ELECT("cp.async.bulk.global.shared::cta.bulk_group [%0], [%1], %2;") :: "l"(dst), "r"(src), "r"(bytes) : "memory");
}
__device__ __forceinline__ void bulk_commit() { asm volatile("cp.async.bulk.commit_group;" ::: "memory"); }
__device__ __forceinline__ void bulk_wait() { asm volatile("cp.async.bulk.wait_group 0;" ::: "memory"); }
__device__ __forceinline__ void l2_prefetch(const void* src, uint32_t bytes) {
    asm volatile(ELECT("cp.async.bulk.prefetch.L2.global [%0], %1;") :: "l"(src), "r"(bytes) : "memory");
}
__device__ __forceinline__ void tma_load(uint32_t dst, const CUtensorMap* tm, int c0, int c1, uint32_t bar) {
    asm volatile(ELECT("cp.async.bulk.tensor.2d.shared::cluster.global.mbarrier::complete_tx::bytes [%0], [%1, {%3, %4}], [%2];")
                 :: "r"(dst), "l"(tm), "r"(bar), "r"(c0), "r"(c1) : "memory");
}
__device__ __forceinline__ void tma_load3(uint32_t dst, const CUtensorMap* tm, int c0, int c1, int c2, uint32_t bar) {
    asm volatile(ELECT("cp.async.bulk.tensor.3d.shared::cluster.global.mbarrier::complete_tx::bytes [%0], [%1, {%3, %4, %5}], [%2];")
                 :: "r"(dst), "l"(tm), "r"(bar), "r"(c0), "r"(c1), "r"(c2) : "memory");
}
__device__ __forceinline__ uint64_t evict_first() { uint64_t a; asm("createpolicy.fractional.L2::evict_first.b64 %0, 1.0;" : "=l"(a)); return a; }
__device__ __forceinline__ void tma_load_h(uint32_t dst, const CUtensorMap* tm, int c0, int c1, uint32_t bar, bool ef) {
    if (!ef) tma_load(dst, tm, c0, c1, bar);
    else asm volatile(ELECT("cp.async.bulk.tensor.2d.shared::cluster.global.mbarrier::complete_tx::bytes.L2::cache_hint [%0], [%1, {%3, %4}], [%2], %5;")
                      :: "r"(dst), "l"(tm), "r"(bar), "r"(c0), "r"(c1), "l"(evict_first()) : "memory");
}
__device__ __forceinline__ void tma_load3_h(uint32_t dst, const CUtensorMap* tm, int c0, int c1, int c2, uint32_t bar, bool ef) {
    if (!ef) tma_load3(dst, tm, c0, c1, c2, bar);
    else asm volatile(ELECT("cp.async.bulk.tensor.3d.shared::cluster.global.mbarrier::complete_tx::bytes.L2::cache_hint [%0], [%1, {%3, %4, %5}], [%2], %6;")
                      :: "r"(dst), "l"(tm), "r"(bar), "r"(c0), "r"(c1), "r"(c2), "l"(evict_first()) : "memory");
}
__device__ __forceinline__ void tma_load5(uint32_t dst, const CUtensorMap* tm, int c0, int c1, int c2, int c3, int c4, uint32_t bar) {
    asm volatile(ELECT("cp.async.bulk.tensor.5d.shared::cluster.global.mbarrier::complete_tx::bytes [%0], [%1, {%3, %4, %5, %6, %7}], [%2];")
                 :: "r"(dst), "l"(tm), "r"(bar), "r"(c0), "r"(c1), "r"(c2), "r"(c3), "r"(c4) : "memory");
}
__device__ __forceinline__ void tma_store(const CUtensorMap* tm, uint32_t src, int c0, int c1) {
    asm volatile(ELECT("cp.async.bulk.tensor.2d.global.shared::cta.bulk_group [%0, {%2, %3}], [%1];") :: "l"(tm), "r"(src), "r"(c0), "r"(c1) : "memory");
}
__device__ __forceinline__ void tm_prefetch(const CUtensorMap* tm) { asm volatile(ELECT("prefetch.tensormap [%0];") :: "l"(tm) : "memory"); }
__device__ __forceinline__ uint32_t lds32(uint32_t a) { uint32_t v; asm volatile("ld.shared.b32 %0, [%1];" : "=r"(v) : "r"(a) : "memory"); return v; }
__device__ __forceinline__ float ldsf(uint32_t a) { return __uint_as_float(lds32(a)); }
__device__ __forceinline__ float2 lds64f(uint32_t a) { float2 v; asm volatile("ld.shared.v2.f32 {%0, %1}, [%2];" : "=f"(v.x), "=f"(v.y) : "r"(a) : "memory"); return v; }
__device__ __forceinline__ uint4 lds128(uint32_t a) { uint4 v; asm volatile("ld.shared.v4.b32 {%0, %1, %2, %3}, [%4];" : "=r"(v.x), "=r"(v.y), "=r"(v.z), "=r"(v.w) : "r"(a) : "memory"); return v; }
__device__ __forceinline__ void sts32(uint32_t a, uint32_t v) { asm volatile("st.shared.b32 [%0], %1;" :: "r"(a), "r"(v) : "memory"); }
__device__ __forceinline__ void stsf(uint32_t a, float v) { sts32(a, __float_as_uint(v)); }
__device__ __forceinline__ void sts64f(uint32_t a, float x, float y) { asm volatile("st.shared.v2.f32 [%0], {%1, %2};" :: "r"(a), "f"(x), "f"(y) : "memory"); }
__device__ __forceinline__ void sts128(uint32_t a, const uint4& v) { asm volatile("st.shared.v4.b32 [%0], {%1, %2, %3, %4};" :: "r"(a), "r"(v.x), "r"(v.y), "r"(v.z), "r"(v.w) : "memory"); }
__device__ __forceinline__ void stsm4(uint32_t a, uint32_t x, uint32_t y, uint32_t z, uint32_t w) {
    asm volatile("stmatrix.sync.aligned.m8n8.x4.shared.b16 [%0], {%1, %2, %3, %4};" :: "r"(a), "r"(x), "r"(y), "r"(z), "r"(w) : "memory");
}
__device__ __forceinline__ void ldsm4(uint32_t& a0, uint32_t& a1, uint32_t& a2, uint32_t& a3, uint32_t addr) {
    asm volatile("ldmatrix.sync.aligned.m8n8.x4.shared.b16 {%0,%1,%2,%3}, [%4];" : "=r"(a0), "=r"(a1), "=r"(a2), "=r"(a3) : "r"(addr) : "memory");
}
__device__ __forceinline__ void ldsm4t(uint32_t& a0, uint32_t& a1, uint32_t& a2, uint32_t& a3, uint32_t addr) {
    asm volatile("ldmatrix.sync.aligned.m8n8.x4.trans.shared.b16 {%0,%1,%2,%3}, [%4];" : "=r"(a0), "=r"(a1), "=r"(a2), "=r"(a3) : "r"(addr) : "memory");
}
__device__ __forceinline__ void mma_bf16(float (&c)[4], uint32_t a0, uint32_t a1, uint32_t a2, uint32_t a3, uint32_t b0, uint32_t b1) {
    asm("mma.sync.aligned.m16n8k16.row.col.f32.bf16.bf16.f32 {%0,%1,%2,%3}, {%4,%5,%6,%7}, {%8,%9}, {%0,%1,%2,%3};"
        : "+f"(c[0]), "+f"(c[1]), "+f"(c[2]), "+f"(c[3]) : "r"(a0), "r"(a1), "r"(a2), "r"(a3), "r"(b0), "r"(b1));
}
__device__ __forceinline__ void mma_f16(float (&c)[4], uint32_t a0, uint32_t a1, uint32_t a2, uint32_t a3, uint32_t b0, uint32_t b1) {
    asm("mma.sync.aligned.m16n8k16.row.col.f32.f16.f16.f32 {%0,%1,%2,%3}, {%4,%5,%6,%7}, {%8,%9}, {%0,%1,%2,%3};"
        : "+f"(c[0]), "+f"(c[1]), "+f"(c[2]), "+f"(c[3]) : "r"(a0), "r"(a1), "r"(a2), "r"(a3), "r"(b0), "r"(b1));
}
__device__ __forceinline__ uint32_t ld_acquire(const void* p) { uint32_t v; asm volatile("ld.acquire.gpu.global.u32 %0, [%1];" : "=r"(v) : "l"(p) : "memory"); return v; }
__device__ __forceinline__ void sts_release(uint32_t a, uint32_t v) { asm volatile("st.release.cta.shared.u32 [%0], %1;" :: "r"(a), "r"(v) : "memory"); }
__device__ __forceinline__ uint32_t ld_relaxed(const void* p) { uint32_t v; asm volatile("ld.relaxed.gpu.global.u32 %0, [%1];" : "=r"(v) : "l"(p) : "memory"); return v; }
__device__ __forceinline__ uint4 ld_relaxed4(const void* p) {
    uint4 v; asm volatile("ld.relaxed.gpu.global.v4.b32 {%0, %1, %2, %3}, [%4];" : "=r"(v.x), "=r"(v.y), "=r"(v.z), "=r"(v.w) : "l"(p) : "memory"); return v;
}
__device__ __forceinline__ uint2 ld_relaxed2(const void* p) { uint2 v; asm volatile("ld.relaxed.gpu.global.v2.b32 {%0, %1}, [%2];" : "=r"(v.x), "=r"(v.y) : "l"(p) : "memory"); return v; }
__device__ __forceinline__ void st_relaxed(void* p, uint32_t v) { asm volatile("st.relaxed.gpu.global.u32 [%0], %1;" :: "l"(p), "r"(v) : "memory"); }
__device__ __forceinline__ void st_relaxed4_if(void* p, const uint4& v, bool on) {
    asm volatile("{\n.reg .pred q;\nsetp.ne.u32 q, %5, 0;\n@q st.relaxed.gpu.global.v4.b32 [%0], {%1, %2, %3, %4};\n}"
                 :: "l"(p), "r"(v.x), "r"(v.y), "r"(v.z), "r"(v.w), "r"((uint32_t)on) : "memory");
}
__device__ __forceinline__ uint32_t not_sent(float v) { const uint32_t u = __float_as_uint(v); return u == SENT ? 0x7FFFFFFFu : u; }
__device__ __forceinline__ bool has_sent(const uint4& v) { return max(max(v.x, v.y), max(v.z, v.w)) == SENT; }
constexpr uint32_t SPIN_MAX = 1u << 22;
__device__ __forceinline__ void spin_check(uint32_t n) { asm volatile("{\n.reg .pred p;\nsetp.ge.u32 p, %0, %1;\n@p st.global.u32 [%2], %0;\n}" :: "r"(n), "n"(SPIN_MAX), "l"(0ull) : "memory"); }
__device__ __forceinline__ void ctr_arrive(uint32_t* c, uint32_t n = 1) { asm volatile(ELECT("red.release.gpu.global.add.u32 [%0], %1;") :: "l"(c), "r"(n) : "memory"); }
__device__ __forceinline__ void ctr_wait(const uint32_t* c, uint32_t target) {
    asm volatile("{\n.reg .pred p;\n.reg .u32 n, v;\nmov.u32 n, 0;\n"
                 "LAB_WAIT:\nld.acquire.gpu.global.u32 v, [%0];\nsetp.ge.u32 p, v, %1;\n@p bra LAB_DONE;\n"
                 "add.u32 n, n, 1;\nsetp.lt.u32 p, n, 0x400000;\n@p bra LAB_WAIT;\ntrap;\nLAB_DONE:\n}" :: "l"(c), "r"(target) : "memory");
}
__device__ __forceinline__ void ctr_wait_all(const uint32_t* c, uint32_t target) {
    asm volatile("{\n.reg .pred p;\n.reg .u32 n, v;\nmov.u32 n, 0;\n"
                 "LAB_WAIT:\nld.acquire.gpu.global.u32 v, [%0];\nsetp.ge.u32 p, v, %1;\nvote.sync.all.pred p, p, 0xffffffff;\n@p bra.uni LAB_DONE;\n"
                 "add.u32 n, n, 1;\nsetp.lt.u32 p, n, 0x400000;\n@p bra.uni LAB_WAIT;\ntrap;\nLAB_DONE:\n}" :: "l"(c), "r"(target) : "memory");
}
__device__ __forceinline__ uint32_t smem_wait_any(uint32_t a, uint32_t mask) {
    uint32_t v;
    asm volatile("{\n.reg .pred p;\n.reg .u32 n, t;\nmov.u32 n, 0;\n"
                 "LAB_WAIT:\nld.acquire.cta.shared.u32 %0, [%1];\nand.b32 t, %0, %2;\nsetp.ne.u32 p, t, 0;\nvote.sync.all.pred p, p, 0xffffffff;\n@p bra.uni LAB_DONE;\n"
                 "add.u32 n, n, 1;\nsetp.lt.u32 p, n, 0x4000000;\n@p bra.uni LAB_WAIT;\ntrap;\nLAB_DONE:\n}" : "=r"(v) : "r"(a), "r"(mask) : "memory");
    return warp_uniform(v);
}
__device__ __forceinline__ void publish(uint32_t* c, uint32_t n = 1) { bulk_wait(); fence_async_global(); ctr_arrive(c, n); }

__device__ __forceinline__ void wg_fence() { asm volatile("wgmma.fence.sync.aligned;" ::: "memory"); }
__device__ __forceinline__ void wg_commit() { asm volatile("wgmma.commit_group.sync.aligned;" ::: "memory"); }
template <int N> __device__ __forceinline__ void wg_wait() { asm volatile("wgmma.wait_group.sync.aligned %0;" :: "n"(N) : "memory"); }
template <int N> __device__ __forceinline__ void reg_inc() { asm volatile("setmaxnreg.inc.sync.aligned.u32 %0;" :: "n"(N)); }
template <int N> __device__ __forceinline__ void reg_dec() { asm volatile("setmaxnreg.dec.sync.aligned.u32 %0;" :: "n"(N)); }
__host__ __device__ constexpr uint64_t desc_plain(uint32_t addr, uint32_t lbo, uint32_t sbo) {
    return (uint64_t)((addr & 0x3FFFF) >> 4) | ((uint64_t)(lbo >> 4) << 16) | ((uint64_t)(sbo >> 4) << 32);
}
__host__ __device__ constexpr uint64_t desc_sw128(uint32_t addr, uint32_t lbo, uint32_t sbo) { return desc_plain(addr, lbo, sbo) | (1ull << 62); }

__device__ __forceinline__ float ex2(float x) { float y; asm("ex2.approx.ftz.f32 %0, %1;" : "=f"(y) : "f"(x)); return y; }
__device__ __forceinline__ float rcp(float x) { float y; asm("rcp.approx.ftz.f32 %0, %1;" : "=f"(y) : "f"(x)); return y; }
__device__ __forceinline__ float rsq(float x) { float y; asm("rsqrt.approx.ftz.f32 %0, %1;" : "=f"(y) : "f"(x)); return y; }
__device__ __forceinline__ uint32_t pack_bf16(float lo, float hi) { uint32_t r; asm("cvt.rn.bf16x2.f32 %0, %1, %2;" : "=r"(r) : "f"(hi), "f"(lo)); return r; }
__device__ __forceinline__ uint32_t pack_f16(float lo, float hi) { uint32_t r; asm("cvt.rn.f16x2.f32 %0, %1, %2;" : "=r"(r) : "f"(hi), "f"(lo)); return r; }
__device__ __forceinline__ uint32_t round8(uint32_t v) { return (v + 0x00040004u) & 0xFFF8FFF8u; }
__device__ __forceinline__ float bf_lo(uint32_t v) { return __uint_as_float(v << 16); }
__device__ __forceinline__ float bf_hi(uint32_t v) { return __uint_as_float(v & 0xFFFF0000u); }
__device__ __forceinline__ float bf_round(float x) { return __uint_as_float(pack_bf16(0.f, x)); }
__device__ __forceinline__ uint32_t badd2(uint32_t a, uint32_t b) { uint32_t r; asm("add.rn.bf16x2 %0, %1, %2;" : "=r"(r) : "r"(a), "r"(b)); return r; }
__device__ __forceinline__ void h2_unpack(uint32_t v, float& lo, float& hi) {
    asm("{.reg .f16 l, h; mov.b32 {l, h}, %2; cvt.f32.f16 %0, l; cvt.f32.f16 %1, h;}" : "=f"(lo), "=f"(hi) : "r"(v));
}
__device__ __forceinline__ uint32_t add_ln2(uint32_t x, float rstd, float nb) { return badd2(x, pack_bf16(fmaf(bf_lo(x), rstd, nb), fmaf(bf_hi(x), rstd, nb))); }
__device__ __forceinline__ float sel4(int t, float a0, float a1, float a2, float a3) {
    float r;
    asm("{\n.reg .pred p, q;\n.reg .f32 x, y;\nsetp.ne.u32 p, %1, 0;\nsetp.ne.u32 q, %2, 0;\nselp.f32 x, %4, %3, p;\nselp.f32 y, %6, %5, p;\nselp.f32 %0, y, x, q;\n}"
        : "=f"(r) : "r"(t & 1), "r"(t & 2), "f"(a0), "f"(a1), "f"(a2), "f"(a3));
    return r;
}
__device__ __forceinline__ float warp_sum(float v) {
    #pragma unroll
    for (int o = 16; o > 0; o >>= 1) v += __shfl_xor_sync(0xffffffffu, v, o);
    return v;
}
__device__ __forceinline__ uint32_t redux_or(uint32_t v) { uint32_t r; asm volatile("redux.sync.or.b32 %0, %1, 0xffffffff;" : "=r"(r) : "r"(v)); return r; }
__device__ __forceinline__ uint32_t redux_max(uint32_t v) { uint32_t r; asm volatile("redux.sync.max.u32 %0, %1, 0xffffffff;" : "=r"(r) : "r"(v)); return r; }
__device__ __forceinline__ uint32_t redux_min(uint32_t v) { uint32_t r; asm volatile("redux.sync.min.u32 %0, %1, 0xffffffff;" : "=r"(r) : "r"(v)); return r; }


__device__ __forceinline__ void wg_gemm_n128(float (&d)[64], uint64_t desca, uint64_t desc) {
    asm volatile("{\n.reg .pred p;\nsetp.ne.b32 p, 1, 0;\n"
        "wgmma.mma_async.sync.aligned.m64n128k16.f32.bf16.bf16 "
        "{%0,%1,%2,%3,%4,%5,%6,%7,%8,%9,%10,%11,%12,%13,%14,%15,%16,%17,%18,%19,%20,%21,%22,%23,%24,%25,%26,%27,%28,%29,%30,%31,%32,%33,%34,%35,%36,%37,%38,%39,%40,%41,%42,%43,%44,%45,%46,%47,%48,%49,%50,%51,%52,%53,%54,%55,%56,%57,%58,%59,%60,%61,%62,%63}, "
        "%64, %65, p, 1, 1, 0, 1;\n}\n"
        : "+f"(d[0]), "+f"(d[1]), "+f"(d[2]), "+f"(d[3]), "+f"(d[4]), "+f"(d[5]), "+f"(d[6]), "+f"(d[7]),
          "+f"(d[8]), "+f"(d[9]), "+f"(d[10]), "+f"(d[11]), "+f"(d[12]), "+f"(d[13]), "+f"(d[14]), "+f"(d[15]),
          "+f"(d[16]), "+f"(d[17]), "+f"(d[18]), "+f"(d[19]), "+f"(d[20]), "+f"(d[21]), "+f"(d[22]), "+f"(d[23]),
          "+f"(d[24]), "+f"(d[25]), "+f"(d[26]), "+f"(d[27]), "+f"(d[28]), "+f"(d[29]), "+f"(d[30]), "+f"(d[31]),
          "+f"(d[32]), "+f"(d[33]), "+f"(d[34]), "+f"(d[35]), "+f"(d[36]), "+f"(d[37]), "+f"(d[38]), "+f"(d[39]),
          "+f"(d[40]), "+f"(d[41]), "+f"(d[42]), "+f"(d[43]), "+f"(d[44]), "+f"(d[45]), "+f"(d[46]), "+f"(d[47]),
          "+f"(d[48]), "+f"(d[49]), "+f"(d[50]), "+f"(d[51]), "+f"(d[52]), "+f"(d[53]), "+f"(d[54]), "+f"(d[55]),
          "+f"(d[56]), "+f"(d[57]), "+f"(d[58]), "+f"(d[59]), "+f"(d[60]), "+f"(d[61]), "+f"(d[62]), "+f"(d[63])
        : "l"(desca), "l"(desc));
}
__device__ __forceinline__ void wg_gemm_n128_init(float (&d)[64], uint64_t desca, uint64_t desc) {
    asm volatile("{\n.reg .pred p;\nsetp.ne.b32 p, 0, 0;\n"
        "wgmma.mma_async.sync.aligned.m64n128k16.f32.bf16.bf16 "
        "{%0,%1,%2,%3,%4,%5,%6,%7,%8,%9,%10,%11,%12,%13,%14,%15,%16,%17,%18,%19,%20,%21,%22,%23,%24,%25,%26,%27,%28,%29,%30,%31,%32,%33,%34,%35,%36,%37,%38,%39,%40,%41,%42,%43,%44,%45,%46,%47,%48,%49,%50,%51,%52,%53,%54,%55,%56,%57,%58,%59,%60,%61,%62,%63}, "
        "%64, %65, p, 1, 1, 0, 1;\n}\n"
        : "=f"(d[0]), "=f"(d[1]), "=f"(d[2]), "=f"(d[3]), "=f"(d[4]), "=f"(d[5]), "=f"(d[6]), "=f"(d[7]),
          "=f"(d[8]), "=f"(d[9]), "=f"(d[10]), "=f"(d[11]), "=f"(d[12]), "=f"(d[13]), "=f"(d[14]), "=f"(d[15]),
          "=f"(d[16]), "=f"(d[17]), "=f"(d[18]), "=f"(d[19]), "=f"(d[20]), "=f"(d[21]), "=f"(d[22]), "=f"(d[23]),
          "=f"(d[24]), "=f"(d[25]), "=f"(d[26]), "=f"(d[27]), "=f"(d[28]), "=f"(d[29]), "=f"(d[30]), "=f"(d[31]),
          "=f"(d[32]), "=f"(d[33]), "=f"(d[34]), "=f"(d[35]), "=f"(d[36]), "=f"(d[37]), "=f"(d[38]), "=f"(d[39]),
          "=f"(d[40]), "=f"(d[41]), "=f"(d[42]), "=f"(d[43]), "=f"(d[44]), "=f"(d[45]), "=f"(d[46]), "=f"(d[47]),
          "=f"(d[48]), "=f"(d[49]), "=f"(d[50]), "=f"(d[51]), "=f"(d[52]), "=f"(d[53]), "=f"(d[54]), "=f"(d[55]),
          "=f"(d[56]), "=f"(d[57]), "=f"(d[58]), "=f"(d[59]), "=f"(d[60]), "=f"(d[61]), "=f"(d[62]), "=f"(d[63])
        : "l"(desca), "l"(desc));
}
__device__ __forceinline__ void wg_gemm_n192(float (&d)[96], uint64_t desca, uint64_t desc) {
    asm volatile("{\n.reg .pred p;\nsetp.ne.b32 p, 1, 0;\n"
        "wgmma.mma_async.sync.aligned.m64n192k16.f32.bf16.bf16 "
        "{%0,%1,%2,%3,%4,%5,%6,%7,%8,%9,%10,%11,%12,%13,%14,%15,%16,%17,%18,%19,%20,%21,%22,%23,%24,%25,%26,%27,%28,%29,%30,%31,%32,%33,%34,%35,%36,%37,%38,%39,%40,%41,%42,%43,%44,%45,%46,%47,%48,%49,%50,%51,%52,%53,%54,%55,%56,%57,%58,%59,%60,%61,%62,%63,%64,%65,%66,%67,%68,%69,%70,%71,%72,%73,%74,%75,%76,%77,%78,%79,%80,%81,%82,%83,%84,%85,%86,%87,%88,%89,%90,%91,%92,%93,%94,%95}, "
        "%96, %97, p, 1, 1, 0, 1;\n}\n"
        : "+f"(d[0]), "+f"(d[1]), "+f"(d[2]), "+f"(d[3]), "+f"(d[4]), "+f"(d[5]), "+f"(d[6]), "+f"(d[7]),
          "+f"(d[8]), "+f"(d[9]), "+f"(d[10]), "+f"(d[11]), "+f"(d[12]), "+f"(d[13]), "+f"(d[14]), "+f"(d[15]),
          "+f"(d[16]), "+f"(d[17]), "+f"(d[18]), "+f"(d[19]), "+f"(d[20]), "+f"(d[21]), "+f"(d[22]), "+f"(d[23]),
          "+f"(d[24]), "+f"(d[25]), "+f"(d[26]), "+f"(d[27]), "+f"(d[28]), "+f"(d[29]), "+f"(d[30]), "+f"(d[31]),
          "+f"(d[32]), "+f"(d[33]), "+f"(d[34]), "+f"(d[35]), "+f"(d[36]), "+f"(d[37]), "+f"(d[38]), "+f"(d[39]),
          "+f"(d[40]), "+f"(d[41]), "+f"(d[42]), "+f"(d[43]), "+f"(d[44]), "+f"(d[45]), "+f"(d[46]), "+f"(d[47]),
          "+f"(d[48]), "+f"(d[49]), "+f"(d[50]), "+f"(d[51]), "+f"(d[52]), "+f"(d[53]), "+f"(d[54]), "+f"(d[55]),
          "+f"(d[56]), "+f"(d[57]), "+f"(d[58]), "+f"(d[59]), "+f"(d[60]), "+f"(d[61]), "+f"(d[62]), "+f"(d[63]),
          "+f"(d[64]), "+f"(d[65]), "+f"(d[66]), "+f"(d[67]), "+f"(d[68]), "+f"(d[69]), "+f"(d[70]), "+f"(d[71]),
          "+f"(d[72]), "+f"(d[73]), "+f"(d[74]), "+f"(d[75]), "+f"(d[76]), "+f"(d[77]), "+f"(d[78]), "+f"(d[79]),
          "+f"(d[80]), "+f"(d[81]), "+f"(d[82]), "+f"(d[83]), "+f"(d[84]), "+f"(d[85]), "+f"(d[86]), "+f"(d[87]),
          "+f"(d[88]), "+f"(d[89]), "+f"(d[90]), "+f"(d[91]), "+f"(d[92]), "+f"(d[93]), "+f"(d[94]), "+f"(d[95])
        : "l"(desca), "l"(desc));
}
__device__ __forceinline__ void wg_gemm_n192_init(float (&d)[96], uint64_t desca, uint64_t desc) {
    asm volatile("{\n.reg .pred p;\nsetp.ne.b32 p, 0, 0;\n"
        "wgmma.mma_async.sync.aligned.m64n192k16.f32.bf16.bf16 "
        "{%0,%1,%2,%3,%4,%5,%6,%7,%8,%9,%10,%11,%12,%13,%14,%15,%16,%17,%18,%19,%20,%21,%22,%23,%24,%25,%26,%27,%28,%29,%30,%31,%32,%33,%34,%35,%36,%37,%38,%39,%40,%41,%42,%43,%44,%45,%46,%47,%48,%49,%50,%51,%52,%53,%54,%55,%56,%57,%58,%59,%60,%61,%62,%63,%64,%65,%66,%67,%68,%69,%70,%71,%72,%73,%74,%75,%76,%77,%78,%79,%80,%81,%82,%83,%84,%85,%86,%87,%88,%89,%90,%91,%92,%93,%94,%95}, "
        "%96, %97, p, 1, 1, 0, 1;\n}\n"
        : "=f"(d[0]), "=f"(d[1]), "=f"(d[2]), "=f"(d[3]), "=f"(d[4]), "=f"(d[5]), "=f"(d[6]), "=f"(d[7]),
          "=f"(d[8]), "=f"(d[9]), "=f"(d[10]), "=f"(d[11]), "=f"(d[12]), "=f"(d[13]), "=f"(d[14]), "=f"(d[15]),
          "=f"(d[16]), "=f"(d[17]), "=f"(d[18]), "=f"(d[19]), "=f"(d[20]), "=f"(d[21]), "=f"(d[22]), "=f"(d[23]),
          "=f"(d[24]), "=f"(d[25]), "=f"(d[26]), "=f"(d[27]), "=f"(d[28]), "=f"(d[29]), "=f"(d[30]), "=f"(d[31]),
          "=f"(d[32]), "=f"(d[33]), "=f"(d[34]), "=f"(d[35]), "=f"(d[36]), "=f"(d[37]), "=f"(d[38]), "=f"(d[39]),
          "=f"(d[40]), "=f"(d[41]), "=f"(d[42]), "=f"(d[43]), "=f"(d[44]), "=f"(d[45]), "=f"(d[46]), "=f"(d[47]),
          "=f"(d[48]), "=f"(d[49]), "=f"(d[50]), "=f"(d[51]), "=f"(d[52]), "=f"(d[53]), "=f"(d[54]), "=f"(d[55]),
          "=f"(d[56]), "=f"(d[57]), "=f"(d[58]), "=f"(d[59]), "=f"(d[60]), "=f"(d[61]), "=f"(d[62]), "=f"(d[63]),
          "=f"(d[64]), "=f"(d[65]), "=f"(d[66]), "=f"(d[67]), "=f"(d[68]), "=f"(d[69]), "=f"(d[70]), "=f"(d[71]),
          "=f"(d[72]), "=f"(d[73]), "=f"(d[74]), "=f"(d[75]), "=f"(d[76]), "=f"(d[77]), "=f"(d[78]), "=f"(d[79]),
          "=f"(d[80]), "=f"(d[81]), "=f"(d[82]), "=f"(d[83]), "=f"(d[84]), "=f"(d[85]), "=f"(d[86]), "=f"(d[87]),
          "=f"(d[88]), "=f"(d[89]), "=f"(d[90]), "=f"(d[91]), "=f"(d[92]), "=f"(d[93]), "=f"(d[94]), "=f"(d[95])
        : "l"(desca), "l"(desc));
}
__device__ __forceinline__ void wg_qk_init(uint32_t (&d)[32], uint32_t a0, uint32_t a1, uint32_t a2, uint32_t a3, uint64_t desc) {
    asm volatile("{\n.reg .pred p;\nsetp.ne.b32 p, 0, 0;\n"
        "wgmma.mma_async.sync.aligned.m64n128k16.f16.f16.f16 "
        "{%0,%1,%2,%3,%4,%5,%6,%7,%8,%9,%10,%11,%12,%13,%14,%15,%16,%17,%18,%19,%20,%21,%22,%23,%24,%25,%26,%27,%28,%29,%30,%31}, "
        "{%32,%33,%34,%35}, %36, p, 1, 1, 0;\n}\n"
        : "=r"(d[0]), "=r"(d[1]), "=r"(d[2]), "=r"(d[3]), "=r"(d[4]), "=r"(d[5]), "=r"(d[6]), "=r"(d[7]),
          "=r"(d[8]), "=r"(d[9]), "=r"(d[10]), "=r"(d[11]), "=r"(d[12]), "=r"(d[13]), "=r"(d[14]), "=r"(d[15]),
          "=r"(d[16]), "=r"(d[17]), "=r"(d[18]), "=r"(d[19]), "=r"(d[20]), "=r"(d[21]), "=r"(d[22]), "=r"(d[23]),
          "=r"(d[24]), "=r"(d[25]), "=r"(d[26]), "=r"(d[27]), "=r"(d[28]), "=r"(d[29]), "=r"(d[30]), "=r"(d[31])
        : "r"(a0), "r"(a1), "r"(a2), "r"(a3), "l"(desc));
}
__device__ __forceinline__ void wg_qk_acc(uint32_t (&d)[32], uint64_t desca, uint64_t desc) {
    asm volatile("{\n.reg .pred p;\nsetp.ne.b32 p, 1, 0;\n"
        "wgmma.mma_async.sync.aligned.m64n128k16.f16.f16.f16 "
        "{%0,%1,%2,%3,%4,%5,%6,%7,%8,%9,%10,%11,%12,%13,%14,%15,%16,%17,%18,%19,%20,%21,%22,%23,%24,%25,%26,%27,%28,%29,%30,%31}, "
        "%32, %33, p, 1, 1, 0, 0;\n}\n"
        : "+r"(d[0]), "+r"(d[1]), "+r"(d[2]), "+r"(d[3]), "+r"(d[4]), "+r"(d[5]), "+r"(d[6]), "+r"(d[7]),
          "+r"(d[8]), "+r"(d[9]), "+r"(d[10]), "+r"(d[11]), "+r"(d[12]), "+r"(d[13]), "+r"(d[14]), "+r"(d[15]),
          "+r"(d[16]), "+r"(d[17]), "+r"(d[18]), "+r"(d[19]), "+r"(d[20]), "+r"(d[21]), "+r"(d[22]), "+r"(d[23]),
          "+r"(d[24]), "+r"(d[25]), "+r"(d[26]), "+r"(d[27]), "+r"(d[28]), "+r"(d[29]), "+r"(d[30]), "+r"(d[31])
        : "l"(desca), "l"(desc));
}
__device__ __forceinline__ void wg_pv_init(uint32_t (&d)[10], uint32_t a0, uint32_t a1, uint32_t a2, uint32_t a3, uint64_t desc) {
    asm volatile("{\n.reg .pred p;\nsetp.ne.b32 p, 0, 0;\n"
        "wgmma.mma_async.sync.aligned.m64n40k16.f16.f16.f16 "
        "{%0,%1,%2,%3,%4,%5,%6,%7,%8,%9}, "
        "{%10,%11,%12,%13}, %14, p, 1, 1, 1;\n}\n"
        : "=r"(d[0]), "=r"(d[1]), "=r"(d[2]), "=r"(d[3]), "=r"(d[4]), "=r"(d[5]), "=r"(d[6]), "=r"(d[7]),
          "=r"(d[8]), "=r"(d[9])
        : "r"(a0), "r"(a1), "r"(a2), "r"(a3), "l"(desc));
}
__device__ __forceinline__ void wg_pv_acc(uint32_t (&d)[10], uint32_t a0, uint32_t a1, uint32_t a2, uint32_t a3, uint64_t desc) {
    asm volatile("{\n.reg .pred p;\nsetp.ne.b32 p, 1, 0;\n"
        "wgmma.mma_async.sync.aligned.m64n40k16.f16.f16.f16 "
        "{%0,%1,%2,%3,%4,%5,%6,%7,%8,%9}, "
        "{%10,%11,%12,%13}, %14, p, 1, 1, 1;\n}\n"
        : "+r"(d[0]), "+r"(d[1]), "+r"(d[2]), "+r"(d[3]), "+r"(d[4]), "+r"(d[5]), "+r"(d[6]), "+r"(d[7]),
          "+r"(d[8]), "+r"(d[9])
        : "r"(a0), "r"(a1), "r"(a2), "r"(a3), "l"(desc));
}

constexpr int Q_ABYTES = 256 * 64 * 2, Q_STB = Q_ABYTES + 192 * 64 * 2;
constexpr int OFF_SIDE = 3 * Q_STB;
constexpr int OFF_XS = OFF_SIDE + 49152;
constexpr int OFF_CS = OFF_XS + 4096;
constexpr int OFF_RC = OFF_CS + 768;
constexpr int OFF_FIX = OFF_RC + 2048;
constexpr int A_WIN = KV_WIN + 4096;
constexpr int OFF_QA = 3 * A_WIN;
constexpr int OFF_LC = OFF_QA + 32768;
constexpr int OFF_FE = 147456;
constexpr int OFF_XT = 196608;
__host__ __device__ constexpr uint32_t o_stage(uint32_t s) { return s == 3 ? OFF_QA : s == 2 ? 0 : (s + 1) * A_WIN; }
__host__ __device__ constexpr uint32_t gu_piece(uint32_t i) { return i < 3 ? OFF_FE + i * 16384 : i < 6 ? (i - 1) * 16384 : (i - 6) * 16384; }
constexpr int OFF_FD = 5 * 16384;
constexpr int OFF_BAR = OFF_XT + 32768;
constexpr int OFF_PART = OFF_BAR + 384;
constexpr int OFF_RED = OFF_PART + 2048;
constexpr int OFF_RT = OFF_RED + 96;
constexpr int OFF_M = OFF_RT + 144;
constexpr int OFF_WR = OFF_M + 72;
constexpr int K_SMEM = OFF_WR + 264;
static_assert(K_SMEM <= 232448 && OFF_FIX + 768 <= OFF_BAR && OFF_QA + 32768 <= OFF_FE, "smem");
constexpr uint32_t CH_OK = 0x38003800u;
constexpr int M_SC = 0,
              M_IVS = 24,
              M_ISC = 32,
              M_OK = 40,
              M_WS = 48,
              M_RIDX = 60,
              M_ORDY = 64;
constexpr uint32_t BB = SB + OFF_BAR;
constexpr uint32_t B_QF = BB, B_EPI = BB + 24, B_RES2 = BB + 56, B_AF = BB + 64, B_RES = BB + 120, B_OF = BB + 128,
                   B_FE = BB + 160, B_FL = BB + 168, B_FD = BB + 184, B_PR = BB + 192, B_FW = B_PR, B_SW = BB + 216,
                   B_QE = BB + 224, B_QAF = BB + 248, B_OE = BB + 288, B_AE = BB + 320, B_K0 = BB + 344, B_KV0 = BB + 376;

constexpr int N_OST = 5, N_XST = 9, N_RT = 11, N_KV1 = 12, N_FW = 13, N_GD = 14, N_DD = 15;

struct Maps { CUtensorMap xa0, wqkv, xa, x0, x, out, w64, wo, r, g, u, d; };

__device__ __forceinline__ float2 ln_coef(const uint4& s) {
    const float mean = __uint_as_float(s.x) * (1.f / D_);
    return make_float2(rsq(fmaxf(fmaf(-mean, mean, fmaf(__uint_as_float(s.y), 1.f / D_, LN_EPS)), LN_EPS)), mean);
}
__device__ __forceinline__ uint32_t order_bits(float r) { const uint32_t u = __float_as_uint(r); return (u & 0x80000000u) ? ~u : (u | 0x80000000u); }
__device__ __forceinline__ uint4 warp_best(const uint4& e) {
    const uint32_t m = redux_max(e.x), row = redux_min(e.x == m ? e.y : 0x7FFFFFFFu);
    const int src = __ffs(__ballot_sync(0xffffffffu, e.y == row)) - 1;
    return make_uint4(m, row, __shfl_sync(0xffffffffu, e.z, src), __shfl_sync(0xffffffffu, e.w, src));
}
__device__ __forceinline__ RouteOut route_out(const uint4& e) {
    RouteOut rt;
    rt.idx = e.y; rt.r = __uint_as_float((e.x & 0x80000000u) ? e.x & 0x7FFFFFFFu : ~e.x); rt.mean = __uint_as_float(e.z); rt.rstd = __uint_as_float(e.w);
    return rt;
}

__device__ __forceinline__ void prep_work(const bf16* __restrict__ x0, const CUtensorMap* tmW, int t) {
    const int c = blockIdx.x, lane = t & 31, warp = warp_uniform(t >> 5);
    const int ki = c >> 4, n = c & 15;
    constexpr uint32_t red = SB + OFF_SIDE, xs = red + 4096;
    if (warp == 0) {
        mbar_expect_tx(B_PR, 32768);
        bulk_load(xs, x0 + (size_t)c * 16 * D_, 32768, B_PR);
        mbar_expect_tx(B_PR + 8, 16384);
        tma_load(xs + 32768, tmW, 2 * D_ + n * 64, ki * 128, B_PR + 8);
        tma_load(xs + 32768 + 8192, tmW, 2 * D_ + n * 64, ki * 128 + 64, B_PR + 8);
    }
    const uint4 sent = make_uint4(SENT, SENT, SENT, SENT);
    for (int i = t; i < 2 * NFC * 2; i += 96) reinterpret_cast<uint4*>(&g_ypart[0][0][0])[c * (2 * NFC * 2) + i] = sent;
    if (t < 64) reinterpret_cast<uint4*>(&g_acc[0][0][0])[c * 64 + t] = make_uint4(0u, 0u, 0u, 0u);
    if (t >= 64 && t < 80) g_sums[c * 16 + t - 64] = sent;
    if (t < 2) reinterpret_cast<uint4*>(g_x2row)[c * 2 + t] = sent;
    else if (t < 8) reinterpret_cast<uint4*>(g_fix)[c * 6 + t - 2] = sent;
    else if (t < 12) (&g_kvc[0][0][0])[c * 4 + t - 8] = 0u;
    else if (t >= 24 && t < 32) (&g_oc[0][0][0][0])[c * 8 + t - 24] = 0u;
    else if (t == 13 && c < 16) (&g_xc[0][0])[c] = 0u;
    else if (t >= 16 && t < 20) (&g_tab[0][0][0][0])[c * 4 + t - 16] = sent;
    else if (t >= 32 && t < 64) reinterpret_cast<uint4*>(&g_xrow[0][0][0])[c * 32 + t - 32] = sent;
    mbar_wait(B_PR, 0);
    #pragma unroll 1
    for (int r = warp; r < 16; r += 3) {
        float s = 0.f, q = 0.f;
        #pragma unroll
        for (int i = 0; i < 4; i++) {
            const uint4 u = lds128(xs + r * 2048 + (lane + 32 * i) * 16);
            const float f[8] = {bf_lo(u.x), bf_hi(u.x), bf_lo(u.y), bf_hi(u.y), bf_lo(u.z), bf_hi(u.z), bf_lo(u.w), bf_hi(u.w)};
            #pragma unroll
            for (int e = 0; e < 8; e++) { s += f[e]; q = fmaf(f[e], f[e], q); }
        }
        #pragma unroll
        for (int o = 16; o > 0; o >>= 1) { s += __shfl_xor_sync(0xffffffffu, s, o); q += __shfl_xor_sync(0xffffffffu, q, o); }
        const float mean = s * (1.f / D_);
        const float var = fmaxf(q * (1.f / D_) - mean * mean, 0.f);
        if (lane == 0) g_rs0[c * 16 + r] = make_float2(rsqrtf(var + LN_EPS), mean);
    }
    named_sync(2, 96);
    if (warp == 0) {
        mbar_expect_tx(B_PR + 16, 32768);
        #pragma unroll
        for (int b = 0; b < 4; b++) tma_load(xs + b * 8192, tmW, (b >> 1) * D_ + n * 64, ki * 128 + (b & 1) * 64, B_PR + 16);
    }
    const int j = t & 7, rg = t >> 3;
    #pragma unroll 1
    for (int blk = 0; blk < 3; blk++) {
        const int type = blk == 0 ? 2 : blk - 1;
        const uint32_t wb = xs + type * 16384;
        if (blk < 2) mbar_wait(B_PR + 8 + 8 * blk, 0);
        float cs[8];
        uint32_t z2[4] = {0u, 0u, 0u, 0u};
        #pragma unroll
        for (int i = 0; i < 8; i++) cs[i] = 0.f;
        #pragma unroll 4
        for (int r = rg; r < 128; r += 12) {
            const uint4 u = lds128(wb + r * 128 + ((j ^ (r & 7)) << 4));
            cs[0] += bf_lo(u.x); cs[1] += bf_hi(u.x); cs[2] += bf_lo(u.y); cs[3] += bf_hi(u.y);
            cs[4] += bf_lo(u.z); cs[5] += bf_hi(u.z); cs[6] += bf_lo(u.w); cs[7] += bf_hi(u.w);
            asm("fma.rn.bf16x2 %0, %1, %1, %0;" : "+r"(z2[0]) : "r"(u.x));
            asm("fma.rn.bf16x2 %0, %1, %1, %0;" : "+r"(z2[1]) : "r"(u.y));
            asm("fma.rn.bf16x2 %0, %1, %1, %0;" : "+r"(z2[2]) : "r"(u.z));
            asm("fma.rn.bf16x2 %0, %1, %1, %0;" : "+r"(z2[3]) : "r"(u.w));
        }
        #pragma unroll
        for (int i = 0; i < 8; i++) { cs[i] += __shfl_xor_sync(0xffffffffu, cs[i], 8); cs[i] += __shfl_xor_sync(0xffffffffu, cs[i], 16); }
        float z = ((bf_lo(z2[0]) + bf_hi(z2[0])) + (bf_lo(z2[1]) + bf_hi(z2[1]))) + ((bf_lo(z2[2]) + bf_hi(z2[2])) + (bf_lo(z2[3]) + bf_hi(z2[3])));
        z += __shfl_xor_sync(0xffffffffu, z, 1); z += __shfl_xor_sync(0xffffffffu, z, 2);
        z += __shfl_xor_sync(0xffffffffu, z, 8); z += __shfl_xor_sync(0xffffffffu, z, 16);
        if (lane < 8) {
            #pragma unroll
            for (int i = 0; i < 8; i++) stsf(red + (warp * 200 + type * 64 + j * 8 + i) * 4, cs[i]);
            if ((lane & 3) == 0) stsf(red + (warp * 200 + 192 + type * 2 + (lane >> 2)) * 4, z);
        }
    }
    named_sync(2, 96);
    for (int i = t; i < 198; i += 96) {
        const float v = ldsf(red + i * 4) + ldsf(red + (200 + i) * 4) + ldsf(red + (400 + i) * 4);
        if (i < 192) g_csum[ki * (3 * D_) + (i >> 6) * D_ + n * 64 + (i & 63)] = v;
        else g_wsq[ki * 96 + ((i - 192) >> 1) * 32 + n * 2 + (i & 1)] = v;
    }
    named_sync(2, 96);
    if (warp == 0) { ctr_arrive(&g_c0); ctr_wait(&g_c0, 128); }
    named_sync(2, 96);
}

__device__ __forceinline__ float pow2_inv(float b) {
    const int e = min(max((int)(__float_as_uint(b) >> 23) + 1, 20), 234);
    return __uint_as_float((uint32_t)(254 - e) << 23);
}
__device__ __forceinline__ void epi_inputs(int L) {
    const int t = tid_now() - 288, mt = cta_now() >> 4, nt = cta_now() & 15;
    float p[2][8], r0[3], r1[3];
    #pragma unroll
    for (int k = 0; k < 2; k++)
        #pragma unroll
        for (int q = 0; q < 8; q++) p[k][q] = __ldcg(g_csum + q * (3 * D_) + ((t + 96 * k) >> 6) * D_ + nt * 64 + ((t + 96 * k) & 63));
    #pragma unroll
    for (int k = 0; k < 2; k++) stsf(SB + OFF_CS + (t + 96 * k) * 4, ((p[k][0] + p[k][1]) + (p[k][2] + p[k][3])) + ((p[k][4] + p[k][5]) + (p[k][6] + p[k][7])));
    bool wait;
    uint32_t n = 0;
    do {
        wait = false;
        #pragma unroll
        for (int k = 0; k < 3; k++) {
            const int row = mt * 256 + min(t + 96 * k, 255);
            if (L == 0) { const float2 s = __ldcg(&g_rs0[row]); r0[k] = s.x; r1[k] = s.y; }
            else { const uint4 s = ld_relaxed4(&g_sums[row]); r0[k] = __uint_as_float(s.x); r1[k] = __uint_as_float(s.y); wait = wait || has_sent(s); }
        }
    } while (wait && ++n < SPIN_MAX);
    #pragma unroll
    for (int k = 0; k < 3; k++) {
        if (L != 0) {
            const float mean = r0[k] * (1.f / D_);
            const float var = fmaxf(r1[k] * (1.f / D_) - mean * mean, 0.f);
            const float a = 1.f + rsqrtf(var + LN_EPS);
            r0[k] = a * rsqrtf(a * a * var + LN_EPS); r1[k] = mean;
        }
        if (t + 96 * k < 256) sts64f(SB + OFF_RC + (t + 96 * k) * 8, r0[k], r1[k]);
    }
    if (L == 0 && t < 32) {
        float z = 0.f;
        if (t < 6) {
            #pragma unroll
            for (int q = 0; q < 8; q++) z += __ldcg(g_wsq + q * 96 + (t >> 1) * 32 + nt * 2 + (t & 1));
        }
        const float b = sqrtf(z) * (t < 2 ? 34.f * QSCALE : 34.f);
        const float sc = t < 4 ? fminf(pow2_inv(b) * 32768.f, 1.f) : pow2_inv(b);
        const float bk = __shfl_down_sync(0xffffffffu, b, 2), sk = __shfl_down_sync(0xffffffffu, sc, 2);
        if (t < 6) stsf(SB + OFF_M + M_SC + t * 4, t < 2 ? sc * QSCALE : sc);
        if (t < 2) { stsf(SB + OFF_M + M_ISC + t * 4, 1.f / (sc * sk)); sts32(SB + OFF_M + M_OK + t * 4, sc == 1.f && sk == 1.f && b * bk < 60000.f ? CH_OK : 0u); }
        if (t == 4 || t == 5) stsf(SB + OFF_M + M_IVS + (t - 4) * 4, 1.f / sc);
    }
}

__device__ __forceinline__ int ypos_col(int p) { return (p >> 7) * 128 + ((p >> 1) & 7) * 16 + (p & 1) * 8 + ((p >> 4) & 7); }

template <int NT>
__device__ __forceinline__ float ffn_finish(int L, const RouteOut& rt, int t, uint32_t red, int bid) {
    constexpr int NL = (2 * NFC + NT - 1) / NT;
    const int c = cta_now(), col = ypos_col(c * 8 + (t & 7));
    const uint32_t* src = &g_ypart[L][t >> 1][c * 8 + (t & 1) * 4];
    uint32_t n = 0, xp;
    do { xp = ld_relaxed(&g_xrow[L][rt.idx >> 7][((col >> 5) & 7) * 64 + (col >> 8) * 16 + (col & 6) * 2 + ((col >> 3) & 3)]); } while (xp == SENT && ++n < SPIN_MAX);
    uint4 v[NL];
    #pragma unroll
    for (int i = 0; i < NL; i++) v[i] = t + NT * i < 2 * NFC ? ld_relaxed4(src + i * (NT / 2) * D_) : make_uint4(0u, 0u, 0u, 0u);
    const float xv = (col & 1) ? bf_hi(xp) : bf_lo(xp);
    float rsel = bf_round(rcp(1.f + ex2(bf_round(rt.r) * -1.4426950408889634f))), xn = bf_round((xv - rt.mean) * rt.rstd);
    asm volatile("" : "+f"(rsel), "+f"(xn));
    while (true) {
        bool wait = false;
        #pragma unroll
        for (int i = 0; i < NL; i++) wait = wait || has_sent(v[i]);
        if (!wait || ++n >= SPIN_MAX) break;
        #pragma unroll
        for (int i = 0; i < NL; i++) if (t + NT * i < 2 * NFC) v[i] = ld_relaxed4(src + i * (NT / 2) * D_);
    }
    spin_check(n);
    __syncwarp();
    float a[4] = {0.f, 0.f, 0.f, 0.f};
    #pragma unroll
    for (int i = 0; i < NL; i++) { a[0] += __uint_as_float(v[i].x); a[1] += __uint_as_float(v[i].y); a[2] += __uint_as_float(v[i].z); a[3] += __uint_as_float(v[i].w); }
    const bool b1 = t & 2, b2 = t & 4;
    a[0] = (b1 ? a[1] : a[0]) + __shfl_xor_sync(0xffffffffu, b1 ? a[0] : a[1], 2);
    a[2] = (b1 ? a[3] : a[2]) + __shfl_xor_sync(0xffffffffu, b1 ? a[2] : a[3], 2);
    a[0] = (b2 ? a[2] : a[0]) + __shfl_xor_sync(0xffffffffu, b2 ? a[0] : a[2], 4);
    a[0] += __shfl_xor_sync(0xffffffffu, a[0], 8); a[0] += __shfl_xor_sync(0xffffffffu, a[0], 16);
    if ((t & 31) < 8) stsf(red + (t >> 5) * 32 + (t & 1) * 16 + (t & 6) * 2, a[0]);
    named_sync(bid, NT);
    float y = 0.f, y2 = 0.f;
    #pragma unroll
    for (int i = 0; i < NT / 32; i++) { const float p = ldsf(red + (t & 7) * 4 + i * 32); if (i & 1) y2 += p; else y += p; }
    y += y2;
    return bf_round(xv + bf_round(xn + bf_round(bf_round(y) * rsel)));
}

__device__ __forceinline__ void routed_qkv(int ridx) {
    const int t = tid_now() - 288, c = cta_now(), lane = t & 31, warp = t >> 5;
    constexpr uint32_t red = SB + OFF_RED;
    {
        uint4 v[3];
        uint32_t n = 0;
        do {
            v[0] = ld_relaxed4(g_x2row + t * 4); v[1] = ld_relaxed4(g_x2row + (t + 96) * 4);
            v[2] = t < 64 ? ld_relaxed4(g_x2row + (t + 192) * 4) : make_uint4(0u, 0u, 0u, 0u);
        } while ((has_sent(v[0]) || has_sent(v[1]) || has_sent(v[2])) && ++n < SPIN_MAX);
        spin_check(n);
        __syncwarp();
        float f[12];
        float s = 0.f;
        #pragma unroll
        for (int i = 0; i < 3; i++) { f[4*i] = __uint_as_float(v[i].x); f[4*i+1] = __uint_as_float(v[i].y); f[4*i+2] = __uint_as_float(v[i].z); f[4*i+3] = __uint_as_float(v[i].w); }
        #pragma unroll
        for (int i = 0; i < 12; i++) s += f[i];
        s = warp_sum(s);
        if (lane == 0) stsf(red + warp * 4, s);
        named_sync(2, 96);
        const float mean = (ldsf(red) + ldsf(red + 4) + ldsf(red + 8)) * (1.f / D_);
        float q = 0.f;
        #pragma unroll
        for (int i = 0; i < 12; i++) { f[i] -= mean; if (i < 8 || t < 64) q = fmaf(f[i], f[i], q); }
        q = warp_sum(q);
        if (lane == 0) stsf(red + 16 + warp * 4, q);
        named_sync(2, 96);
        const float rstd = rsqrtf((ldsf(red + 16) + ldsf(red + 20) + ldsf(red + 24)) * (1.f / D_) + LN_EPS);
        #pragma unroll
        for (int i = 0; i < 3; i++)
            if (i < 2 || t < 64) sts128(SB + OFF_XS + (t + 96 * i) * 16, make_uint4(pack_bf16(0.f, f[4*i] * rstd), pack_bf16(0.f, f[4*i+1] * rstd), pack_bf16(0.f, f[4*i+2] * rstd), pack_bf16(0.f, f[4*i+3] * rstd)));
    }
    named_sync(2, 96);
    mbar_wait(B_SW, 0);
    float a[8];
    #pragma unroll
    for (int i = 0; i < 8; i++) a[i] = 0.f;
    const uint32_t wa = SB + OFF_SIDE + t * 16, xa = SB + OFF_XS + (t / 3) * 4;
    #pragma unroll 4
    for (int i = 0; i < 32; i++) {
        const uint4 u = lds128(wa + i * 1536);
        const float xv = ldsf(xa + i * 128);
        a[0] = fmaf(xv, bf_lo(u.x), a[0]); a[1] = fmaf(xv, bf_hi(u.x), a[1]); a[2] = fmaf(xv, bf_lo(u.y), a[2]); a[3] = fmaf(xv, bf_hi(u.y), a[3]);
        a[4] = fmaf(xv, bf_lo(u.z), a[4]); a[5] = fmaf(xv, bf_hi(u.z), a[5]); a[6] = fmaf(xv, bf_lo(u.w), a[6]); a[7] = fmaf(xv, bf_hi(u.w), a[7]);
    }
    named_sync(2, 96);
    sts128(SB + OFF_SIDE + t * 32, make_uint4(__float_as_uint(a[0]), __float_as_uint(a[1]), __float_as_uint(a[2]), __float_as_uint(a[3])));
    sts128(SB + OFF_SIDE + t * 32 + 16, make_uint4(__float_as_uint(a[4]), __float_as_uint(a[5]), __float_as_uint(a[6]), __float_as_uint(a[7])));
    named_sync(2, 96);
    {
        float y = 0.f;
        #pragma unroll
        for (int i = 0; i < 8; i++) y += ldsf(SB + OFF_SIDE + ((t & 3) * 8 + i) * 96 + (t >> 2) * 4);
        y += __shfl_xor_sync(0xffffffffu, y, 1); y += __shfl_xor_sync(0xffffffffu, y, 2);
        if ((t & 3) == 0) st_relaxed(g_fix + c * 24 + (t >> 2), not_sent(y));
    }
    if ((ridx >> 8) == (c >> 4) && t < 24) {
        const uint32_t* src = g_fix + (t >> 3) * D_ + (c & 15) * 64 + (t & 7) * 8;
        uint4 a, b;
        uint32_t n = 0;
        do { a = ld_relaxed4(src); b = ld_relaxed4(src + 4); } while ((has_sent(a) || has_sent(b)) && ++n < SPIN_MAX);
        spin_check(n);
        const int hh = t >> 2, ch = t & 3, lr = ridx & 255;
        const float hs = ldsf(SB + OFF_M + M_SC + hh * 4);
        sts128(SB + OFF_FIX + t * 16, make_uint4(pack_f16(__uint_as_float(a.x) * hs, __uint_as_float(a.y) * hs), pack_f16(__uint_as_float(a.z) * hs, __uint_as_float(a.w) * hs),
                                                 pack_f16(__uint_as_float(b.x) * hs, __uint_as_float(b.y) * hs), pack_f16(__uint_as_float(b.z) * hs, __uint_as_float(b.w) * hs)));
        sts32(SB + OFF_FIX + 512 + t * 4, SB + (hh < 2 ? OFF_QA + hh * 16384 + (lr >> 6) * 4096 + ch * 1024 + (lr & 63) * 16
                                                        : (hh & 1) * OFF_FE + (hh >> 2) * 16384 + ch * 4096 + lr * 16));
    }
    __syncwarp();
}

__device__ __forceinline__ void ffn_load(const Maps& mp, int c, int i, uint32_t dst, uint32_t bar, bool last_use) {
    if (i < 8) tma_load_h(dst, (i & 1) ? &mp.u : &mp.g, c * 32, (i >> 1) * 256, bar, last_use);
    else tma_load3_h(dst, &mp.d, 0, c * 32, (i - 8) * 4, bar, last_use);
}
__device__ __forceinline__ void side_role(const Maps& mp, const bf16* __restrict__ x0, const bf16* __restrict__ wo, const bf16* __restrict__ w_r) {
    prep_work(x0, &mp.w64, threadIdx.x - 288);
    epi_inputs(0);
    #pragma unroll 1
    for (int L = 0; L < 2; L++) {
        const int t = tid_now() - 288, lane = t & 31, sw = warp_uniform(t >> 5);
        const int c = cta_now(), mt = c >> 4, nt = c & 15;
        named_sync(2, 96);
        if (t == 0) mbar_arrive(B_EPI);
        __syncwarp();
        char* kv = g_kv + (size_t)(nt * 16 + mt) * KV_WIN;
        if (sw < 2) {
            mbar_wait(sw ? B_K0 : B_KV0, L);
            bulk_store(kv + (1 - sw) * 16384, SB + (1 - sw) * 16384, 16384);
            bulk_commit();
            publish(&g_kvc[L][nt * 2][mt], 1 + sw);
        }
        if (sw == 0) {
            named_sync(N_KV1, 96);
            bulk_store(kv + 8 * KV_WIN, SB + OFF_FE, KV_WIN);
            bulk_commit();
            publish(&g_kvc[L][nt * 2 + 1][mt], 3);
        }
        if (sw < 2) {
            #pragma unroll 1
            for (int p = 0; p < 2; p++) {
                named_sync(N_OST + 2 * p + sw, p > sw ? 192 : 160);
                if (p == 1) mbar_arrive_elect(B_QAF);
                ctr_arrive(&g_oc[L][mt * 2 + sw][p][nt]);
            }
        } else {
            if (L == 0) {
                float ws = 0.f;
                #pragma unroll
                for (int i = 0; i < 4; i++) {
                    const uint4 v = reinterpret_cast<const uint4*>(w_r)[i * 32 + lane];
                    ws += ((bf_lo(v.x) + bf_hi(v.x)) + (bf_lo(v.y) + bf_hi(v.y))) + ((bf_lo(v.z) + bf_hi(v.z)) + (bf_lo(v.w) + bf_hi(v.w)));
                }
                const uint32_t* wp = reinterpret_cast<const uint32_t*>(w_r) + (nt >> 1) * 64 + (lane >> 2) * 8 + (lane & 3);
                sts64f(SB + OFF_WR + lane * 8, __uint_as_float(wp[0]), __uint_as_float(wp[4]));
                ws = warp_sum(ws);
                if (lane == 0) { stsf(SB + OFF_M + M_WS, ws); sts64f(SB + OFF_M + M_ORDY, 0.f, 0.f); sts64f(SB + OFF_WR + 256, __uint_as_float(0x3F803F80u), __uint_as_float(0x3F803F80u)); }
                __syncwarp();
            }
            named_sync(N_KV1, 96);
            mbar_expect_tx(B_RES, 32768);
            #pragma unroll
            for (int i = 0; i < 4; i++) tma_load_h(SB + OFF_XT + i * 8192, L == 0 ? &mp.x0 : &mp.x, (nt >> 1) * 128 + (i >> 1) * 64, mt * 256 + (nt & 1) * 128 + (i & 1) * 64, B_RES, true);
            mbar_wait(B_RES, L);
            const uint32_t lr = lds32(SB + OFF_M + M_RIDX) - (mt * 256 + (nt & 1) * 128);
            if (L == 1 && lr < 128u && lane < 16) {
                const uint4 a = ld_relaxed4(g_x2row + (nt >> 1) * 128 + lane * 8), b = ld_relaxed4(g_x2row + (nt >> 1) * 128 + lane * 8 + 4);
                sts128(SB + OFF_XT + (lane >> 3) * 16384 + lr * 128 + (((lane & 7) ^ (lr & 7)) << 4),
                       make_uint4(__byte_perm(a.x, a.y, 0x7632), __byte_perm(a.z, a.w, 0x7632), __byte_perm(b.x, b.y, 0x7632), __byte_perm(b.z, b.w, 0x7632)));
            }
            if (L == 1) {
                #pragma unroll
                for (int i = 0; i < 4; i++) {
                    const float2 r = ln_coef(ld_relaxed4(&g_sums[mt * 256 + (nt & 1) * 128 + i * 32 + lane]));
                    const float a = i * 32 + lane == lr ? 0.f : r.x;
                    sts64f(SB + OFF_LC + (i * 32 + lane) * 8, a, -a * r.y);
                }
            }
            __syncwarp();
            mbar_arrive_elect(B_RES2);
            named_sync(N_FW, 64);
            l2_prefetch(reinterpret_cast<const char*>(wo) + (size_t)c * 16384, 16384);
            if (c < NFC) {
                #pragma unroll 1
                for (int r = 0; r < 4; r++) {
                    __nanosleep(100);
                    if (r > 0) mbar_wait(B_FW, (r + L) & 1);
                    const uint32_t bar = r < 3 ? B_FW : B_FE;
                    mbar_expect_tx(bar, 3 * 16384);
                    #pragma unroll 1
                    for (int b = 0; b < 3; b++) ffn_load(mp, c, 9 - 3 * r + b, SB + OFF_FE + b * 16384, bar, r == 3);
                }
            }
            named_sync(N_OST + 2, 192);
            l2_prefetch(&g_ypart[L][0][0] + c * (NFC * 8), NFC * 32);
            l2_prefetch(&g_acc[L][c * 16][0], 512);
            l2_prefetch(&g_sums[c * 16], 256);
            l2_prefetch(&g_xrow[L][0][0] + c * 64, 256);
            l2_prefetch(&g_tab[L][0][0][0] + c * 2, 32);
            l2_prefetch(c < 32 ? &g_x2row[c * 32] : c < 40 ? &g_kvc[1][(c - 32) * 4][0] : &g_xc[0][0], c < 40 ? 128 : 64);
            l2_prefetch(&g_fix[c * 24], 96);
            __nanosleep(300);
            uint32_t ready, n = 0;
            do {
                ready = __ballot_sync(0xffffffffu, ld_acquire(&g_oc[L][mt * 2 + (nt & 1)][1][lane & 15]) != 0);
                fence_async_global();
                if (lane == 0) sts_release(SB + OFF_M + M_ORDY + 4 * L, ready & ready >> 1);
            } while (ready != 0xFFFFFFFFu && ++n < SPIN_MAX);
            spin_check(n);
        }
        if (sw < 2) {
            named_sync(N_XST + sw, 160);
            #pragma unroll
            for (int h = 0; h < 2; h++)
                tma_store(L == 0 ? &mp.x : &mp.out, SB + OFF_XT + h * 16384 + sw * 8192, (nt >> 1) * 128 + h * 64, mt * 256 + (nt & 1) * 128 + sw * 64);
            bulk_commit();
            publish(&g_xc[L][mt]);
        }
        if (L == 0) {
            __syncwarp();
            named_sync(N_RT, 128);
            const RouteOut rt = route_out(lds128(SB + OFF_RT + 128));
            if (t == 0) { sts32(SB + OFF_M + M_RIDX, rt.idx); if (c == 0) g_c0 = 0u; }
            epi_inputs(1);
            const float v = ffn_finish<96>(0, rt, t, SB + OFF_RED, 2);
            if (t < 8) st_relaxed(g_x2row + ypos_col(c * 8 + t), not_sent(v));
            routed_qkv(rt.idx);
        }
    }
}

struct EpiIn { float2 c2[4]; float hs; };
template <int HH>
__device__ __forceinline__ EpiIn qkv_epi_in(int t) {
    EpiIn e;
    #pragma unroll
    for (int jj = 0; jj < 4; jj++) e.c2[jj] = lds64f(SB + OFF_CS + (HH * 32 + jj * 8) * 4 + t * 8);
    e.hs = ldsf(SB + OFF_M + M_SC + HH * 4);
    return e;
}
template <int HH, int NEXT>
__device__ __forceinline__ void qkv_epi_head(const float (&acc0)[96], const float (&acc1)[96], const float (&cf)[4], const float (&nm)[4], EpiIn& in, uint32_t dst, int t) {
    const EpiIn e = in;
    #pragma unroll
    for (int i = 0; i < 4; i++) {
        const float* a = (i >> 1) ? acc1 : acc0;
        const float sc = cf[i] * e.hs;
        uint32_t pk[4];
        #pragma unroll
        for (int jj = 0; jj < 4; jj++)
            pk[jj] = pack_f16(fmaf(nm[i], e.c2[jj].x, a[4 * (4 * HH + jj) + 2 * (i & 1)]) * sc, fmaf(nm[i], e.c2[jj].y, a[4 * (4 * HH + jj) + 2 * (i & 1) + 1]) * sc);
        #pragma unroll
        for (int jj = 0; jj < 4; jj++) if (HH >= 2) pk[jj] = round8(pk[jj]);
        stsm4(dst + (i >> 1) * (HH < 2 ? 4096 : 1024) + (i & 1) * 128, pk[0], pk[1], pk[2], pk[3]);
        if (i == 1 && NEXT >= 0) in = qkv_epi_in<NEXT < 0 ? 0 : NEXT>(t);
    }
}
__device__ __forceinline__ void qkv_patch(int lane, uint32_t on) {
    __syncwarp();
    asm volatile("{\n.reg .pred q;\n.reg .b32 a, x, y, z, w;\nsetp.ne.u32 q, %2, 0;\nld.shared.v4.b32 {x, y, z, w}, [%0];\nld.shared.b32 a, [%1];\n"
                 "@q st.shared.v4.b32 [a], {x, y, z, w};\n}" :: "r"(SB + OFF_FIX + lane * 16), "r"(SB + OFF_FIX + 512 + lane * 4), "r"(on) : "memory");
}

template <bool INIT>
__device__ __forceinline__ void qkv_step(float (&acc0)[96], float (&acc1)[96], uint32_t st, int wg) {
    const uint64_t da = desc_sw128(SB, 16, 1024) + ((st * Q_STB + wg * 16384) >> 4);
    const uint64_t db = desc_sw128(SB + Q_ABYTES, 8192, 1024) + ((st * Q_STB) >> 4);
    wg_fence();
    if (INIT) { wg_gemm_n192_init(acc0, da, db); wg_gemm_n192_init(acc1, da + (8192 >> 4), db); }
    #pragma unroll
    for (int kk = INIT ? 1 : 0; kk < 4; kk++) {
        wg_gemm_n192(acc0, da + kk * 2, db + kk * 128);
        wg_gemm_n192(acc1, da + (8192 >> 4) + kk * 2, db + kk * 128);
    }
    wg_commit();
}
__device__ __forceinline__ void qkv_phase(int L, int wg) {
    const uint32_t rb = L * 32;
    float acc0[96], acc1[96];
    const bool leader = (tid_now() & 127) == 0;
    mbar_wait(rb + B_QF, 0);
    qkv_step<true>(acc0, acc1, 0, wg);
    uint32_t st = 1, ph = 0;
    #pragma unroll 1
    for (int k = 1; k < 16; k++) {
        mbar_wait(rb + B_QF + 8 * st, ph);
        qkv_step<false>(acc0, acc1, st, wg);
        wg_wait<1>();
        if (leader) mbar_arrive(rb + B_QE + 8 * (st == 0 ? 2 : st - 1));
        if (++st == 3) { st = 0; ph ^= 1; }
    }
    const int tid = tid_now(), lane = tid & 31, w = (tid >> 5) & 3, g = lane >> 2, t = lane & 3;
    mbar_wait(B_EPI, L);
    float cf[4], nm[4];
    #pragma unroll
    for (int i = 0; i < 4; i++) { const float2 r = lds64f(SB + OFF_RC + (wg * 128 + w * 16 + g + (i >> 1) * 64 + (i & 1) * 8) * 8); cf[i] = r.x; nm[i] = -r.y; }
    const int d = (int)lds32(SB + OFF_M + M_RIDX) - (cta_now() >> 4) * 256;
    const uint32_t own = L == 1 && (d >> 7) == wg && ((d >> 4) & 3) == w ? 1u << lane : 0u;
    EpiIn in = qkv_epi_in<2>(t);
    wg_wait<0>();
    named_sync(1, 256);
    const uint32_t dk = SB + wg * 2048 + (lane >> 3) * 4096 + (w * 16 + (lane & 7)) * 16;
    const uint32_t dq = SB + OFF_QA + wg * 8192 + (lane >> 3) * 1024 + (w * 16 + (lane & 7)) * 16;
    qkv_epi_head<2, 4>(acc0, acc1, cf, nm, in, dk, t);
    qkv_patch(lane, own & 0x000F00u);
    fence_async_smem();
    __syncwarp();
    mbar_arrive_elect(B_K0);
    qkv_epi_head<4, 0>(acc0, acc1, cf, nm, in, dk + 16384, t);
    qkv_patch(lane, own & 0x0F0000u);
    #pragma unroll
    for (int s = 0; s < 3; s++) sts128(SB + s * A_WIN + KV_WIN + tid * 16, make_uint4(0x3C003C00u, 0x3C003C00u, 0x3C003C00u, 0x3C003C00u));
    fence_async_smem();
    __syncwarp();
    mbar_arrive_elect(B_KV0);
    qkv_epi_head<0, 1>(acc0, acc1, cf, nm, in, dq, t);
    qkv_epi_head<1, 3>(acc0, acc1, cf, nm, in, dq + 16384, t);
    qkv_epi_head<3, 5>(acc0, acc1, cf, nm, in, dk + OFF_FE, t);
    qkv_epi_head<5, -1>(acc0, acc1, cf, nm, in, dk + OFF_FE + 16384, t);
    qkv_patch(lane, own & 0xF0F0FFu);
    fence_async_smem();
    named_sync(3 + wg, 128);
}

struct Unit {
    uint32_t o[8];
    uint32_t l, bz, sc;
    uint32_t ch[2];
};
template <int H> __device__ __forceinline__ uint32_t hdup(uint32_t v) {
    uint32_t r;
    if (H) asm("{.reg .b16 l, h; mov.b32 {l, h}, %1; mov.b32 %0, {h, h};}" : "=r"(r) : "r"(v));
    else asm("{.reg .b16 l, h; mov.b32 {l, h}, %1; mov.b32 %0, {l, l};}" : "=r"(r) : "r"(v));
    return r;
}
__device__ __forceinline__ uint32_t hmax2(uint32_t a, uint32_t b) { uint32_t r; asm("max.f16x2 %0, %1, %2;" : "=r"(r) : "r"(a), "r"(b)); return r; }
__device__ __forceinline__ uint32_t hadd2(uint32_t a, uint32_t b) { uint32_t r; asm("add.rn.f16x2 %0, %1, %2;" : "=r"(r) : "r"(a), "r"(b)); return r; }
__device__ __forceinline__ uint32_t hsub2(uint32_t a, uint32_t b) { uint32_t r; asm("sub.rn.f16x2 %0, %1, %2;" : "=r"(r) : "r"(a), "r"(b)); return r; }
__device__ __forceinline__ uint32_t hfma2(uint32_t a, uint32_t b, uint32_t c) { uint32_t r; asm("fma.rn.f16x2 %0, %1, %2, %3;" : "=r"(r) : "r"(a), "r"(b), "r"(c)); return r; }
__device__ __forceinline__ uint32_t exp2_h2(uint32_t s, uint32_t bz, uint32_t& ch) {
    uint32_t z, w, d;
    asm("fma.rn.relu.f16x2 %0, %1, %2, %3;" : "=r"(z) : "r"(s), "r"(0x00400040u), "r"(bz));
    asm("lop3.b32 %0, %1, 0x003F003F, %0, 0xC2;" : "+r"(ch) : "r"(z));
    asm("fma.rn.f16x2 %0, %1, %2, %3;" : "=r"(w) : "r"(ch), "r"(0x30A630A6u), "r"(0xACCCACCCu));
    asm("{.reg .b32 n; neg.f16x2 n, %1; fma.rn.relu.f16x2 %0, n, %1, %2;}" : "=r"(d) : "r"(w), "r"(0x00580058u));
    return (z << 4) - d;
}
__device__ __forceinline__ void exp_tile(uint32_t (&p)[32], const uint32_t (&s)[32], Unit& u) {
    #pragma unroll
    for (int j = 0; j < 32; j++) {
        const int i = (j & 1) | (j & 6) << 2 | (j & 24) >> 2;
        p[i] = exp2_h2(s[i], (i & 1) ? hdup<1>(u.bz) : hdup<0>(u.bz), u.ch[i & 1]);
    }
}
struct QOp { uint32_t r[4]; uint64_t d; };
__device__ __forceinline__ void issue_qk(uint32_t (&s)[32], const QOp& q, uint64_t dk) {
    wg_qk_init(s, q.r[0], q.r[1], q.r[2], q.r[3], dk); wg_qk_acc(s, q.d, dk + (8192 >> 4));
    wg_commit();
}
template <bool INIT>
__device__ __forceinline__ void issue_pv(uint32_t (&h)[10], const uint32_t (&p)[32], uint64_t dv) {
    #pragma unroll
    for (int k = 0; k < 8; k++) {
        if (INIT && k == 0) wg_pv_init(h, p[0], p[1], p[2], p[3], dv);
        else wg_pv_acc(h, p[4*k], p[4*k+1], p[4*k+2], p[4*k+3], dv + k * 16);
    }
    wg_commit();
}
__device__ __forceinline__ void unit_init(Unit& u, const uint32_t (&s)[32], uint32_t ok) {
    uint32_t m0 = s[0], m1 = s[1];
    #pragma unroll
    for (int i = 1; i < 16; i++) { m0 = hmax2(m0, s[2 * i]); m1 = hmax2(m1, s[2 * i + 1]); }
    uint32_t m = hmax2(__byte_perm(m0, m1, 0x5410), __byte_perm(m0, m1, 0x7632));
    m = hmax2(m, __shfl_xor_sync(0xffffffffu, m, 1)); m = hmax2(m, __shfl_xor_sync(0xffffffffu, m, 2));
    const uint32_t q = hfma2(m, 0x80048004u, 0x003E003Eu);
    u.bz = hfma2(q, 0x4C004C00u, 0x80008000u);
    u.ch[0] = u.ch[1] = ok & ~hadd2(q, q);
    u.sc = 0u; u.l = 0u;
    #pragma unroll
    for (int i = 0; i < 8; i++) u.o[i] = 0u;
}
template <bool MORE>
__device__ __forceinline__ void unit_flush(Unit& u, const uint32_t (&h)[10]) {
    u.l = hfma2(u.l, u.sc, __byte_perm(h[8], h[9], 0x5410));
    #pragma unroll
    for (int i = 0; i < 8; i++) u.o[i] = hfma2(u.o[i], (i & 1) ? hdup<1>(u.sc) : hdup<0>(u.sc), h[i]);
    if (MORE) {
        const uint32_t ex = u.l & 0x7C007C00u;
        u.sc = 0x84008400u - ex;
        u.bz = hsub2(hadd2(u.bz, 0x04800480u), ex >> 4);
    }
}
__device__ __forceinline__ char* o_block(int wg, int pass) { const int c = cta_now(); return g_o + (size_t)((((c >> 4) * 2 + wg) * 2 + pass) * 16 + (c & 15)) * 8192; }
__device__ __forceinline__ uint32_t unit_finish(Unit& u, float ivs) {
    float lf[2]; h2_unpack(u.l, lf[0], lf[1]);
    #pragma unroll
    for (int i = 0; i < 8; i++) { float x, y; h2_unpack(u.o[i], x, y); const float inv = ivs * rcp(lf[i & 1]); u.o[i] = pack_bf16(x * inv, y * inv); }
    return ((~u.ch[0] & CH_OK) != 0 || (u.l << 16) - 0x40000000u >= 0x3C000000u ? 1u : 0u) | ((~u.ch[1] & CH_OK) != 0 || u.l - 0x40000000u >= 0x3C000000u ? 2u : 0u);
}
__device__ __forceinline__ void unit_store(const Unit& u, char* dst) {
    #pragma unroll
    for (int i = 0; i < 8; i++) *reinterpret_cast<uint32_t*>(dst + (i >> 1) * 1024 + (i & 1) * 128) = u.o[i];
}
__device__ __noinline__ void exact_rows(int L, int pass, int wg, uint32_t bad) {
    const int tid = tid_now() & 127, lane = tid & 31, w = tid >> 5, t = lane & 3;
    const int head = (cta_now() & 15) * 2 + pass;
    const uint32_t scr = SB + OFF_PART + wg * 1024;
    bad = redux_or(bad << (lane & 28));
    if (lane == 0) sts32(scr + w * 4, bad);
    ctr_wait_all(&g_kvc[L][head][lane & 7], 3);
    named_sync(3 + wg, 128);
    const float isc = ldsf(SB + OFF_M + M_ISC + pass * 4), ivs = ldsf(SB + OFF_M + M_IVS + pass * 4);
    const char* kv = g_kv + (size_t)(head * 8 + w * 2) * KV_WIN + t * 4096 + (lane >> 2) * 16;
    #pragma unroll 1
    for (int ww = 0; ww < 4; ww++)
    #pragma unroll 1
    for (uint32_t m = lds32(scr + ww * 4); m; m &= m - 1) {
        const int bit = __ffs(m) - 1;
        const uint32_t ro = (bit & 2) * 2048 + (ww * 16 + (bit & 1) * 8 + (bit >> 2)) * 16;
        const uint4 q = lds128(SB + OFF_QA + pass * 16384 + wg * 8192 + ro + t * 1024);
        float a[9], mx = -INFINITY;
        #pragma unroll
        for (int i = 0; i < 9; i++) a[i] = 0.f;
        #pragma unroll 1
        for (int it = 0; it < 8; it++) {
            uint4 k[8], v[8];
            #pragma unroll
            for (int i = 0; i < 8; i++) {
                const char* p = kv + (it >> 2) * KV_WIN + (it & 3) * 1024 + i * 128;
                k[i] = __ldcg(reinterpret_cast<const uint4*>(p)); v[i] = __ldcg(reinterpret_cast<const uint4*>(p + 16384));
            }
            float s[8], mn = mx;
            #pragma unroll
            for (int i = 0; i < 8; i += 2) {
                float c[4] = {0.f, 0.f, 0.f, 0.f};
                mma_f16(c, k[i].x, k[i + 1].x, k[i].y, k[i + 1].y, q.x, q.y);
                mma_f16(c, k[i].z, k[i + 1].z, k[i].w, k[i + 1].w, q.z, q.w);
                s[i] = c[0]; s[i + 1] = c[2];
                mn = fmaxf(mn, fmaxf(c[0], c[2]));
            }
            const float al = ex2((mx - mn) * isc);
            mx = mn;
            #pragma unroll
            for (int i = 0; i < 9; i++) a[i] *= al;
            #pragma unroll
            for (int i = 0; i < 8; i++) {
                const float p = ex2((s[i] - mx) * isc);
                const uint32_t u[4] = {v[i].x, v[i].y, v[i].z, v[i].w};
                a[8] += p;
                #pragma unroll
                for (int e = 0; e < 4; e++) { float x, y; h2_unpack(u[e], x, y); a[2 * e] = fmaf(p, x, a[2 * e]); a[2 * e + 1] = fmaf(p, y, a[2 * e + 1]); }
            }
        }
        #pragma unroll 1
        for (int o = 4; o < 32; o <<= 1) {
            const float mn = fmaxf(mx, __shfl_xor_sync(0xffffffffu, mx, o)), al = ex2((mx - mn) * isc);
            mx = mn;
            #pragma unroll
            for (int i = 0; i < 9; i++) { a[i] *= al; a[i] += __shfl_xor_sync(0xffffffffu, a[i], o); }
        }
        named_sync(3 + wg, 128);
        const uint32_t mine = scr + 16 + w * 144;
        sts128(mine + t * 32, make_uint4(__float_as_uint(a[0]), __float_as_uint(a[1]), __float_as_uint(a[2]), __float_as_uint(a[3])));
        sts128(mine + t * 32 + 16, make_uint4(__float_as_uint(a[4]), __float_as_uint(a[5]), __float_as_uint(a[6]), __float_as_uint(a[7])));
        sts64f(mine + 128, a[8], mx);
        named_sync(3 + wg, 128);
        float o = 0.f, l = 0.f;
        mx = -INFINITY;
        #pragma unroll 1
        for (int i = 0; i < 4; i++) {
            const float2 e = lds64f(scr + 16 + i * 144 + 128);
            const float mn = fmaxf(mx, e.y), al = ex2((mx - mn) * isc), be = ex2((e.y - mn) * isc);
            mx = mn;
            o = fmaf(o, al, be * ldsf(scr + 16 + i * 144 + lane * 4)); l = fmaf(l, al, be * e.x);
        }
        if (w == 0) *reinterpret_cast<unsigned short*>(o_block(wg, pass) + ro + (lane >> 3) * 1024 + (lane & 7) * 2) = (unsigned short)pack_bf16(o * ivs * rcp(l), 0.f);
    }
}

__device__ __forceinline__ void attention_phase(int L, int wg) {
    const uint32_t rb = L * 32;
    constexpr uint64_t dk0 = desc_plain(SB, 4096, 128), dv0 = desc_plain(SB + 16384, 128, 4096);
    constexpr int T1 = 2048 >> 4;
    uint32_t st = 0, ph = 0;
    #pragma unroll 1
    for (int pass = 0; pass < 2; pass++) {
        QOp dqa, dqc;
        dqa.d = desc_plain(SB + OFF_QA + 2048, 1024, 128) + (pass * 4 + wg * 2) * (4096 >> 4); dqc.d = dqa.d + (4096 >> 4);
        {
            const int tid = tid_now();
            const uint32_t a0 = SB + OFF_QA + (pass * 4 + wg * 2) * 4096 + ((tid >> 4) & 1) * 1024 + (((tid >> 5) & 3) * 16 + (tid & 15)) * 16;
            ldsm4(dqa.r[0], dqa.r[1], dqa.r[2], dqa.r[3], a0); ldsm4(dqc.r[0], dqc.r[1], dqc.r[2], dqc.r[3], a0 + 4096);
        }
        Unit a, c;
        st = warp_uniform(st); ph = warp_uniform(ph);
        uint32_t SA[32], SC[32], PA[32], PC[32], ha[10], hc[10], bad;
        #pragma unroll
        for (int i = 0; i < 10; i++) hc[i] = 0u;
        #pragma unroll
        for (int i = 0; i < 32; i++) PC[i] = 0u;
        const uint32_t ok = lds32(SB + OFF_M + M_OK + pass * 4);
        mbar_wait(rb + B_AF + 8 * st, ph);
        wg_fence();
        issue_qk(SA, dqa, dk0 + st * (A_WIN >> 4));
        issue_qk(SC, dqc, dk0 + st * (A_WIN >> 4));
        wg_wait<1>();
        unit_init(a, SA, ok);
        exp_tile(PA, SA, a);
        wg_wait<0>();
        unit_init(c, SC, ok);
        uint32_t eb = 0;
        #pragma unroll 1
        for (int s = 0;; s++) {
            const uint64_t dkb = dk0 + st * (A_WIN >> 4), dvb = dv0 + st * (A_WIN >> 4);
            if (__builtin_expect(s == 8 * gridDim.y, 0)) {
                wg_wait<0>();
                bad = 0;
                #pragma unroll
                for (int i = 0; i < 32; i++) bad |= PC[i];
                break;
            }
            wg_fence();
            issue_pv<true>(ha, PA, dvb); issue_qk(SA, dqa, dkb + T1);
            wg_wait<2>();
            if (s > 0) { mbar_arrive_elect(eb); unit_flush<true>(c, hc); }
            exp_tile(PC, SC, c);
            wg_fence();
            issue_pv<true>(hc, PC, dvb); issue_qk(SC, dqc, dkb + T1);
            wg_wait<2>();
            exp_tile(PA, SA, a);
            eb = rb + B_AE + 8 * st;
            if (++st == 3) { st = 0; ph ^= 1; }
            if (s == 7) {
                wg_fence(); issue_pv<false>(ha, PA, dvb + T1);
                wg_wait<1>();
                exp_tile(PC, SC, c);
                wg_fence(); issue_pv<false>(hc, PC, dvb + T1);
                wg_wait<1>();
                const int tid = tid_now();
                const float ivs = ldsf(SB + OFF_M + M_IVS + pass * 4);
                char* dst = o_block(wg, pass) + (tid & 96) * 8 + (tid & 31) * 4;
                unit_flush<false>(a, ha);
                bad = unit_finish(a, ivs);
                wg_wait<0>();
                mbar_arrive_elect(eb);
                unit_store(a, dst);
                unit_flush<false>(c, hc);
                bad |= unit_finish(c, ivs) << 2;
                unit_store(c, dst + 4096);
                break;
            }
            const uint64_t dkn = dk0 + st * (A_WIN >> 4);
            mbar_wait(rb + B_AF + 8 * st, ph);
            wg_fence();
            issue_pv<false>(ha, PA, dvb + T1); issue_qk(SA, dqa, dkn);
            wg_wait<2>();
            exp_tile(PC, SC, c);
            wg_fence();
            issue_pv<false>(hc, PC, dvb + T1); issue_qk(SC, dqc, dkn);
            wg_wait<2>();
            unit_flush<true>(a, ha);
            exp_tile(PA, SA, a);
        }
        if (__builtin_expect(named_any(bad != 0, 3 + wg), 0)) {
            exact_rows(L, pass, wg, bad);
        }
        named_arrive(N_OST + 2 * pass + wg, pass > wg ? 192 : 160);
    }
}

template <bool INIT>
__device__ __forceinline__ void oproj_step(float (&acc)[64], uint32_t s, int wg) {
    const uint64_t da = desc_plain(SB, 1024, 128) + ((o_stage(s) + wg * 4096) >> 4);
    const uint64_t db = desc_sw128(SB + 16384, 8192, 1024) + (o_stage(s) >> 4);
    wg_fence();
    if (INIT) wg_gemm_n128_init(acc, da, db);
    #pragma unroll
    for (int kk = INIT ? 1 : 0; kk < 4; kk++) wg_gemm_n128(acc, da + (kk >> 1) * 512 + (kk & 1) * 128, db + kk * 128);
    wg_commit();
}
__device__ __forceinline__ void oproj_phase(int L, int wg, bf16* __restrict__ out) {
    const int c = cta_now(), tid = tid_now(), lane = tid & 31, W = tid >> 5, g = lane >> 2, t = lane & 3;
    const int row0 = (c >> 4) * 256 + (c & 1) * 128, col0 = ((c & 15) >> 1) * 128;
    float acc[64];
    mbar_wait(B_OF, 0);
    oproj_step<true>(acc, 0, wg);
    const uint32_t xa = SB + OFF_XT + (W * 16 + ((lane >> 3) & 1) * 8 + (lane & 7)) * 128, xs = (lane >> 4) ^ (lane & 7);
    mbar_wait(B_RES2, L);
    const float2 c0 = lds64f(SB + OFF_LC + (W * 16 + g) * 8), c1 = lds64f(SB + OFF_LC + (W * 16 + g + 8) * 8);
    #pragma unroll 1
    for (int k = 1; k < 16; k++) {
        mbar_wait(B_OF + 8 * (k & 3), (k >> 2) & 1);
        oproj_step<false>(acc, k & 3, wg);
        wg_wait<1>();
        if ((tid & 127) == 0) mbar_arrive(B_OE + 8 * ((k - 1) & 3));
        if (L == 1 && (k & 1)) {
            const uint32_t a = xa + (k & 8) * 2048 + ((xs ^ (k & 6)) << 4);
            uint32_t v0, v1, v2, v3;
            ldsm4(v0, v1, v2, v3, a);
            stsm4(a, add_ln2(v0, c0.x, c0.y), add_ln2(v1, c1.x, c1.y), add_ln2(v2, c0.x, c0.y), add_ln2(v3, c1.x, c1.y));
        }
    }
    uint32_t x[32];
    const uint32_t wra = SB + OFF_WR + (g == 4 ? t * 8 : 256), wrs = g == 4 ? 32 : 0;
    float2 wb[8];
    #pragma unroll
    for (int ks = 0; ks < 8; ks++) {
        ldsm4(x[4*ks], x[4*ks+1], x[4*ks+2], x[4*ks+3], xa + (ks >> 2) * 16384 + ((xs ^ ((ks & 3) * 2)) << 4));
        wb[ks] = lds64f(wra + ks * wrs);
    }
    wg_wait<0>();
    if ((tid & 127) == 0) mbar_arrive(B_OE + 24);
    {
        float sd[4] = {0.f, 0.f, 0.f, 0.f}, z0[4] = {0.f, 0.f, 0.f, 0.f}, z1[4] = {0.f, 0.f, 0.f, 0.f};
        #pragma unroll
        for (int ks = 0; ks < 8; ks++) {
            #pragma unroll
            for (int i = 0; i < 4; i++) x[4*ks + i] = badd2(x[4*ks + i], pack_bf16(acc[8*ks + 2*i], acc[8*ks + 2*i + 1]));
            mma_bf16(sd, x[4*ks], x[4*ks+1], x[4*ks+2], x[4*ks+3], __float_as_uint(wb[ks].x), __float_as_uint(wb[ks].y));
            mma_bf16(z0, x[4*ks], x[4*ks+1], x[4*ks+2], x[4*ks+3], x[4*ks], x[4*ks+2]);
            mma_bf16(z1, x[4*ks], x[4*ks+1], x[4*ks+2], x[4*ks+3], x[4*ks+1], x[4*ks+3]);
        }
        const float s0 = __shfl_sync(0xffffffffu, (g & 1) ? z0[1] : z0[0], 4 * g + (g >> 1));
        const float s1 = __shfl_sync(0xffffffffu, (g & 1) ? z1[3] : z1[2], 4 * g + (g >> 1));
        double* p = &g_acc[L][row0 + W * 16 + g][t];
        asm volatile("red.relaxed.gpu.global.add.f64 [%0], %1;" :: "l"(p), "d"((double)sel4(t, sd[0], s0, sd[0], 1.f)) : "memory");
        asm volatile("red.relaxed.gpu.global.add.f64 [%0], %1;" :: "l"(p + 32), "d"((double)sel4(t, sd[2], s1, sd[2], 1.f)) : "memory");
    }
    if (L == 0) {
        #pragma unroll
        for (int ks = 0; ks < 8; ks++) stsm4(xa + (ks >> 2) * 16384 + ((xs ^ ((ks & 3) * 2)) << 4), x[4*ks], x[4*ks+1], x[4*ks+2], x[4*ks+3]);
        fence_async_smem();
        named_arrive(N_XST + wg, 160);
    }
    const bool ffn = c < NFC;
    uint4 fa[32], fd[16];
    const uint32_t ga = SB + W * 2048 + ((lane >> 4) * 8 + (lane & 7)) * 64 + ((((lane >> 3) & 1) ^ ((lane >> 1) & 3)) << 4);
    if (ffn) mbar_wait(B_FE, L);
    #pragma unroll
    for (int i = 0; i < 12; i++) ldsm4t(fa[i].x, fa[i].y, fa[i].z, fa[i].w, (ga ^ ((i & 1) * 32)) + gu_piece(i >> 2) + (i & 2) * 512);
    float2 r0, r1;
    {
        const float ws = ldsf(SB + OFF_M + M_WS);
        const uint32_t row = row0 + W * 16 + g;
        const bool odd = t & 1, up = t & 2;
        const uint32_t me = row + (odd ? 8 : 0);
        uint4 v;
        uint32_t n = 0;
        do { v = ld_relaxed4(&g_acc[L][me][t & 2]); } while (__any_sync(0xffffffffu, up && v.w != 0x40200000u) && ++n < SPIN_MAX);
        spin_check(n);
        const float f0 = (float)__hiloint2double(v.y, v.x), f1 = (float)__hiloint2double(v.w, v.z);
        const float e0 = __shfl_xor_sync(0xffffffffu, f0, 2), e1 = __shfl_xor_sync(0xffffffffu, f1, 2);
        const float a[3] = {up ? e0 : f0, up ? e1 : f1, up ? f0 : e0};
        const uint4 tot = make_uint4(not_sent(a[0]), not_sent(a[1]), 0u, 0u);
        st_relaxed4_if(&g_sums[me], tot, L == 0 && col0 == 0 && t < 2);
        const float2 r = ln_coef(tot), ro = make_float2(__shfl_xor_sync(0xffffffffu, r.x, 1), __shfl_xor_sync(0xffffffffu, r.y, 1));
        r0 = odd ? ro : r; r1 = odd ? r : ro;
        const uint32_t k = min(order_bits(r.x * fmaf(-r.y, ws, a[2])), SENT - 1);
        const uint32_t m = redux_max(k), mrow = redux_min(k == m ? me : 0x7FFFFFFFu);
        if (me == mrow) sts128(SB + OFF_RT + W * 16, make_uint4(k, me, not_sent(r.y), not_sent(r.x)));
    }
    named_sync(1, 256);
    {
        const uint4 e = lds128(SB + OFF_RT + (lane & 7) * 16);
        const uint32_t m = redux_max(e.x), row = redux_min(e.x == m ? e.y : 0x7FFFFFFFu);
        const int lr = row - row0;
        st_relaxed4_if(&g_tab[L][(c & 15) >> 1][row0 >> 7][(lane >> 3) & 1], e, W == ((lr >> 4) ^ 1) && e.y == row && lane < 16);
        if ((lr >> 4) == W) {
            const bool hi = lr & 8;
            uint32_t* dst = &g_xrow[L][row0 >> 7][(col0 & 128) * 2 + (col0 >> 8) * 16 + t * 4];
            #pragma unroll
            for (int i = 0; i < 4; i++)
                st_relaxed4_if(dst + i * 64, make_uint4(min(hi ? x[8*i+1] : x[8*i], SENT - 1), min(hi ? x[8*i+3] : x[8*i+2], SENT - 1),
                               min(hi ? x[8*i+5] : x[8*i+4], SENT - 1), min(hi ? x[8*i+7] : x[8*i+6], SENT - 1)), g == (lr & 7));
        }
        __syncwarp();
    }
    if (L == 1) {
        const float b0 = -r0.x * r0.y, b1 = -r1.x * r1.y;
        #pragma unroll
        for (int ks = 0; ks < 8; ks++)
            stsm4(xa + (ks >> 2) * 16384 + ((xs ^ ((ks & 3) * 2)) << 4), add_ln2(x[4*ks], r0.x, b0), add_ln2(x[4*ks+1], r1.x, b1),
                  add_ln2(x[4*ks+2], r0.x, b0), add_ln2(x[4*ks+3], r1.x, b1));
        fence_async_smem();
        named_arrive(N_XST + wg, 160);
    }
    RouteOut rt;
    {
        const uint4* tp = &g_tab[L][(c & 15) >> 1][lane & 15][0];
        uint4 e = ld_relaxed4(tp);
        if (ffn) mbar_wait(B_FL, L);
        #pragma unroll
        for (int i = 12; i < 32; i++) ldsm4t(fa[i].x, fa[i].y, fa[i].z, fa[i].w, (ga ^ ((i & 1) * 32)) + gu_piece(i >> 2) + (i & 2) * 512);
        if (L == 0) named_arrive(N_GD, 288);
        uint32_t n = 0;
        while (has_sent(e) && ++n < SPIN_MAX) e = ld_relaxed4(tp);
        spin_check(n);
        __syncwarp();
        e = warp_best(e);
        rt = route_out(e);
        if (W == 7 && L == 0) { sts128(SB + OFF_RT + 128, e); named_arrive(N_RT, 128); }
    }
    uint2 xrow;
    {
        const uint32_t* xp = &g_xrow[L][rt.idx >> 7][W * 64 + (g >> 1) * 16 + t * 4 + (g & 1) * 2];
        xrow = ld_relaxed2(xp);
        if (ffn) mbar_wait(B_FD, L);
        const uint32_t wa = SB + OFF_FD + W * 8192 + ((lane >> 4) * 8 + (lane & 7)) * 128 + ((((lane >> 3) & 1) ^ (lane & 7)) << 4);
        #pragma unroll
        for (int i = 0; i < 16; i++) ldsm4t(fd[i].x, fd[i].y, fd[i].z, fd[i].w, (wa ^ (((i >> 1) & 3) * 32)) + (i >> 3) * 4096 + (i & 1) * 2048);
        if (L == 0) named_arrive(N_DD, 288);
        uint32_t n = 0;
        while ((xrow.x == SENT || xrow.y == SENT) && ++n < SPIN_MAX) xrow = ld_relaxed2(xp);
        spin_check(n);
        __syncwarp();
    }
    {
        const float nb = -rt.mean * rt.rstd;
        const uint32_t n0 = pack_bf16(fmaf(bf_lo(xrow.x), rt.rstd, nb), fmaf(bf_hi(xrow.x), rt.rstd, nb));
        const uint32_t n1 = pack_bf16(fmaf(bf_lo(xrow.y), rt.rstd, nb), fmaf(bf_hi(xrow.y), rt.rstd, nb));
        float gu[4][4];
        #pragma unroll
        for (int i = 0; i < 4; i++) { gu[i][0] = 0.f; gu[i][1] = 0.f; gu[i][2] = 0.f; gu[i][3] = 0.f; }
        #pragma unroll
        for (int ks = 0; ks < 8; ks++) {
            const uint32_t b0 = __shfl_sync(0xffffffffu, n0, 4 * ks + t), b1 = __shfl_sync(0xffffffffu, n1, 4 * ks + t);
            #pragma unroll
            for (int i = 0; i < 4; i++) {
                const uint4& a = fa[(ks >> 1) * 8 + (i >> 1) * 4 + (ks & 1) * 2 + (i & 1)];
                mma_bf16(gu[i], a.x, a.y, a.z, a.w, b0, b1);
            }
        }
        stsf(SB + OFF_PART + (W * 64 + t * 16 + g) * 4, sel4(t, gu[0][0], gu[1][0], gu[2][0], gu[3][0]));
        stsf(SB + OFF_PART + (W * 64 + t * 16 + g + 8) * 4, sel4(t, gu[0][2], gu[1][2], gu[2][2], gu[3][2]));
    }
    named_sync(1, 256);
    {
        float gp[8], up[8];
        #pragma unroll
        for (int i = 0; i < 8; i++) gp[i] = ldsf(SB + OFF_PART + (i * 64 + lane) * 4);
        #pragma unroll
        for (int i = 0; i < 8; i++) up[i] = ldsf(SB + OFF_PART + (i * 64 + 32 + lane) * 4);
        const float gv = bf_round(((gp[0] + gp[1]) + (gp[2] + gp[3])) + ((gp[4] + gp[5]) + (gp[6] + gp[7])));
        const float uv = bf_round(((up[0] + up[1]) + (up[2] + up[3])) + ((up[4] + up[5]) + (up[6] + up[7])));
        const float hv = bf_round(gv * rcp(1.f + ex2(gv * -1.4426950408889634f))) * uv;
        const uint32_t hp = pack_bf16(hv, __shfl_down_sync(0xffffffffu, hv, 1));
        uint32_t hb[4];
        #pragma unroll
        for (int i = 0; i < 4; i++) hb[i] = __shfl_sync(0xffffffffu, hp, 8 * i + 2 * t);
        float y[8][4];
        #pragma unroll
        for (int mb = 0; mb < 8; mb++) {
            y[mb][0] = 0.f; y[mb][1] = 0.f; y[mb][2] = 0.f; y[mb][3] = 0.f;
            #pragma unroll
            for (int ks = 0; ks < 2; ks++) mma_bf16(y[mb], fd[2*mb + ks].x, fd[2*mb + ks].y, fd[2*mb + ks].z, fd[2*mb + ks].w, hb[2 * ks], hb[2 * ks + 1]);
        }
        st_relaxed4_if(&g_ypart[L][min(c, NFC - 1)][tid * 4], make_uint4(not_sent(sel4(t, y[0][0], y[2][0], y[4][0], y[6][0])), not_sent(sel4(t, y[0][2], y[2][2], y[4][2], y[6][2])),
                       not_sent(sel4(t, y[1][0], y[3][0], y[5][0], y[7][0])), not_sent(sel4(t, y[1][2], y[3][2], y[5][2], y[7][2]))), ffn);
    }
    if (L == 1) {
        if (W == 7) ctr_wait(&g_xc[1][rt.idx >> 8], 32);
        unsigned short* dst = reinterpret_cast<unsigned short*>(out) + (size_t)rt.idx * D_ + ypos_col(c * 8 + (tid & 7));
        asm volatile("" : "+l"(dst));
        const float v = ffn_finish<256>(1, rt, tid, SB + OFF_FE, 1);
        if (tid < 8) asm volatile("st.global.u16 [%0], %1;" :: "l"(dst), "h"((unsigned short)(__float_as_uint(v) >> 16)) : "memory");
    }
}

constexpr int KW1 = 3, FW0 = 11;
constexpr int RK0 = 7;
static_assert(FW0 >= 8 && KW1 >= 3 && KW1 < 7, "buffer reuse");
__device__ __forceinline__ void qkv_fill(const CUtensorMap* tx, const CUtensorMap* tw, uint32_t bar, int st, int k) {
    const uint32_t sa = SB + st * Q_STB;
    mbar_expect_tx(bar, Q_STB);
    tma_load(sa, tx, k * 64, (blockIdx.x >> 4) * 256, bar);
    tma_load3(sa + Q_ABYTES, tw, (blockIdx.x & 15) * 64, k * 64, 0, bar);
}
__device__ __forceinline__ void oproj_fill(const Maps& mp, const char* osrc, int s, int par, int pair, int parts) {
    const uint32_t fb = B_OF + 8 * s, sa = SB + o_stage(s);
    if (parts & 1) { mbar_expect_tx(fb, 32768); bulk_load(sa, osrc + (par * 16 + pair) * 8192, 16384, fb); }
    if (parts & 2) tma_load5(sa + 16384, &mp.wo, 0, 0, par, pair, blockIdx.x & 14, fb);
}
__device__ __forceinline__ void producer_role(const Maps& mp) {
    const int c = blockIdx.x, mt = c >> 4, nt = c & 15, lane = threadIdx.x & 31;
    #pragma unroll 1
    for (int i = 2; i < 12; i++) tm_prefetch(&mp.xa0 + i);
    #pragma unroll 1
    for (int L = 0; L < 2; L++) {
        const uint32_t rb = L * 32;
        uint32_t st = 0, ph = L;
        #pragma unroll 1
        for (int k = L == 0 ? 3 : 0; k < 16; k++) {
            if (k == 0) { ctr_wait_all(&g_xc[0][mt], 32); fence_async_global(); named_sync(N_GD, 288); }
            if (k == 1) named_sync(N_DD, 288);
            mbar_wait(rb + B_QE + 8 * st, ph);
            qkv_fill(L == 0 ? &mp.xa0 : &mp.xa, &mp.wqkv, rb + B_QF + 8 * st, st, k);
            if (L == 1 && k >= RK0 && k < RK0 + 4) {
                if (k == RK0) mbar_expect_tx(B_SW, 4 * 12288);
                tma_load(SB + OFF_SIDE + (k - RK0) * 12288, &mp.r, c * 24, (k - RK0) * 256, B_SW);
            }
            if (++st == 3) { st = 0; ph ^= 1; }
        }
        mbar_wait(B_KV0, L);
        mbar_arrive_elect(rb + B_AF);
        {
            const int win = nt * 16 + ((mt + 1) & 7);
            mbar_expect_tx(rb + B_AF + 8, KV_WIN);
            #pragma unroll 1
            for (int h = 0; h < 2; h++) {
                ctr_wait_all(&g_kvc[L][0][0] + win, 2 + h);
                fence_async_global();
                bulk_load(SB + A_WIN + h * 16384, g_kv + (size_t)win * KV_WIN + h * 16384, 16384, rb + B_AF + 8);
            }
        }
        st = 2; ph = 1;
        #pragma unroll 1
        for (int w = 2; w < 16; w++) {
            const int win = nt * 16 + (w & 8) + ((mt + w) & 7);
            if (w <= 3 || w == 8) {
                ctr_wait_all(&g_kvc[L][0][0] + (w < 3 ? win : (win & ~7) + (lane & 7)), 3);
                fence_async_global();
            }
            mbar_wait(rb + B_AE + 8 * st, ph);
            mbar_expect_tx(rb + B_AF + 8 * st, KV_WIN);
            bulk_load(SB + st * A_WIN, g_kv + (size_t)win * KV_WIN, KV_WIN, rb + B_AF + 8 * st);
            if (w == KW1) named_arrive(N_KV1, 96);
            if (w == FW0) named_arrive(N_FW, 64);
            if (++st == 3) { st = 0; ph ^= 1; }
        }
        ctr_wait_all(&g_oc[L][mt * 2 + (nt & 1)][0][lane & 15], 1);
        fence_async_global();
        const char* osrc = g_o + (size_t)(mt * 2 + (nt & 1)) * 32 * 8192;
        oproj_fill(mp, osrc, 3, 0, 6, 1);
        #pragma unroll
        for (int k = 0; k < 4; k++) {
            mbar_wait(k < 2 ? rb + B_AE + 8 + 8 * k : k == 2 ? rb + B_AE : B_QAF, k < 2 ? 0 : k == 2 ? 1 : L);
            oproj_fill(mp, osrc, k, 0, 2 * k, k == 3 ? 2 : 3);
        }
        uint32_t ready = 0xFFFFu;
        #pragma unroll 1
        for (int k4 = 1; k4 < 4; k4++) {
            #pragma unroll
            for (int s = 0; s < 4; s++) {
                const int p = k4 * 8 + 2 * s;
                if (!((ready >> p) & 1)) {
                    ready = smem_wait_any(SB + OFF_M + M_ORDY + 4 * L, 1u << p);
                    fence_async_global();
                }
                mbar_wait(B_OE + 8 * s, (k4 - 1) & 1);
                oproj_fill(mp, osrc, s, p >> 4, p & 15, 3);
            }
        }
        if (c < NFC) {
            mbar_expect_tx(B_FL, 5 * 16384);
            mbar_expect_tx(B_FD, 4 * 16384);
            #pragma unroll 1
            for (int i = 3; i < 12; i++) {
                mbar_wait(B_OE + (i < 5 ? 0 : i == 5 ? 8 : i < 9 ? 16 : 24), 1);
                if (i == 10) mbar_wait(B_FL, L);
                ffn_load(mp, c, i, SB + (i < 8 ? gu_piece(i) : OFF_FD + (i - 8) * 16384), i < 8 ? B_FL : B_FD, true);
            }
        }
    }
}

__global__ void __launch_bounds__(384, 1) k_all(const bf16* __restrict__ x0, const bf16* __restrict__ wo, const bf16* __restrict__ w_r, bf16* __restrict__ out,
                                                const __grid_constant__ Maps mp) {
    extern __shared__ __align__(1024) char smem[];
    if (smem_u32(smem) != SB) __trap();
    const int warp = warp_uniform(threadIdx.x >> 5), wg = warp >> 2;
    {
        const int grp = warp >= 8 ? warp - 8 : warp + 4;
        #pragma unroll
        for (int i = 0; i < 4; i++) mbar_init(BB + grp * 32 + i * 8, grp < 7 ? 1 : grp < 10 ? 2 : 8);
        fence_mbar_init();
    }
    if (warp == 8) {
        #pragma unroll 1
        for (int s = 0; s < 3; s++) qkv_fill(&mp.xa0, &mp.wqkv, B_QF + 8 * s, s, s);
    }
    __syncthreads();
    if (wg == 2) {
        reg_dec<40>();
        if (warp == 8) producer_role(mp);
        else side_role(mp, x0, wo, w_r);
        if (gridDim.y == 2) {
            uint32_t v = threadIdx.x;
            #pragma unroll
            for (int i = 0; i < 1500; i++) asm volatile("fma.rn.f16x2 %0, %0, %0, %0;" : "+r"(v));
            sts32(SB, v);
        }
    } else {
        reg_inc<232>();
        #pragma unroll 1
        for (int L = 0; L < 2; L++) {
            qkv_phase(L, wg);
            attention_phase(L, wg);
            oproj_phase(L, wg, out);
        }
    }
}

typedef CUresult (*EncodeFn)(CUtensorMap*, CUtensorMapDataType, cuuint32_t, void*, const cuuint64_t*, const cuuint64_t*, const cuuint32_t*,
                             const cuuint32_t*, CUtensorMapInterleave, CUtensorMapSwizzle, CUtensorMapL2promotion, CUtensorMapFloatOOBfill);

void make_map(EncodeFn enc, CUtensorMap* tm, const void* ptr, int rank, const cuuint64_t* dims, const cuuint64_t* strides, const cuuint32_t* box, CUtensorMapSwizzle sw) {
    const cuuint32_t es[5] = {1, 1, 1, 1, 1};
    enc(tm, CU_TENSOR_MAP_DATA_TYPE_BFLOAT16, rank, const_cast<void*>(ptr), dims, strides, box, es, CU_TENSOR_MAP_INTERLEAVE_NONE, sw,
        box[0] == 64 ? CU_TENSOR_MAP_L2_PROMOTION_L2_128B : CU_TENSOR_MAP_L2_PROMOTION_NONE, CU_TENSOR_MAP_FLOAT_OOB_FILL_NONE);
}
void make_map2(EncodeFn enc, CUtensorMap* tm, const void* ptr, uint64_t cols, uint64_t rows, uint32_t bc, uint32_t br, CUtensorMapSwizzle sw) {
    const cuuint64_t dims[2] = {cols, rows}, strides[1] = {cols * 2};
    const cuuint32_t box[2] = {bc, br};
    make_map(enc, tm, ptr, 2, dims, strides, box, sw);
}

}

extern "C" void kernel_launch(void* const* d_in, const int* in_sizes, int n_in, void* d_out, int out_size) {
    const bf16* x0 = (const bf16*)d_in[0];
    const bf16* wqkv = (const bf16*)d_in[1];
    const bf16* wo = (const bf16*)d_in[2];
    const bf16* w_r = (const bf16*)d_in[4];
    const bf16* w_gate = (const bf16*)d_in[5];
    const bf16* w_up = (const bf16*)d_in[6];
    const bf16* w_down = (const bf16*)d_in[7];

    EncodeFn enc = nullptr;
    cudaDriverEntryPointQueryResult qr;
    cudaGetDriverEntryPoint("cuTensorMapEncodeTiled", (void**)&enc, cudaEnableDefault, &qr);
    void* p_x;
    cudaGetSymbolAddress(&p_x, g_x);
    Maps mp;
    const CUtensorMapSwizzle S128 = CU_TENSOR_MAP_SWIZZLE_128B;
    make_map2(enc, &mp.x0, x0, D_, S_, 64, 64, S128);
    make_map2(enc, &mp.x, p_x, D_, S_, 64, 64, S128);
    make_map2(enc, &mp.out, d_out, D_, S_, 64, 64, S128);
    make_map2(enc, &mp.xa0, x0, D_, S_, 64, 256, S128);
    make_map2(enc, &mp.xa, p_x, D_, S_, 64, 256, S128);
    make_map2(enc, &mp.w64, wqkv, 3 * D_, D_, 64, 64, S128);
    {
        const cuuint64_t dims[3] = {D_, D_, 3}, strides[2] = {3 * D_ * 2, D_ * 2};
        const cuuint32_t box[3] = {64, 64, 3};
        make_map(enc, &mp.wqkv, wqkv, 3, dims, strides, box, S128);
    }
    make_map2(enc, &mp.r, wqkv, 3 * D_, D_, 24, 256, CU_TENSOR_MAP_SWIZZLE_NONE);
    make_map2(enc, &mp.g, w_gate, FF, D_, 32, 256, CU_TENSOR_MAP_SWIZZLE_64B);
    make_map2(enc, &mp.u, w_up, FF, D_, 32, 256, CU_TENSOR_MAP_SWIZZLE_64B);
    {
        const cuuint64_t dims[5] = {64, 32, 2, 16, 16}, strides[4] = {D_ * 2, 32 * D_ * 2, 64 * D_ * 2, 128};
        const cuuint32_t box[5] = {64, 32, 1, 2, 2};
        make_map(enc, &mp.wo, wo, 5, dims, strides, box, S128);
    }
    {
        const cuuint64_t dims[3] = {64, FF, 16}, strides[2] = {D_ * 2, 128};
        const cuuint32_t box[3] = {64, 32, 4};
        make_map(enc, &mp.d, w_down, 3, dims, strides, box, S128);
    }
    cudaFuncSetAttribute(k_all, cudaFuncAttributeMaxDynamicSharedMemorySize, K_SMEM);
    k_all<<<128, 384, K_SMEM, cudaStreamPerThread>>>(x0, wo, w_r, (bf16*)d_out, mp);
}
```
